```python
import torch

def _softmax(x, axis=-1):
    return torch.softmax(x, dim=axis)
def _gelu(x):
    return torch.nn.functional.gelu(x, approximate="tanh")
def _silu(x):
    return torch.nn.functional.silu(x)
def _sigmoid(x):
    return torch.sigmoid(x)
def _layernorm(x, axis=-1, eps=1e-5):
    m = x.mean(dim=axis, keepdim=True)
    v = x.var(dim=axis, keepdim=True, unbiased=False)
    return (x - m) / torch.sqrt(v + eps)
def _scatter_add(tgt, idx, src, axis=0):
    return tgt.clone().index_add_(axis, idx, src)
def _segment_sum(src, seg, n):
    out = torch.zeros((n,) + src.shape[1:], dtype=src.dtype)
    return out.index_add_(0, seg, src)
def _pad(x, pw):
    flat = tuple(v for pair in reversed(pw) for v in pair)
    return torch.nn.functional.pad(x, flat)

kernel_name = 'gated_mix__linear_kernel_hedgehog__moe_arch_mod__prompt'

def setup_inputs():

    _w = (lambda a: (lambda t: t.to(torch.bfloat16) if t.is_floating_point() else t)(torch.as_tensor(a)))
    def _A_setup():
        B, S, D, H = 1, 2048, 1024, 32
        Dh = D // H
        return {
            "x": _w((lambda *s: torch.randn(*s, dtype=torch.bfloat16) * 0.05)(B, S, D)),
            "wqkv": _w((lambda *s: torch.randn(*s, dtype=torch.bfloat16) * 1.6)(D, 3 * D)),
            "w_phi": _w((lambda *s: torch.randn(*s, dtype=torch.bfloat16) * 1.6)(H, Dh, Dh) * (Dh ** -0.5)),
            "wo": _w((lambda *s: torch.randn(*s, dtype=torch.bfloat16) * 1.6)(D, D)),
        }
    _A_in = _A_setup()

    def _B_setup():
        B, S, D, F, C = 1, 2048, 1024, 3584, 1
        return {
            "x": _w((lambda *s: torch.randn(*s, dtype=torch.bfloat16) * 0.05)(B, S, D)),
            "w_r": _w((lambda *s: torch.randn(*s, dtype=torch.bfloat16) * 1.6)(D)),
            "w_gate": _w((lambda *s: torch.randn(*s, dtype=torch.bfloat16) * 0.8)(D, F)),
            "w_up": _w((lambda *s: torch.randn(*s, dtype=torch.bfloat16) * 0.8)(D, F)),
            "w_down": _w((lambda *s: torch.randn(*s, dtype=torch.bfloat16) * 0.8)(F, D)),
        }
    _B_in = _B_setup()

    return {
        "A_x": _A_in["x"],
        "A_wqkv": _A_in["wqkv"],
        "A_w_phi": _A_in["w_phi"],
        "A_wo": _A_in["wo"],
        "B_x": _B_in["x"],
        "B_w_r": _B_in["w_r"],
        "B_w_gate": _B_in["w_gate"],
        "B_w_up": _B_in["w_up"],
        "B_w_down": _B_in["w_down"],
        "gate_w": _w((lambda *s: torch.randn(*s, dtype=torch.bfloat16) * 0.05)(1024) * 16.0),
    }

def reference(A_x, A_wqkv, A_w_phi, A_wo, B_x, B_w_r, B_w_gate, B_w_up, B_w_down, gate_w):
    def _A_ref(x, wqkv, w_phi, wo):
        B, S, D = x.shape
        H = 32; Dh = D // H
        qkv = (lambda x, *d: x.permute(*d))((x @ wqkv).reshape(B, S, 3, H, Dh), 2, 0, 3, 1, 4)
        q, k, v = qkv[0], qkv[1], qkv[2]
        pq = torch.einsum("bhsd,hdf->bhsf", q, w_phi)
        pk = torch.einsum("bhsd,hdf->bhsf", k, w_phi)
        phi_q = torch.concatenate([_softmax(pq, axis=-1), _softmax(-pq, axis=-1)], axis=-1)
        phi_k = torch.concatenate([_softmax(pk, axis=-1), _softmax(-pk, axis=-1)], axis=-1)
        kv = torch.einsum("bhsf,bhsd->bhfd", phi_k, v)
        z  = torch.einsum("bhsf->bhf", phi_k)
        num = torch.einsum("bhqf,bhfd->bhqd", phi_q, kv)
        den = torch.einsum("bhqf,bhf->bhq", phi_q, z)[..., None] + 1e-6
        o = num / den
        return (lambda x, *d: x.permute(*d))(o, 0, 2, 1, 3).reshape(B, S, D) @ wo

    def _B_ref(x, w_r, w_gate, w_up, w_down):
        B, S, D = x.shape
        C = 1
        r = x @ w_r
        idx = torch.argsort(-r, axis=-1)[:, :C]
        idx_e = (lambda x, n, axis: torch.repeat_interleave(x, n, dim=axis))(idx.reshape(B, C, 1), D, axis=2)
        x_sel = (lambda x, i, axis: torch.take_along_dim(x, i, dim=axis))(x, idx_e, axis=1)
        g = _silu(x_sel @ w_gate)
        u = x_sel @ w_up
        y = (g * u) @ w_down
        r_sel = _sigmoid((lambda x, i, axis: torch.take_along_dim(x, i, dim=axis))(r, idx, axis=1))
        y = y * r_sel.reshape(B, C, 1)
        b_off = (torch.arange(B) * S).reshape(B, 1)
        flat_idx = (idx + b_off).reshape(B * C)
        zero = (x * 0.0).reshape(B * S, D)
        upd = _scatter_add(zero, flat_idx, y.reshape(B * C, D), axis=0)
        return x + upd.reshape(B, S, D)

    x = A_x
    g = _sigmoid((x * gate_w).sum(-1, keepdims=True))
    a = _A_ref(x, A_wqkv, A_w_phi, A_wo)
    b = _B_ref(x, B_w_r, B_w_gate, B_w_up, B_w_down)
    return g * a + (1 - g) * b
```

```cpp
#include <cuda_runtime.h>
#include <cuda_bf16.h>
#include <cuda.h>
#include <stdint.h>

namespace {

template<int TA, int TB> __device__ __forceinline__ void wgmma_m64n128k16_ss(float (&d)[64], uint64_t da, uint64_t db, int scale_d) {
  asm volatile("{\n.reg .pred p;\nsetp.ne.b32 p, %66, 0;\n"
    "wgmma.mma_async.sync.aligned.m64n128k16.f32.bf16.bf16 "
    "{%0, %1, %2, %3, %4, %5, %6, %7, %8, %9, %10, %11, %12, %13, %14, %15, "
    "%16, %17, %18, %19, %20, %21, %22, %23, %24, %25, %26, %27, %28, %29, %30, %31, "
    "%32, %33, %34, %35, %36, %37, %38, %39, %40, %41, %42, %43, %44, %45, %46, %47, "
    "%48, %49, %50, %51, %52, %53, %54, %55, %56, %57, %58, %59, %60, %61, %62, %63}, "
    "%64, %65, p, 1, 1, %67, %68;\n}\n"
    : "+f"(d[0]), "+f"(d[1]), "+f"(d[2]), "+f"(d[3]), "+f"(d[4]), "+f"(d[5]), "+f"(d[6]), "+f"(d[7]),
      "+f"(d[8]), "+f"(d[9]), "+f"(d[10]), "+f"(d[11]), "+f"(d[12]), "+f"(d[13]), "+f"(d[14]), "+f"(d[15]),
      "+f"(d[16]), "+f"(d[17]), "+f"(d[18]), "+f"(d[19]), "+f"(d[20]), "+f"(d[21]), "+f"(d[22]), "+f"(d[23]),
      "+f"(d[24]), "+f"(d[25]), "+f"(d[26]), "+f"(d[27]), "+f"(d[28]), "+f"(d[29]), "+f"(d[30]), "+f"(d[31]),
      "+f"(d[32]), "+f"(d[33]), "+f"(d[34]), "+f"(d[35]), "+f"(d[36]), "+f"(d[37]), "+f"(d[38]), "+f"(d[39]),
      "+f"(d[40]), "+f"(d[41]), "+f"(d[42]), "+f"(d[43]), "+f"(d[44]), "+f"(d[45]), "+f"(d[46]), "+f"(d[47]),
      "+f"(d[48]), "+f"(d[49]), "+f"(d[50]), "+f"(d[51]), "+f"(d[52]), "+f"(d[53]), "+f"(d[54]), "+f"(d[55]),
      "+f"(d[56]), "+f"(d[57]), "+f"(d[58]), "+f"(d[59]), "+f"(d[60]), "+f"(d[61]), "+f"(d[62]), "+f"(d[63])
    : "l"(da), "l"(db), "r"(scale_d), "n"(TA), "n"(TB));
}

template<int TB> __device__ __forceinline__ void wgmma_m64n32k16_rs(float (&d)[16], const uint32_t (&a)[4], uint64_t db, int scale_d) {
  asm volatile("{\n.reg .pred p;\nsetp.ne.b32 p, %21, 0;\n"
    "wgmma.mma_async.sync.aligned.m64n32k16.f32.bf16.bf16 "
    "{%0, %1, %2, %3, %4, %5, %6, %7, %8, %9, %10, %11, %12, %13, %14, %15}, "
    "{%16, %17, %18, %19}, %20, p, 1, 1, %22;\n}\n"
    : "+f"(d[0]), "+f"(d[1]), "+f"(d[2]), "+f"(d[3]), "+f"(d[4]), "+f"(d[5]), "+f"(d[6]), "+f"(d[7]),
      "+f"(d[8]), "+f"(d[9]), "+f"(d[10]), "+f"(d[11]), "+f"(d[12]), "+f"(d[13]), "+f"(d[14]), "+f"(d[15])
    : "r"(a[0]), "r"(a[1]), "r"(a[2]), "r"(a[3]), "l"(db), "r"(scale_d), "n"(TB));
}

template<int TA, int TB> __device__ __forceinline__ void wgmma_m64n40k16_ss(float (&d)[20], uint64_t da, uint64_t db, int scale_d) {
  asm volatile("{\n.reg .pred p;\nsetp.ne.b32 p, %22, 0;\n"
    "wgmma.mma_async.sync.aligned.m64n40k16.f32.bf16.bf16 "
    "{%0, %1, %2, %3, %4, %5, %6, %7, %8, %9, %10, %11, %12, %13, %14, %15, "
    "%16, %17, %18, %19}, "
    "%20, %21, p, 1, 1, %23, %24;\n}\n"
    : "+f"(d[0]), "+f"(d[1]), "+f"(d[2]), "+f"(d[3]), "+f"(d[4]), "+f"(d[5]), "+f"(d[6]), "+f"(d[7]),
      "+f"(d[8]), "+f"(d[9]), "+f"(d[10]), "+f"(d[11]), "+f"(d[12]), "+f"(d[13]), "+f"(d[14]), "+f"(d[15]),
      "+f"(d[16]), "+f"(d[17]), "+f"(d[18]), "+f"(d[19])
    : "l"(da), "l"(db), "r"(scale_d), "n"(TA), "n"(TB));
}

template<int TB> __device__ __forceinline__ void wgmma_m64n40k16_rs(float (&d)[20], const uint32_t (&a)[4], uint64_t db, int scale_d) {
  asm volatile("{\n.reg .pred p;\nsetp.ne.b32 p, %25, 0;\n"
    "wgmma.mma_async.sync.aligned.m64n40k16.f32.bf16.bf16 "
    "{%0, %1, %2, %3, %4, %5, %6, %7, %8, %9, %10, %11, %12, %13, %14, %15, "
    "%16, %17, %18, %19}, "
    "{%20, %21, %22, %23}, %24, p, 1, 1, %26;\n}\n"
    : "+f"(d[0]), "+f"(d[1]), "+f"(d[2]), "+f"(d[3]), "+f"(d[4]), "+f"(d[5]), "+f"(d[6]), "+f"(d[7]),
      "+f"(d[8]), "+f"(d[9]), "+f"(d[10]), "+f"(d[11]), "+f"(d[12]), "+f"(d[13]), "+f"(d[14]), "+f"(d[15]),
      "+f"(d[16]), "+f"(d[17]), "+f"(d[18]), "+f"(d[19])
    : "r"(a[0]), "r"(a[1]), "r"(a[2]), "r"(a[3]), "l"(db), "r"(scale_d), "n"(TB));
}

constexpr int kS = 2048, kD = 1024, kF = 3584;
constexpr int NST = 5, STAGE = 32768;
constexpr int SM_PHI  = NST * STAGE;
constexpr int SM_V    = SM_PHI + 32768;
constexpr int SM_Z    = SM_V + 16384;
constexpr int SM_WPHI = SM_Z + 4096;
constexpr int SM_XSEL = SM_WPHI + 8192;
constexpr int SM_RED  = SM_XSEL + 4096;
constexpr int SM_G    = SM_RED + 1024;
constexpr int SM_YS   = SM_G + 512;
constexpr int SM_H    = SM_YS + 512;
constexpr int SM_BAR  = SM_H + 128;
constexpr int SM_MISC = SM_BAR + 256;
constexpr int SM_TOTAL = SM_MISC + 64;
static_assert(SM_TOTAL <= 232448, "smem");
constexpr int B_FX = 0, B_FY = 5, B_EM = 10, B_WPHI = 15, B_XT = 16, B_INFO = 17, B_EPOCH = 18, B_KV = 19, B_QS = 20, B_YS = 21, B_PUB = 22;
constexpr int C_ROUTER = 0, C_Y = 32, C_KV = 64, C_O = 64 + 8 * 32;

__device__ float g_kvacc[32 * 4 * 128 * 4];
__device__ float g_zacc[32 * 64];
__device__ float g_yacc[kD];
__device__ float g_gate[kS];
__device__ uint32_t g_key[128];
__device__ uint32_t g_cnt[C_O + 16 * 32];
__device__ __align__(1024) __nv_bfloat16 g_o[kS * kD];
#define TS(id)
#define TSG(id)

struct Params {
  const __nv_bfloat16 *x, *w_r, *w_gate, *w_up, *w_down, *gate_w;
};

constexpr int SPIN_LIMIT = 1 << 18;
__device__ __forceinline__ uint32_t smem_u32(const void* p) { return (uint32_t)__cvta_generic_to_shared(p); }
__device__ __forceinline__ void mbar_init(uint32_t bar, uint32_t cnt) { asm volatile("mbarrier.init.shared::cta.b64 [%0], %1;" :: "r"(bar), "r"(cnt) : "memory"); }
__device__ __forceinline__ void mbar_expect_tx(uint32_t bar, uint32_t bytes) { asm volatile("mbarrier.arrive.expect_tx.shared::cta.b64 _, [%0], %1;" :: "r"(bar), "r"(bytes) : "memory"); }
__device__ __forceinline__ void mbar_arrive(uint32_t bar) { asm volatile("mbarrier.arrive.shared::cta.b64 _, [%0];" :: "r"(bar) : "memory"); }
__device__ __forceinline__ void mbar_arrive_n(uint32_t bar, uint32_t n) { asm volatile("mbarrier.arrive.shared::cta.b64 _, [%0], %1;" :: "r"(bar), "r"(n) : "memory"); }
__device__ __forceinline__ bool mbar_try(uint32_t bar, uint32_t parity) {
  uint32_t ok;
  asm volatile("{\n.reg .pred p;\nmbarrier.try_wait.parity.shared::cta.b64 p, [%1], %2;\nselp.u32 %0, 1, 0, p;\n}" : "=r"(ok) : "r"(bar), "r"(parity) : "memory");
  return ok;
}
__device__ __forceinline__ void mbar_wait(uint32_t bar, uint32_t parity) {
#pragma unroll 1
  for (int it = 0; it < SPIN_LIMIT; it++) if (mbar_try(bar, parity)) break;
}
__device__ __forceinline__ void tma_load(uint32_t dst, const CUtensorMap* m, uint32_t bar, int c0, int c1) {
  asm volatile("cp.async.bulk.tensor.2d.shared::cluster.global.mbarrier::complete_tx::bytes [%0], [%1, {%3, %4}], [%2];"
    :: "r"(dst), "l"(m), "r"(bar), "r"(c0), "r"(c1) : "memory");
}
__device__ __forceinline__ void tma_prefetch(const CUtensorMap* m, int c0, int c1) {
  asm volatile("cp.async.bulk.prefetch.tensor.2d.L2.global [%0, {%1, %2}];" :: "l"(m), "r"(c0), "r"(c1) : "memory");
}
__device__ __forceinline__ void tma_store(const CUtensorMap* m, uint32_t src, int c0, int c1) {
  asm volatile("cp.async.bulk.tensor.2d.global.shared::cta.bulk_group [%0, {%2, %3}], [%1];" :: "l"(m), "r"(src), "r"(c0), "r"(c1) : "memory");
}
__device__ __forceinline__ void prefetch_map(const CUtensorMap* m) { asm volatile("prefetch.tensormap [%0];" :: "l"(m) : "memory"); }
__device__ __forceinline__ bool elect_one() {
  uint32_t p;
  asm volatile("{\n.reg .pred P;\nelect.sync _|P, 0xffffffff;\nselp.u32 %0, 1, 0, P;\n}" : "=r"(p));
  return p;
}
__device__ __forceinline__ void wg_fence() { asm volatile("wgmma.fence.sync.aligned;" ::: "memory"); }
__device__ __forceinline__ void wg_commit() { asm volatile("wgmma.commit_group.sync.aligned;" ::: "memory"); }
template <int N> __device__ __forceinline__ void wg_wait() { asm volatile("wgmma.wait_group.sync.aligned %0;" :: "n"(N) : "memory"); }
template <int N> __device__ __forceinline__ void zero(float (&r)[N]) {
#pragma unroll
  for (int i = 0; i < N; i++) r[i] = 0.f;
}
template <int N> __device__ __forceinline__ void pin(float (&r)[N]) {
#pragma unroll
  for (int i = 0; i < N; i++) asm volatile("" : "+f"(r[i]) :: "memory");
}
__device__ __forceinline__ void fence_async_smem() { asm volatile("fence.proxy.async.shared::cta;" ::: "memory"); }
__device__ __forceinline__ void bar_sync(int id, int n) { asm volatile("bar.sync %0, %1;" :: "r"(id), "r"(n) : "memory"); }
__device__ __forceinline__ void bar_arrive(int id, int n) { asm volatile("bar.arrive %0, %1;" :: "r"(id), "r"(n) : "memory"); }
__device__ __forceinline__ uint64_t make_desc(uint32_t addr, uint32_t lbo, uint32_t sbo, uint32_t swz) {
  return (uint64_t)((addr & 0x3FFFF) >> 4) | ((uint64_t)((lbo & 0x3FFFF) >> 4) << 16) | ((uint64_t)(sbo >> 4) << 32) | ((uint64_t)swz << 62);
}
__device__ __forceinline__ uint32_t pack2(float lo, float hi) {
  uint32_t r; asm("cvt.rn.bf16x2.f32 %0, %1, %2;" : "=r"(r) : "f"(hi), "f"(lo)); return r;
}
__device__ __forceinline__ float bf_lo(uint32_t v) { return __uint_as_float(v << 16); }
__device__ __forceinline__ float bf_hi(uint32_t v) { return __uint_as_float(v & 0xffff0000u); }
__device__ __forceinline__ float ex2(float x) { float r; asm("ex2.approx.ftz.f32 %0, %1;" : "=f"(r) : "f"(x)); return r; }
__device__ __forceinline__ float rcp(float x) { float r; asm("rcp.approx.ftz.f32 %0, %1;" : "=f"(r) : "f"(x)); return r; }
__device__ __forceinline__ float sigmoidf(float x) { return 1.0f / (1.0f + __expf(-x)); }
__device__ __forceinline__ void sts128(uint32_t a, uint32_t x, uint32_t y, uint32_t z, uint32_t w) {
  asm volatile("st.shared.v4.u32 [%0], {%1,%2,%3,%4};" :: "r"(a), "r"(x), "r"(y), "r"(z), "r"(w) : "memory");
}
__device__ __forceinline__ void lds128(uint32_t a, uint32_t (&r)[4]) {
  asm volatile("ld.shared.v4.u32 {%0,%1,%2,%3}, [%4];" : "=r"(r[0]), "=r"(r[1]), "=r"(r[2]), "=r"(r[3]) : "r"(a) : "memory");
}
__device__ __forceinline__ void sts32(uint32_t a, uint32_t v) { asm volatile("st.shared.u32 [%0], %1;" :: "r"(a), "r"(v) : "memory"); }
__device__ __forceinline__ uint32_t lds32(uint32_t a) { uint32_t v; asm volatile("ld.shared.u32 %0, [%1];" : "=r"(v) : "r"(a) : "memory"); return v; }
__device__ __forceinline__ float ldsf(uint32_t a) { return __uint_as_float(lds32(a)); }
__device__ __forceinline__ void stsf(uint32_t a, float v) { sts32(a, __float_as_uint(v)); }
__device__ __forceinline__ void stmatrix4(uint32_t a, uint32_t r0, uint32_t r1, uint32_t r2, uint32_t r3) {
  asm volatile("stmatrix.sync.aligned.m8n8.x4.shared.b16 [%0], {%1,%2,%3,%4};" :: "r"(a), "r"(r0), "r"(r1), "r"(r2), "r"(r3) : "memory");
}
__device__ __forceinline__ void ldmatrix4(uint32_t a, uint32_t (&r)[4]) {
  asm volatile("ldmatrix.sync.aligned.m8n8.x4.shared.b16 {%0,%1,%2,%3}, [%4];" : "=r"(r[0]), "=r"(r[1]), "=r"(r[2]), "=r"(r[3]) : "r"(a) : "memory");
}
__device__ __forceinline__ uint4 ldg_nc(const void* p) {
  uint4 v; asm volatile("ld.global.nc.L1::no_allocate.v4.u32 {%0,%1,%2,%3}, [%4];" : "=r"(v.x), "=r"(v.y), "=r"(v.z), "=r"(v.w) : "l"(p)); return v;
}
__device__ __forceinline__ float4 ldg_strong4(const float* p) {
  float4 v; asm volatile("ld.relaxed.gpu.global.v4.f32 {%0,%1,%2,%3}, [%4];" : "=f"(v.x), "=f"(v.y), "=f"(v.z), "=f"(v.w) : "l"(p) : "memory"); return v;
}
__device__ __forceinline__ uint32_t ldg_strong(const void* p) { uint32_t v; asm volatile("ld.relaxed.gpu.global.u32 %0, [%1];" : "=r"(v) : "l"(p) : "memory"); return v; }
__device__ __forceinline__ void red4(float* p, float a, float b, float c, float d) {
  asm volatile("red.relaxed.gpu.global.add.v4.f32 [%0], {%1,%2,%3,%4};" :: "l"(p), "f"(a), "f"(b), "f"(c), "f"(d) : "memory");
}
__device__ __forceinline__ void red1(float* p, float a) { asm volatile("red.relaxed.gpu.global.add.f32 [%0], %1;" :: "l"(p), "f"(a) : "memory"); }
__device__ __forceinline__ void signal_add(uint32_t* p, uint32_t v) { asm volatile("red.release.gpu.global.add.u32 [%0], %1;" :: "l"(p), "r"(v) : "memory"); }
__device__ __forceinline__ void wait_count(const uint32_t* p, uint32_t target) {
#pragma unroll 1
  for (int it = 0; it < SPIN_LIMIT; it++) if ((int32_t)(ldg_strong(p) - target) >= 0) break;
  asm volatile("fence.acq_rel.gpu;" ::: "memory");
}
__device__ __forceinline__ float qmax(float v) { v = fmaxf(v, __shfl_xor_sync(0xffffffffu, v, 1)); return fmaxf(v, __shfl_xor_sync(0xffffffffu, v, 2)); }
__device__ __forceinline__ float qmin(float v) { v = fminf(v, __shfl_xor_sync(0xffffffffu, v, 1)); return fminf(v, __shfl_xor_sync(0xffffffffu, v, 2)); }
__device__ __forceinline__ float qsum(float v) { v += __shfl_xor_sync(0xffffffffu, v, 1); return v + __shfl_xor_sync(0xffffffffu, v, 2); }

__device__ __forceinline__ void dual_exp(const float (&p)[16], float (&ep)[16], float (&em)[16]) {
  constexpr float L = 1.4426950408889634f;
#pragma unroll
  for (int r = 0; r < 2; r++) {
    const int o = 2 * r;
    float mx = fmaxf(fmaxf(fmaxf(p[o], p[o + 1]), fmaxf(p[o + 4], p[o + 5])), fmaxf(fmaxf(p[o + 8], p[o + 9]), fmaxf(p[o + 12], p[o + 13])));
    float mn = fminf(fminf(fminf(p[o], p[o + 1]), fminf(p[o + 4], p[o + 5])), fminf(fminf(p[o + 8], p[o + 9]), fminf(p[o + 12], p[o + 13])));
    const float bp = -L * qmax(mx), bm = L * qmin(mn);
#pragma unroll
    for (int c = 0; c < 4; c++)
#pragma unroll
      for (int e = 0; e < 2; e++) {
        ep[4 * c + o + e] = ex2(fmaf(p[4 * c + o + e], L, bp));
        em[4 * c + o + e] = ex2(fmaf(p[4 * c + o + e], -L, bm));
      }
  }
}

__device__ __forceinline__ void mainloop128(float (&acc)[2][64], uint32_t sb, int n0, int lane, int& last_slot) {
  int slot = n0 % NST, ph = (n0 / NST) & 1, prev = 0;
  zero(acc[0]); zero(acc[1]);
  const uint64_t da0 = make_desc(sb, 16, 1024, 1), db0 = make_desc(sb + 16384, 8192, 1024, 1);
#pragma unroll 1
  for (int k = 0; k < 16; k++) {
    mbar_wait(sb + SM_BAR + (B_FX + slot) * 8, ph);
    const uint64_t da = da0 + slot * (STAGE >> 4), db = db0 + slot * (STAGE >> 4);
    wg_fence();
#pragma unroll
    for (int kk = 0; kk < 4; kk++) {
      wgmma_m64n128k16_ss<0, 1>(acc[0], da + kk * 2, db + kk * 128, k | kk);
      wgmma_m64n128k16_ss<0, 1>(acc[1], da + 512 + kk * 2, db + kk * 128, k | kk);
    }
    wg_commit();
    wg_wait<1>();
    if (k > 0 && lane == 0) mbar_arrive_n(sb + SM_BAR + (B_EM + prev) * 8, 2);
    prev = slot;
    if (++slot == NST) { slot = 0; ph ^= 1; }
  }
  last_slot = prev;
}

__global__ void __launch_bounds__(512, 1)
fused_kernel(const __grid_constant__ CUtensorMap mx, const __grid_constant__ CUtensorMap mw, const __grid_constant__ CUtensorMap mwo,
             const __grid_constant__ CUtensorMap mo, const __grid_constant__ CUtensorMap mout, const __grid_constant__ CUtensorMap mphi,
             const Params P) {
  extern __shared__ __align__(1024) uint8_t smem_raw[];
  const uint32_t sb = smem_u32(smem_raw);
  const int tid = threadIdx.x, lane = tid & 31;
  const int warp = __shfl_sync(0xffffffffu, tid >> 5, 0), wg = warp >> 2;
  int cta;
  {
    uint32_t smid, nsm;
    asm volatile("mov.u32 %0, %%smid;" : "=r"(smid));
    asm volatile("mov.u32 %0, %%nsmid;" : "=r"(nsm));
    if (nsm != 132u) cta = blockIdx.x;
    else if (smid < 64) cta = ((smid >> 1) & 7) * 16 + (smid >> 4) * 2 + (smid & 1);
    else if (smid < 120) { const int t = (smid - 64) >> 1; cta = (1 + t % 7) * 16 + 8 + (t / 7) * 2 + (smid & 1); }
    else if (smid < 124) cta = 128 + smid - 120;
    else cta = 8 + smid - 124;
  }
  if (cta >= 128) {
    if (tid == 0) {
      const uint32_t old = atomicAdd(&g_cnt[C_ROUTER], 32u);
      wait_count(&g_cnt[C_ROUTER], (old & ~255u) + 256u);
    }
    return;
  }
  const int bi = (cta >> 5) * 4 + ((cta >> 2) & 3);
  const int bj = ((cta >> 4) & 1) * 4 + (cta & 3);
  const uint32_t bars = sb + SM_BAR;

  if (wg == 2) {
    asm volatile("setmaxnreg.dec.sync.aligned.u32 32;");
    if (warp == 8) {
      const bool lead = elect_one();
      if (lead) {
        TSG(0); TS(1);
        prefetch_map(&mx); prefetch_map(&mw);
        for (int s = 0; s < NST; s++) { mbar_init(bars + (B_FX + s) * 8, 1); mbar_init(bars + (B_FY + s) * 8, 1); mbar_init(bars + (B_EM + s) * 8, 8); }
        mbar_init(bars + B_WPHI * 8, 1); mbar_init(bars + B_XT * 8, 1); mbar_init(bars + B_INFO * 8, 4); mbar_init(bars + B_EPOCH * 8, 1);
        mbar_init(bars + B_KV * 8, 4); mbar_init(bars + B_QS * 8, 4); mbar_init(bars + B_YS * 8, 4);
        for (int s = 0; s < 4; s++) mbar_init(bars + (B_PUB + s) * 8, 4);
        asm volatile("fence.mbarrier_init.release.cluster;" ::: "memory");
        fence_async_smem();
      }
      __syncwarp();
      bar_arrive(0, 512);
      if (lead) {
        int slot = 0, ph = 1;
#pragma unroll 1
        for (int n = 0; n < 48; n++) {
          const int t = n >> 4, k = n & 15;
          const int c0 = t == 2 ? bj * 128 : 1024 + bj * 128 + t * 64, c1 = t == 2 ? c0 + 64 : c0 + 1024;
          const uint32_t st = sb + slot * STAGE, fb = bars + (B_FX + slot) * 8;
          mbar_wait(bars + (B_EM + slot) * 8, ph);
          mbar_expect_tx(fb, STAGE);
          tma_load(st, &mx, fb, k * 64, bi * 128);
          tma_load(st + 16384, &mw, fb, c0, k * 64);
          tma_load(st + 24576, &mw, fb, c1, k * 64);
          if (n == NST - 1) {
            mbar_expect_tx(bars + B_WPHI * 8, 8192);
            tma_load(sb + SM_WPHI, &mphi, bars + B_WPHI * 8, 0, bj * 128);
            prefetch_map(&mwo); prefetch_map(&mo); prefetch_map(&mout);
          }
          if (n == NST) { tma_prefetch(&mw, c0, bi * 64); tma_prefetch(&mw, c1, bi * 64); }
          if (k == 8) {
            if (t == 0) { tma_prefetch(&mw, c0 + 64, bi * 64); tma_prefetch(&mw, c1 + 64, bi * 64); }
            else if (t == 1) { tma_prefetch(&mw, bj * 128, bi * 64); tma_prefetch(&mw, bj * 128 + 64, bi * 64); }
            else { tma_prefetch(&mwo, bj * 128, bi * 64); tma_prefetch(&mwo, bj * 128 + 64, bi * 64); }
          }
          if (++slot == NST) { slot = 0; ph ^= 1; }
        }
        mbar_wait(bars + B_EPOCH * 8, 0);
        const uint32_t target = lds32(sb + SM_MISC);
#pragma unroll 1
        for (int s = 0; s < 16; s++) {
          const int p = s < 2 ? s : (s >= 9), q = s < 9 ? s - 2 : s - 9;
          const int k0 = (s < 2 ? bj : q + (q >= bj)) * 128 + p * 64;
          const uint32_t st = sb + slot * STAGE, fb = bars + (B_FX + slot) * 8;
          mbar_wait(bars + (B_EM + slot) * 8, ph);
          mbar_expect_tx(fb, s < 2 ? 16384 : 24576);
          tma_load(st + 16384, &mwo, fb, bj * 128, k0);
          tma_load(st + 24576, &mwo, fb, bj * 128 + 64, k0);
          if (s >= 2) {
            if (q == 0) { wait_count(&g_cnt[C_O + bi * 32 + p], target); asm volatile("fence.proxy.async.global;" ::: "memory"); TS(2 + p); }
            tma_load(st, &mo, fb, k0, bi * 128);
          }
          if (++slot == NST) { slot = 0; ph ^= 1; }
        }
      }
    } else {
      bar_sync(0, 512);
      if (elect_one()) {
        if (warp == 9) {
          mbar_wait(bars + B_EPOCH * 8, 0);
          const uint32_t target = lds32(sb + SM_MISC);
          int slot = 0, ph = 1;
#pragma unroll 1
          for (int s = 2; s < 16; s++) {
            const int p = s >= 9, q = s < 9 ? s - 2 : s - 9;
            const int k0 = (q + (q >= bj)) * 128 + p * 64;
            if (q == 0) {
              if (p == 0) mbar_wait(bars + (B_PUB + 2) * 8, 0);
              wait_count(&g_cnt[C_O + bi * 32 + 2 + p], target); asm volatile("fence.proxy.async.global;" ::: "memory"); TS(4 + p);
            }
            const uint32_t fb = bars + (B_FY + slot) * 8;
            mbar_wait(bars + (B_EM + slot) * 8, ph);
            mbar_expect_tx(fb, 8192);
            tma_load(sb + slot * STAGE + 8192, &mo, fb, k0, bi * 128 + 64);
            if (++slot == NST) { slot = 0; ph ^= 1; }
          }
        } else {
          const int mt = warp - 10;
#pragma unroll 1
          for (int p = 0; p < 2; p++) {
            mbar_wait(bars + (B_PUB + mt * 2 + p) * 8, 0);
            signal_add(&g_cnt[C_O + bi * 32 + mt * 2 + p], 32u);
          }
        }
      }
    }
  } else if (wg == 3) {
    asm volatile("setmaxnreg.dec.sync.aligned.u32 80;");
    bar_sync(0, 512);
    const int t3 = tid - 384, w3 = warp - 12;
    const bool has_blk = cta < 112;
    const __nv_bfloat16* pg = P.w_gate + (size_t)(w3 * 8 + (lane >> 2)) * kF + cta * 32 + (lane & 3) * 8;
    const __nv_bfloat16* pu = P.w_up + (size_t)(w3 * 8 + (lane >> 2)) * kF + cta * 32 + (lane & 3) * 8;
    mbar_wait(bars + B_EPOCH * 8, 0);
    const uint32_t target = lds32(sb + SM_MISC);
    if (lane == 0) wait_count(&g_cnt[C_ROUTER], target);
    __syncwarp();
    if (t3 == 0) TS(8);
    uint32_t key;
    {
      const uint32_t k0 = ldg_strong(&g_key[lane]), k1 = ldg_strong(&g_key[lane + 32]), k2 = ldg_strong(&g_key[lane + 64]), k3 = ldg_strong(&g_key[lane + 96]);
      const uint32_t gv = ldg_strong(&g_gate[bi * 128 + t3]);
      key = __reduce_max_sync(0xffffffffu, max(max(k0, k1), max(k2, k3)));
      sts32(sb + SM_G + t3 * 4, gv);
    }
    const int idx = 0xFFFF - (key & 0xFFFF);
    if (t3 == 0) sts32(sb + SM_MISC + 4, idx);
    __syncwarp();
    if (lane == 0) mbar_arrive(bars + B_INFO * 8);
    if (has_blk) {
      {
        const uint4 v = ldg_nc(P.x + (size_t)idx * kD + t3 * 8);
        sts128(sb + SM_XSEL + t3 * 32, v.x << 16, v.x & 0xffff0000u, v.y << 16, v.y & 0xffff0000u);
        sts128(sb + SM_XSEL + t3 * 32 + 16, v.z << 16, v.z & 0xffff0000u, v.w << 16, v.w & 0xffff0000u);
      }
      bar_sync(5, 128);
      float ag[8], au[8];
#pragma unroll
      for (int e = 0; e < 8; e++) { ag[e] = 0.f; au[e] = 0.f; }
#pragma unroll 1
      for (int b = 0; b < 8; b++) {
        uint4 vg[4], vu[4];
#pragma unroll
        for (int u = 0; u < 4; u++) { vg[u] = ldg_nc(pg + (size_t)(b * 4 + u) * 32 * kF); vu[u] = ldg_nc(pu + (size_t)(b * 4 + u) * 32 * kF); }
#pragma unroll
        for (int u = 0; u < 4; u++) {
          const float xv = ldsf(sb + SM_XSEL + ((b * 4 + u) * 32 + w3 * 8 + (lane >> 2)) * 4);
          ag[0] = fmaf(xv, bf_lo(vg[u].x), ag[0]); ag[1] = fmaf(xv, bf_hi(vg[u].x), ag[1]);
          ag[2] = fmaf(xv, bf_lo(vg[u].y), ag[2]); ag[3] = fmaf(xv, bf_hi(vg[u].y), ag[3]);
          ag[4] = fmaf(xv, bf_lo(vg[u].z), ag[4]); ag[5] = fmaf(xv, bf_hi(vg[u].z), ag[5]);
          ag[6] = fmaf(xv, bf_lo(vg[u].w), ag[6]); ag[7] = fmaf(xv, bf_hi(vg[u].w), ag[7]);
          au[0] = fmaf(xv, bf_lo(vu[u].x), au[0]); au[1] = fmaf(xv, bf_hi(vu[u].x), au[1]);
          au[2] = fmaf(xv, bf_lo(vu[u].y), au[2]); au[3] = fmaf(xv, bf_hi(vu[u].y), au[3]);
          au[4] = fmaf(xv, bf_lo(vu[u].z), au[4]); au[5] = fmaf(xv, bf_hi(vu[u].z), au[5]);
          au[6] = fmaf(xv, bf_lo(vu[u].w), au[6]); au[7] = fmaf(xv, bf_hi(vu[u].w), au[7]);
        }
      }
      if (t3 == 0) TS(9);
#pragma unroll
      for (int e = 0; e < 8; e++) {
#pragma unroll
        for (int o = 4; o < 32; o <<= 1) { ag[e] += __shfl_xor_sync(0xffffffffu, ag[e], o); au[e] += __shfl_xor_sync(0xffffffffu, au[e], o); }
      }
      if (lane < 4) {
        const uint32_t a = sb + SM_RED + w3 * 256 + lane * 32;
        sts128(a, __float_as_uint(ag[0]), __float_as_uint(ag[1]), __float_as_uint(ag[2]), __float_as_uint(ag[3]));
        sts128(a + 16, __float_as_uint(ag[4]), __float_as_uint(ag[5]), __float_as_uint(ag[6]), __float_as_uint(ag[7]));
        sts128(a + 128, __float_as_uint(au[0]), __float_as_uint(au[1]), __float_as_uint(au[2]), __float_as_uint(au[3]));
        sts128(a + 144, __float_as_uint(au[4]), __float_as_uint(au[5]), __float_as_uint(au[6]), __float_as_uint(au[7]));
      }
      bar_sync(5, 128);
      float hval;
      {
        const uint32_t a = sb + SM_RED + lane * 4;
        const float gs = (ldsf(a) + ldsf(a + 256)) + (ldsf(a + 512) + ldsf(a + 768));
        const float us = (ldsf(a + 128) + ldsf(a + 384)) + (ldsf(a + 640) + ldsf(a + 896));
        hval = gs * sigmoidf(gs) * us;
      }
      float ay[8];
#pragma unroll
      for (int e = 0; e < 8; e++) ay[e] = 0.f;
      const __nv_bfloat16* pd = P.w_down + (size_t)cta * 32 * kD + t3 * 8;
#pragma unroll 1
      for (int b = 0; b < 4; b++) {
        uint4 v[8];
#pragma unroll
        for (int u = 0; u < 8; u++) v[u] = ldg_nc(pd + (size_t)(b * 8 + u) * kD);
#pragma unroll
        for (int u = 0; u < 8; u++) {
          const float hv = __shfl_sync(0xffffffffu, hval, b * 8 + u);
          ay[0] = fmaf(hv, bf_lo(v[u].x), ay[0]); ay[1] = fmaf(hv, bf_hi(v[u].x), ay[1]);
          ay[2] = fmaf(hv, bf_lo(v[u].y), ay[2]); ay[3] = fmaf(hv, bf_hi(v[u].y), ay[3]);
          ay[4] = fmaf(hv, bf_lo(v[u].z), ay[4]); ay[5] = fmaf(hv, bf_hi(v[u].z), ay[5]);
          ay[6] = fmaf(hv, bf_lo(v[u].w), ay[6]); ay[7] = fmaf(hv, bf_hi(v[u].w), ay[7]);
        }
      }
      red4(&g_yacc[t3 * 8], ay[0], ay[1], ay[2], ay[3]);
      red4(&g_yacc[t3 * 8 + 4], ay[4], ay[5], ay[6], ay[7]);
      bar_sync(5, 128);
    }
    if (t3 == 0) { signal_add(&g_cnt[C_Y], 2u); TS(10); }
    if ((idx >> 7) == bi) {
      if (lane == 0) wait_count(&g_cnt[C_Y], target);
      __syncwarp();
      const uint32_t ob = key >> 16;
      const float rsel = __uint_as_float(((ob & 0x8000u) ? (ob ^ 0x8000u) : (~ob & 0xFFFFu)) << 16);
      stsf(sb + SM_YS + t3 * 4, sigmoidf(rsel) * __uint_as_float(ldg_strong(&g_yacc[bj * 128 + t3])));
      __syncwarp();
      if (lane == 0) mbar_arrive(bars + B_YS * 8);
      if (t3 == 0) TS(11);
    }
  } else {
    asm volatile("setmaxnreg.inc.sync.aligned.u32 200;");
    const int tw = tid & 127, w = warp & 3, g = lane >> 2, t = lane & 3;
    if (wg == 0) {
      sts128(sb + SM_Z + (tw & 63) * 16, 0x3f803f80u, 0x3f803f80u, 0x3f803f80u, 0x3f803f80u);
      bar_sync(0, 512);
    } else {
      *reinterpret_cast<float4*>(&g_kvacc[cta * 512 + tw * 4]) = make_float4(0.f, 0.f, 0.f, 0.f);
      if (tw < 16) g_zacc[cta * 16 + tw] = 0.f;
      if (tw < 8) g_yacc[cta * 8 + tw] = 0.f;
      uint4 wr[4], wgt[4], xv[4][4];
#pragma unroll
      for (int c = 0; c < 4; c++) { wr[c] = ldg_nc(P.w_r + c * 256 + lane * 8); wgt[c] = ldg_nc(P.gate_w + c * 256 + lane * 8); }
      bar_sync(0, 512);
      mbar_wait(bars + B_FX * 8, 0);
      const int row0 = bi * 128 + bj * 16 + w * 4;
#pragma unroll
      for (int r = 0; r < 4; r++)
#pragma unroll
        for (int c = 0; c < 4; c++) xv[r][c] = ldg_nc(P.x + (size_t)(row0 + r) * kD + c * 256 + lane * 8);
      uint32_t best = 0;
#pragma unroll
      for (int r = 0; r < 4; r++) {
        float sr = 0.f, sg = 0.f;
#pragma unroll
        for (int c = 0; c < 4; c++) {
          const uint32_t xs[4] = {xv[r][c].x, xv[r][c].y, xv[r][c].z, xv[r][c].w};
          const uint32_t rs[4] = {wr[c].x, wr[c].y, wr[c].z, wr[c].w}, gs[4] = {wgt[c].x, wgt[c].y, wgt[c].z, wgt[c].w};
#pragma unroll
          for (int e = 0; e < 4; e++) {
            sr = fmaf(bf_lo(xs[e]), bf_lo(rs[e]), sr); sr = fmaf(bf_hi(xs[e]), bf_hi(rs[e]), sr);
            sg = fmaf(bf_lo(xs[e]), bf_lo(gs[e]), sg); sg = fmaf(bf_hi(xs[e]), bf_hi(gs[e]), sg);
          }
        }
#pragma unroll
        for (int o = 1; o < 32; o <<= 1) { sr += __shfl_xor_sync(0xffffffffu, sr, o); sg += __shfl_xor_sync(0xffffffffu, sg, o); }
        if (lane == 0) g_gate[row0 + r] = sigmoidf(sg);
        const uint32_t rb = pack2(sr + 0.f, 0.f) & 0xFFFFu;
        const uint32_t ob = (rb & 0x8000u) ? (~rb & 0xFFFFu) : (rb | 0x8000u);
        best = max(best, (ob << 16) | (0xFFFFu - (row0 + r)));
      }
      if (lane == 0) sts32(sb + SM_MISC + 16 + w * 4, best);
      bar_sync(4, 128);
      if (tw == 0) {
        g_key[cta] = max(max(best, lds32(sb + SM_MISC + 20)), max(lds32(sb + SM_MISC + 24), lds32(sb + SM_MISC + 28)));
        uint32_t old;
        asm volatile("atom.add.release.gpu.global.u32 %0, [%1], 1;" : "=r"(old) : "l"(&g_cnt[C_ROUTER]) : "memory");
        sts32(sb + SM_MISC, (old & ~255u) + 256u);
        mbar_arrive(bars + B_EPOCH * 8);
        TS(12);
      }
      bar_sync(1, 256);
    }

    float acc[2][64];
    int last;
    if (tw == 0) TS(16 + wg * 16);
    mainloop128(acc, sb, wg * 16, lane, last);
    if (wg == 0) bar_arrive(1, 256); else bar_sync(2, 256);
    wg_wait<0>();
    pin(acc[0]); pin(acc[1]);
    if (lane == 0) mbar_arrive_n(bars + (B_EM + last) * 8, 2);
    if (tw == 0) TS(17 + wg * 16);
    {
      float p[4][16];
      {
        uint32_t kf[4][2][4];
#pragma unroll
        for (int m = 0; m < 2; m++)
#pragma unroll
          for (int hh = 0; hh < 2; hh++) {
#pragma unroll
            for (int s = 0; s < 2; s++)
#pragma unroll
              for (int r = 0; r < 4; r++) kf[m * 2 + hh][s][r] = pack2(acc[m][16 * hh + 8 * s + 2 * r], acc[m][16 * hh + 8 * s + 2 * r + 1]);
          }
#pragma unroll
        for (int m = 0; m < 2; m++)
#pragma unroll
          for (int hh = 0; hh < 2; hh++)
#pragma unroll
            for (int r = 0; r < 2; r++) {
              const int row = m * 64 + w * 16 + r * 8 + g;
              const float* a = &acc[m][32 + 16 * hh + 2 * r];
              sts128(sb + SM_V + hh * 8192 + row * 64 + ((t ^ ((row >> 1) & 3)) << 4), pack2(a[0], a[1]), pack2(a[4], a[5]), pack2(a[8], a[9]), pack2(a[12], a[13]));
            }
        mbar_wait(bars + B_WPHI * 8, 0);
        const uint64_t dw = make_desc(sb + SM_WPHI + wg * 4096, 16, 512, 2);
        wg_fence();
#pragma unroll
        for (int u = 0; u < 4; u++) {
          wgmma_m64n32k16_rs<1>(p[u], kf[u][0], dw + (u & 1) * 128, 0);
          wgmma_m64n32k16_rs<1>(p[u], kf[u][1], dw + (u & 1) * 128 + 64, 1);
        }
        wg_commit();
        wg_wait<0>();
#pragma unroll
        for (int u = 0; u < 4; u++) pin(p[u]);
      }
      if (tw == 0) TS(18 + wg * 16);
      const int srow = w * 16 + (lane & 15);
      uint32_t sphi = sb + SM_PHI + srow * 128;
#pragma unroll 1
      for (int m = 0; m < 2; m++) {
#pragma unroll
        for (int hh = 0; hh < 2; hh++) {
          float ep[16], em[16];
          dual_exp(p[hh], ep, em);
          float rp[2], rm[2];
#pragma unroll
          for (int r = 0; r < 2; r++) {
            const int o = 2 * r;
            rp[r] = rcp(qsum(((ep[o] + ep[o + 1]) + (ep[o + 4] + ep[o + 5])) + ((ep[o + 8] + ep[o + 9]) + (ep[o + 12] + ep[o + 13]))));
            rm[r] = rcp(qsum(((em[o] + em[o + 1]) + (em[o + 4] + em[o + 5])) + ((em[o + 8] + em[o + 9]) + (em[o + 12] + em[o + 13]))));
          }
#pragma unroll
          for (int s = 0; s < 2; s++) {
            const float* a = &ep[8 * s];
            const float* b = &em[8 * s];
            stmatrix4(sphi + hh * 16384 + (((2 * s + (lane >> 4)) ^ (lane & 7)) << 4),
                      pack2(a[0] * rp[0], a[1] * rp[0]), pack2(a[2] * rp[1], a[3] * rp[1]), pack2(a[4] * rp[0], a[5] * rp[0]), pack2(a[6] * rp[1], a[7] * rp[1]));
            stmatrix4(sphi + hh * 16384 + (((4 + 2 * s + (lane >> 4)) ^ (lane & 7)) << 4),
                      pack2(b[0] * rm[0], b[1] * rm[0]), pack2(b[2] * rm[1], b[3] * rm[1]), pack2(b[4] * rm[0], b[5] * rm[0]), pack2(b[6] * rm[1], b[7] * rm[1]));
          }
        }
#pragma unroll
        for (int e = 0; e < 16; e++) { p[0][e] = p[2][e]; p[1][e] = p[3][e]; }
        sphi += 8192;
      }
      fence_async_smem();
      bar_sync(3 + wg, 128);
      if (tw == 0) TS(19 + wg * 16);
      float kv[2][20];
      wg_fence();
#pragma unroll
      for (int hh = 0; hh < 2; hh++)
#pragma unroll
        for (int ks = 0; ks < 8; ks++)
          wgmma_m64n40k16_ss<1, 1>(kv[hh], make_desc(sb + SM_PHI + hh * 16384 + ks * 2048, 16, 1024, 1),
                                   make_desc(sb + SM_V + hh * 8192 + ks * 1024, SM_Z - (SM_V + hh * 8192 + ks * 1024), 512, 2), ks);
      wg_commit();
      mbar_wait(bars + B_INFO * 8, 0);
      wg_wait<0>();
      pin(kv[0]); pin(kv[1]);
      if (tw == 0) TS(20 + wg * 16);
#pragma unroll
      for (int hh = 0; hh < 2; hh++) {
        const int h = bj * 4 + wg * 2 + hh;
#pragma unroll
        for (int c = 0; c < 4; c++) red4(&g_kvacc[((h * 4 + c) * 128 + tw) * 4], kv[hh][4 * c], kv[hh][4 * c + 1], kv[hh][4 * c + 2], kv[hh][4 * c + 3]);
        if (t < 2) red1(&g_zacc[h * 64 + w * 16 + t * 8 + g], t == 0 ? kv[hh][16] : kv[hh][18]);
      }
      bar_sync(3 + wg, 128);
      if (tw == 0) { signal_add(&g_cnt[C_KV + bj * 32], 8u); TS(21 + wg * 16); }
    }

    const int mt = 1 - wg;
    const uint32_t own0 = sb + 3 * STAGE + mt * 8192;
    uint32_t qf[4][2][4];
    if (wg == 0) {
      bar_sync(2, 256);
      if (tw == 0) TS(22);
      mainloop128(acc, sb, 32, lane, last);
      wg_wait<0>();
      pin(acc[0]); pin(acc[1]);
      if (lane == 0) mbar_arrive_n(bars + (B_EM + last) * 8, 2);
      if (tw == 0) TS(23);
#pragma unroll
      for (int u = 0; u < 8; u++) {
        const float* a = &acc[0][8 * u];
        sts128(sb + (3 + (u >> 2)) * STAGE + (u & 3) * 2048 + tw * 16, pack2(a[0], a[1]), pack2(a[2], a[3]), pack2(a[4], a[5]), pack2(a[6], a[7]));
      }
      __syncwarp();
      if (lane == 0) mbar_arrive(bars + B_QS * 8);
#pragma unroll
      for (int u = 0; u < 8; u++)
#pragma unroll
        for (int r = 0; r < 4; r++) qf[u >> 1][u & 1][r] = pack2(acc[1][8 * u + 2 * r], acc[1][8 * u + 2 * r + 1]);
    } else {
      if (w == 1 && elect_one()) {
        mbar_expect_tx(bars + B_XT * 8, 32768);
        tma_load(sb + SM_PHI, &mx, bars + B_XT * 8, bj * 128, bi * 128);
        tma_load(sb + SM_PHI + 16384, &mx, bars + B_XT * 8, bj * 128 + 64, bi * 128);
      }
      if (tw == 0) wait_count(&g_cnt[C_KV + bj * 32], lds32(sb + SM_MISC));
      bar_sync(4, 128);
      if (tw == 0) TS(38);
      float4 v[4][4];
#pragma unroll
      for (int h = 0; h < 4; h++)
#pragma unroll
        for (int c = 0; c < 4; c++) v[h][c] = ldg_strong4(&g_kvacc[(((bj * 4 + h) * 4 + c) * 128 + tw) * 4]);
      const uint32_t z0 = ldg_strong(&g_zacc[bj * 256 + tw]), z1 = ldg_strong(&g_zacc[bj * 256 + 128 + tw]);
      const int srow = w * 16 + (lane & 15);
#pragma unroll
      for (int h = 0; h < 4; h++)
#pragma unroll
        for (int s = 0; s < 2; s++)
          stmatrix4(sb + SM_V + h * 4096 + srow * 64 + (((2 * s + (lane >> 4)) ^ ((srow >> 1) & 3)) << 4),
                    pack2(v[h][2 * s].x, v[h][2 * s].y), pack2(v[h][2 * s].z, v[h][2 * s].w), pack2(v[h][2 * s + 1].x, v[h][2 * s + 1].y), pack2(v[h][2 * s + 1].z, v[h][2 * s + 1].w));
      {
        const int f = tw & 63, h0 = tw >> 6;
        const uint32_t a = pack2(__uint_as_float(z0), 1.0f), b = pack2(__uint_as_float(z1), 1.0f);
        sts128(sb + SM_Z + f * 64 + ((h0 ^ ((f >> 1) & 3)) << 4), a, a, a, a);
        sts128(sb + SM_Z + f * 64 + (((h0 + 2) ^ ((f >> 1) & 3)) << 4), b, b, b, b);
      }
      fence_async_smem();
      __syncwarp();
      if (lane == 0) mbar_arrive(bars + B_KV * 8);
      if (tw == 0) TS(39);
      mbar_wait(bars + B_QS * 8, 0);
#pragma unroll
      for (int u = 0; u < 8; u++) lds128(sb + (3 + (u >> 2)) * STAGE + (u & 3) * 2048 + tw * 16, qf[u >> 1][u & 1]);
      bar_sync(4, 128);
    }

    const int rowl = mt * 64 + w * 16 + g;
    const float gA = ldsf(sb + SM_G + rowl * 4), gB = ldsf(sb + SM_G + rowl * 4 + 32);
    {
      float p[4][16];
      const uint64_t dw = make_desc(sb + SM_WPHI, 16, 512, 2);
      wg_fence();
#pragma unroll
      for (int h = 0; h < 4; h++) {
        wgmma_m64n32k16_rs<1>(p[h], qf[h][0], dw + h * 128, 0);
        wgmma_m64n32k16_rs<1>(p[h], qf[h][1], dw + h * 128 + 64, 1);
      }
      wg_commit();
      mbar_wait(bars + B_KV * 8, 0);
      wg_wait<0>();
#pragma unroll
      for (int h = 0; h < 4; h++) pin(p[h]);
      if (tw == 0) TS(24 + wg * 16);
      __nv_bfloat16* og = g_o + (size_t)(bi * 128 + rowl) * kD + bj * 128 + t * 8;
#pragma unroll 1
      for (int pr = 0; pr < 2; pr++) {
        float np[2][20], nm[2][20];
        uint32_t ef[2][4][4];
#pragma unroll
        for (int hh = 0; hh < 2; hh++) {
          float ep[16], em[16];
          dual_exp(p[hh], ep, em);
#pragma unroll
          for (int s = 0; s < 2; s++)
#pragma unroll
            for (int r = 0; r < 4; r++) {
              ef[hh][s][r] = pack2(ep[8 * s + 2 * r], ep[8 * s + 2 * r + 1]);
              ef[hh][2 + s][r] = pack2(em[8 * s + 2 * r], em[8 * s + 2 * r + 1]);
            }
          const int h = pr * 2 + hh;
          const uint64_t dk = make_desc(sb + SM_V + h * 4096, SM_Z + h * 16 - (SM_V + h * 4096), 512, 2);
          wg_fence();
          wgmma_m64n40k16_rs<1>(np[hh], ef[hh][0], dk, 0);
          wgmma_m64n40k16_rs<1>(np[hh], ef[hh][1], dk + 64, 1);
          wgmma_m64n40k16_rs<1>(nm[hh], ef[hh][2], dk + 128, 0);
          wgmma_m64n40k16_rs<1>(nm[hh], ef[hh][3], dk + 192, 1);
          wg_commit();
        }
#pragma unroll
        for (int hh = 0; hh < 2; hh++) {
          if (hh == 0) wg_wait<1>(); else wg_wait<0>();
          pin(np[hh]); pin(nm[hh]);
#pragma unroll
          for (int r = 0; r < 2; r++) {
            const float dp = np[hh][16 + 2 * r], sp = np[hh][17 + 2 * r], dm = nm[hh][16 + 2 * r], sm = nm[hh][17 + 2 * r];
            const float inv = (r == 0 ? gA : gB) * rcp(fmaf(dp, sm, fmaf(dm, sp, 1e-6f * sp * sm)));
            const float cp = sm * inv, cm = sp * inv;
            uint32_t o[4];
#pragma unroll
            for (int c = 0; c < 4; c++)
              o[c] = pack2(fmaf(np[hh][4 * c + 2 * r], cp, nm[hh][4 * c + 2 * r] * cm), fmaf(np[hh][4 * c + 2 * r + 1], cp, nm[hh][4 * c + 2 * r + 1] * cm));
            *reinterpret_cast<uint4*>(og + (size_t)r * 8 * kD + pr * 64 + hh * 32) = make_uint4(o[0], o[1], o[2], o[3]);
            sts128(own0 + pr * STAGE + (w * 16 + r * 8 + g) * 128 + (((hh * 4 + t) ^ g) << 4), o[0], o[1], o[2], o[3]);
          }
        }
        __syncwarp();
        if (lane == 0) mbar_arrive(bars + (B_PUB + mt * 2 + pr) * 8);
        if (tw == 0) TS(25 + pr + wg * 16);
#pragma unroll
        for (int e = 0; e < 16; e++) { p[0][e] = p[2][e]; p[1][e] = p[3][e]; }
      }
    }
    fence_async_smem();
    bar_sync(3 + wg, 128);

    float (&oacc)[64] = acc[0];
    float (&base)[64] = acc[1];
    const uint32_t sx = sb + SM_PHI + (mt * 64 + w * 16 + (lane & 15)) * 128;
    {
      int slot = 3, ph = 1, prev = 0, phy = 1;
      zero(oacc); zero(base);
      const uint64_t da0 = make_desc(sb + mt * 8192, 16, 1024, 1), db0 = make_desc(sb + 16384, 8192, 1024, 1);
#pragma unroll 1
      for (int s = 0; s < 16; s++) {
        mbar_wait(bars + (B_FX + slot) * 8, ph);
        if (mt == 1 && s >= 2) mbar_wait(bars + (B_FY + slot) * 8, phy);
        const uint64_t da = da0 + slot * (STAGE >> 4), db = db0 + slot * (STAGE >> 4);
        wg_fence();
#pragma unroll
        for (int kk = 0; kk < 4; kk++) wgmma_m64n128k16_ss<0, 1>(oacc, da + kk * 2, db + kk * 128, s | kk);
        wg_commit();
        if (s == 1) {
          mbar_wait(bars + B_XT * 8, 0);
          const float hA = 1.0f - gA, hB = 1.0f - gB;
#pragma unroll
          for (int u = 0; u < 8; u++) {
            uint32_t xr[4];
            ldmatrix4(sx + (u >> 2) * 16384 + (((2 * (u & 3) + (lane >> 4)) ^ (lane & 7)) << 4), xr);
            base[8 * u + 0] = hA * bf_lo(xr[0]); base[8 * u + 1] = hA * bf_hi(xr[0]);
            base[8 * u + 2] = hB * bf_lo(xr[1]); base[8 * u + 3] = hB * bf_hi(xr[1]);
            base[8 * u + 4] = hA * bf_lo(xr[2]); base[8 * u + 5] = hA * bf_hi(xr[2]);
            base[8 * u + 6] = hB * bf_lo(xr[3]); base[8 * u + 7] = hB * bf_hi(xr[3]);
          }
        }
        wg_wait<1>();
        if (s > 0 && lane == 0) mbar_arrive(bars + (B_EM + prev) * 8);
        prev = slot;
        if (++slot == NST) { slot = 0; ph ^= 1; phy ^= 1; }
      }
    }
    {
      const int il = (int)lds32(sb + SM_MISC + 4) - bi * 128 - mt * 64 - w * 16;
      if (il >= 0 && il < 16) {
        mbar_wait(bars + B_YS * 8, 0);
        const float fA = il == g ? 1.0f - gA : 0.f, fB = il == g + 8 ? 1.0f - gB : 0.f;
        if (il == g || il == g + 8) {
#pragma unroll
          for (int c = 0; c < 16; c++) {
            const float y0 = ldsf(sb + SM_YS + (c * 8 + t * 2) * 4), y1 = ldsf(sb + SM_YS + (c * 8 + t * 2 + 1) * 4);
            if (il == g) { base[4 * c] = fmaf(fA, y0, base[4 * c]); base[4 * c + 1] = fmaf(fA, y1, base[4 * c + 1]); }
            else { base[4 * c + 2] = fmaf(fB, y0, base[4 * c + 2]); base[4 * c + 3] = fmaf(fB, y1, base[4 * c + 3]); }
          }
        }
        __syncwarp();
      }
    }
    wg_wait<0>();
    pin(oacc);
    if (tw == 0) TS(29 + wg * 16);
#pragma unroll
    for (int u = 0; u < 8; u++) {
      const float* a = &oacc[8 * u];
      const float* b = &base[8 * u];
      stmatrix4(sx + (u >> 2) * 16384 + (((2 * (u & 3) + (lane >> 4)) ^ (lane & 7)) << 4),
                pack2(a[0] + b[0], a[1] + b[1]), pack2(a[2] + b[2], a[3] + b[3]), pack2(a[4] + b[4], a[5] + b[5]), pack2(a[6] + b[6], a[7] + b[7]));
    }
    fence_async_smem();
    __syncwarp();
    if (elect_one()) {
      const int r0 = mt * 64 + w * 16;
      tma_store(&mout, sb + SM_PHI + r0 * 128, bj * 128, bi * 128 + r0);
      tma_store(&mout, sb + SM_PHI + 16384 + r0 * 128, bj * 128 + 64, bi * 128 + r0);
      asm volatile("cp.async.bulk.commit_group;" ::: "memory");
      asm volatile("cp.async.bulk.wait_group.read 0;" ::: "memory");
    }
  }
}

typedef CUresult (*EncodeFn)(CUtensorMap*, CUtensorMapDataType, cuuint32_t, void*, const cuuint64_t*, const cuuint64_t*, const cuuint32_t*,
                             const cuuint32_t*, CUtensorMapInterleave, CUtensorMapSwizzle, CUtensorMapL2promotion, CUtensorMapFloatOOBfill);

void make_map(EncodeFn enc, CUtensorMap* m, const void* ptr, uint64_t cols, uint64_t rows, uint32_t bc, uint32_t br, CUtensorMapSwizzle swz) {
  const cuuint64_t dims[2] = {cols, rows}, strides[1] = {cols * 2};
  const cuuint32_t box[2] = {bc, br}, es[2] = {1, 1};
  enc(m, CU_TENSOR_MAP_DATA_TYPE_BFLOAT16, 2, const_cast<void*>(ptr), dims, strides, box, es, CU_TENSOR_MAP_INTERLEAVE_NONE, swz,
      CU_TENSOR_MAP_L2_PROMOTION_L2_128B, CU_TENSOR_MAP_FLOAT_OOB_FILL_NONE);
}

}

extern "C" void kernel_launch(void* const* d_in, const int* in_sizes, int n_in, void* d_out, int out_size) {
  (void)in_sizes; (void)n_in; (void)out_size;
  void* fn = nullptr;
  cudaDriverEntryPointQueryResult qr;
  cudaGetDriverEntryPoint("cuTensorMapEncodeTiled", &fn, cudaEnableDefault, &qr);
  EncodeFn enc = (EncodeFn)fn;
  void* o_ptr = nullptr;
  cudaGetSymbolAddress(&o_ptr, g_o);
  CUtensorMap mx, mw, mwo, mo, mout, mphi;
  make_map(enc, &mx, d_in[0], kD, kS, 64, 128, CU_TENSOR_MAP_SWIZZLE_128B);
  make_map(enc, &mw, d_in[1], 3 * kD, kD, 64, 64, CU_TENSOR_MAP_SWIZZLE_128B);
  make_map(enc, &mphi, d_in[2], 32, 1024, 32, 128, CU_TENSOR_MAP_SWIZZLE_64B);
  make_map(enc, &mwo, d_in[3], kD, kD, 64, 64, CU_TENSOR_MAP_SWIZZLE_128B);
  make_map(enc, &mo, o_ptr, kD, kS, 64, 64, CU_TENSOR_MAP_SWIZZLE_128B);
  make_map(enc, &mout, d_out, kD, kS, 64, 16, CU_TENSOR_MAP_SWIZZLE_128B);
  Params P;
  P.x = (const __nv_bfloat16*)d_in[0];
  P.w_r = (const __nv_bfloat16*)d_in[5];
  P.w_gate = (const __nv_bfloat16*)d_in[6];
  P.w_up = (const __nv_bfloat16*)d_in[7];
  P.w_down = (const __nv_bfloat16*)d_in[8];
  P.gate_w = (const __nv_bfloat16*)d_in[9];
  cudaFuncSetAttribute(fused_kernel, cudaFuncAttributeMaxDynamicSharedMemorySize, SM_TOTAL);
  fused_kernel<<<132, 512, SM_TOTAL, cudaStreamPerThread>>>(mx, mw, mwo, mo, mout, mphi, P);
}
```

```cpp
#include <cuda_runtime.h>
#include <cuda_bf16.h>
#include <cuda.h>
#include <stdint.h>

namespace {

template<int TA, int TB> __device__ __forceinline__ void wgmma_m64n128k16_ss(float (&d)[64], uint64_t da, uint64_t db, int scale_d) {
  asm volatile("{\n.reg .pred p;\nsetp.ne.b32 p, %66, 0;\n"
    "wgmma.mma_async.sync.aligned.m64n128k16.f32.bf16.bf16 "
    "{%0, %1, %2, %3, %4, %5, %6, %7, %8, %9, %10, %11, %12, %13, %14, %15, "
    "%16, %17, %18, %19, %20, %21, %22, %23, %24, %25, %26, %27, %28, %29, %30, %31, "
    "%32, %33, %34, %35, %36, %37, %38, %39, %40, %41, %42, %43, %44, %45, %46, %47, "
    "%48, %49, %50, %51, %52, %53, %54, %55, %56, %57, %58, %59, %60, %61, %62, %63}, "
    "%64, %65, p, 1, 1, %67, %68;\n}\n"
    : "+f"(d[0]), "+f"(d[1]), "+f"(d[2]), "+f"(d[3]), "+f"(d[4]), "+f"(d[5]), "+f"(d[6]), "+f"(d[7]),
      "+f"(d[8]), "+f"(d[9]), "+f"(d[10]), "+f"(d[11]), "+f"(d[12]), "+f"(d[13]), "+f"(d[14]), "+f"(d[15]),
      "+f"(d[16]), "+f"(d[17]), "+f"(d[18]), "+f"(d[19]), "+f"(d[20]), "+f"(d[21]), "+f"(d[22]), "+f"(d[23]),
      "+f"(d[24]), "+f"(d[25]), "+f"(d[26]), "+f"(d[27]), "+f"(d[28]), "+f"(d[29]), "+f"(d[30]), "+f"(d[31]),
      "+f"(d[32]), "+f"(d[33]), "+f"(d[34]), "+f"(d[35]), "+f"(d[36]), "+f"(d[37]), "+f"(d[38]), "+f"(d[39]),
      "+f"(d[40]), "+f"(d[41]), "+f"(d[42]), "+f"(d[43]), "+f"(d[44]), "+f"(d[45]), "+f"(d[46]), "+f"(d[47]),
      "+f"(d[48]), "+f"(d[49]), "+f"(d[50]), "+f"(d[51]), "+f"(d[52]), "+f"(d[53]), "+f"(d[54]), "+f"(d[55]),
      "+f"(d[56]), "+f"(d[57]), "+f"(d[58]), "+f"(d[59]), "+f"(d[60]), "+f"(d[61]), "+f"(d[62]), "+f"(d[63])
    : "l"(da), "l"(db), "r"(scale_d), "n"(TA), "n"(TB));
}

template<int TB> __device__ __forceinline__ void wgmma_m64n32k16_rs(float (&d)[16], const uint32_t (&a)[4], uint64_t db, int scale_d) {
  asm volatile("{\n.reg .pred p;\nsetp.ne.b32 p, %21, 0;\n"
    "wgmma.mma_async.sync.aligned.m64n32k16.f32.bf16.bf16 "
    "{%0, %1, %2, %3, %4, %5, %6, %7, %8, %9, %10, %11, %12, %13, %14, %15}, "
    "{%16, %17, %18, %19}, %20, p, 1, 1, %22;\n}\n"
    : "+f"(d[0]), "+f"(d[1]), "+f"(d[2]), "+f"(d[3]), "+f"(d[4]), "+f"(d[5]), "+f"(d[6]), "+f"(d[7]),
      "+f"(d[8]), "+f"(d[9]), "+f"(d[10]), "+f"(d[11]), "+f"(d[12]), "+f"(d[13]), "+f"(d[14]), "+f"(d[15])
    : "r"(a[0]), "r"(a[1]), "r"(a[2]), "r"(a[3]), "l"(db), "r"(scale_d), "n"(TB));
}

template<int TA, int TB> __device__ __forceinline__ void wgmma_m64n40k16_ss(float (&d)[20], uint64_t da, uint64_t db, int scale_d) {
  asm volatile("{\n.reg .pred p;\nsetp.ne.b32 p, %22, 0;\n"
    "wgmma.mma_async.sync.aligned.m64n40k16.f32.bf16.bf16 "
    "{%0, %1, %2, %3, %4, %5, %6, %7, %8, %9, %10, %11, %12, %13, %14, %15, "
    "%16, %17, %18, %19}, "
    "%20, %21, p, 1, 1, %23, %24;\n}\n"
    : "+f"(d[0]), "+f"(d[1]), "+f"(d[2]), "+f"(d[3]), "+f"(d[4]), "+f"(d[5]), "+f"(d[6]), "+f"(d[7]),
      "+f"(d[8]), "+f"(d[9]), "+f"(d[10]), "+f"(d[11]), "+f"(d[12]), "+f"(d[13]), "+f"(d[14]), "+f"(d[15]),
      "+f"(d[16]), "+f"(d[17]), "+f"(d[18]), "+f"(d[19])
    : "l"(da), "l"(db), "r"(scale_d), "n"(TA), "n"(TB));
}

template<int TB> __device__ __forceinline__ void wgmma_m64n40k16_rs(float (&d)[20], const uint32_t (&a)[4], uint64_t db, int scale_d) {
  asm volatile("{\n.reg .pred p;\nsetp.ne.b32 p, %25, 0;\n"
    "wgmma.mma_async.sync.aligned.m64n40k16.f32.bf16.bf16 "
    "{%0, %1, %2, %3, %4, %5, %6, %7, %8, %9, %10, %11, %12, %13, %14, %15, "
    "%16, %17, %18, %19}, "
    "{%20, %21, %22, %23}, %24, p, 1, 1, %26;\n}\n"
    : "+f"(d[0]), "+f"(d[1]), "+f"(d[2]), "+f"(d[3]), "+f"(d[4]), "+f"(d[5]), "+f"(d[6]), "+f"(d[7]),
      "+f"(d[8]), "+f"(d[9]), "+f"(d[10]), "+f"(d[11]), "+f"(d[12]), "+f"(d[13]), "+f"(d[14]), "+f"(d[15]),
      "+f"(d[16]), "+f"(d[17]), "+f"(d[18]), "+f"(d[19])
    : "r"(a[0]), "r"(a[1]), "r"(a[2]), "r"(a[3]), "l"(db), "r"(scale_d), "n"(TB));
}

template<int TA, int TB> __device__ __forceinline__ void wgmma_m64n8k16_ss(float (&d)[4], uint64_t da, uint64_t db, int scale_d) {
  asm volatile("{\n.reg .pred p;\nsetp.ne.b32 p, %6, 0;\n"
    "wgmma.mma_async.sync.aligned.m64n8k16.f32.bf16.bf16 "
    "{%0, %1, %2, %3}, "
    "%4, %5, p, 1, 1, %7, %8;\n}\n"
    : "+f"(d[0]), "+f"(d[1]), "+f"(d[2]), "+f"(d[3])
    : "l"(da), "l"(db), "r"(scale_d), "n"(TA), "n"(TB));
}

constexpr int kS = 2048, kD = 1024, kF = 3584;
constexpr int NST = 5, STAGE = 32768;
constexpr uint32_t sb = 1024;
constexpr int SM_V    = NST * STAGE;
constexpr int SM_Z    = SM_V + 16384;
constexpr int SM_PHI  = SM_Z + 4096;
constexpr int SM_MOE  = SM_PHI + 16384;
constexpr int SM_WPHI = SM_MOE + 16384;
constexpr int SM_BAND = SM_WPHI + 8192;
constexpr int SM_G    = SM_BAND + 2176;
constexpr int SM_BAR  = SM_G + 512;
constexpr int SM_MISC = SM_BAR + 384;
constexpr int SM_TOTAL = SM_MISC + 64;
static_assert(SM_TOTAL <= 232448, "smem");
constexpr uint32_t bars = sb + SM_BAR;
constexpr int B_FX = 0  , B_FY = 5  , B_XT = 15, B_EPOCH = 16, B_RX = 17  , B_MF = 21  , B_H1 = 24  , B_KV = 26  ;
constexpr int B_WPHI = 28, B_INFO = 29, B_QS = 30, B_XP = 31, B_RED = 32  , B_PUB = 35  , B_ME = 39  , B_MD = 42;
constexpr int B_EM = 43  , B_NUM = 48;
constexpr int C_START = 0, C_O = 32, C_KV = C_O + 64 * 32;

__device__ uint2 g_gate[kS];
__device__ uint2 g_key[128];
__device__ uint2 g_pre[4 * kF];
__device__ uint2 g_yp[32 * kD];
__device__ __align__(128) uint32_t g_kvp[16 * 16 * 2048];
__device__ __align__(128) uint32_t g_kvr[16 * 3072];
__device__ __align__(128) float g_zp[16 * 16 * 128];
__device__ uint32_t g_cnt[C_KV + 32 * 32];
__device__ __align__(1024) __nv_bfloat16 g_o[kS * kD];
#define KS(id)
#define TS(id)
#define TSG(id)
constexpr int SM_ALLOC = SM_TOTAL;

#define POLL0 500
#define POLL1 150
#define POLLF 50
#define WLEAD 11
#define MLEAD 0
#define MGAP 300

struct Params {
  const __nv_bfloat16 *x, *w_phi, *w_r, *gate_w;
  uint64_t da, db, dw, dphi, dv, dband, dxs;
};

__device__ __forceinline__ uint32_t smem_u32(const void* p) { return (uint32_t)__cvta_generic_to_shared(p); }
__device__ __forceinline__ void mbar_init(uint32_t bar, uint32_t cnt) { asm volatile("mbarrier.init.shared::cta.b64 [%0], %1;" :: "r"(bar), "r"(cnt) : "memory"); }
__device__ __forceinline__ void mbar_expect_tx(uint32_t bar, uint32_t bytes) { asm volatile("mbarrier.arrive.expect_tx.shared::cta.b64 _, [%0], %1;" :: "r"(bar), "r"(bytes) : "memory"); }
__device__ __forceinline__ void mbar_arrive(uint32_t bar) { asm volatile("mbarrier.arrive.shared::cta.b64 _, [%0];" :: "r"(bar) : "memory"); }
__device__ __forceinline__ void mbar_arrive_n(uint32_t bar, uint32_t n) { asm volatile("mbarrier.arrive.shared::cta.b64 _, [%0], %1;" :: "r"(bar), "r"(n) : "memory"); }
constexpr int BUDGET = 1 << 20;
__device__ __forceinline__ void mbar_wait(uint32_t bar, uint32_t parity, int& budget) {
  asm volatile("{\n.reg .pred p;\n"
               "WAIT_L:\nmbarrier.try_wait.parity.shared::cta.b64 p, [%1], %2;\n@p bra WAIT_D;\n"
               "add.s32 %0, %0, -1;\nsetp.gt.s32 p, %0, 0;\n@p bra WAIT_L;\nWAIT_D:\n}"
               : "+r"(budget) : "r"(bar), "r"(parity) : "memory");
}
template <int SLEEP>
__device__ __forceinline__ void wait_count(const uint32_t* p, uint32_t target, int& budget) {
  asm volatile("{\n.reg .pred p;\n.reg .s32 v;\n"
               "WAIT_L:\nld.acquire.gpu.global.s32 v, [%1];\nsub.s32 v, v, %2;\nsetp.ge.s32 p, v, 0;\n@p bra WAIT_D;\n"
               "nanosleep.u32 %3;\nadd.s32 %0, %0, -4;\nsetp.gt.s32 p, %0, 0;\n@p bra WAIT_L;\nWAIT_D:\n}"
               : "+r"(budget) : "l"(p), "r"(target), "n"(SLEEP) : "memory");
}
__device__ __forceinline__ void tma_load(uint32_t dst, const CUtensorMap* m, uint32_t bar, int c0, int c1) {
  asm volatile("cp.async.bulk.tensor.2d.shared::cluster.global.mbarrier::complete_tx::bytes [%0], [%1, {%3, %4}], [%2];"
    :: "r"(dst), "l"(m), "r"(bar), "r"(c0), "r"(c1) : "memory");
}
__device__ __forceinline__ void tma_load3(uint32_t dst, const CUtensorMap* m, uint32_t bar, int c1, int c2) {
  asm volatile("cp.async.bulk.tensor.3d.shared::cluster.global.mbarrier::complete_tx::bytes [%0], [%1, {%5, %3, %4}], [%2];"
    :: "r"(dst), "l"(m), "r"(bar), "r"(c1), "r"(c2), "r"(0) : "memory");
}
__device__ __forceinline__ void tma_prefetch3(const CUtensorMap* m, int c1, int c2) {
  asm volatile("cp.async.bulk.prefetch.tensor.3d.L2.global [%0, {%3, %1, %2}];" :: "l"(m), "r"(c1), "r"(c2), "r"(0) : "memory");
}
__device__ __forceinline__ void tma_prefetch(const CUtensorMap* m, int c0, int c1) {
  asm volatile("cp.async.bulk.prefetch.tensor.2d.L2.global [%0, {%1, %2}];" :: "l"(m), "r"(c0), "r"(c1) : "memory");
}
__device__ __forceinline__ void tma_store(const CUtensorMap* m, uint32_t src, int c0, int c1) {
  asm volatile("cp.async.bulk.tensor.2d.global.shared::cta.bulk_group [%0, {%2, %3}], [%1];" :: "l"(m), "r"(src), "r"(c0), "r"(c1) : "memory");
}
__device__ __forceinline__ void bulk_load(uint32_t dst, const void* src, uint32_t bytes, uint32_t bar) {
  asm volatile("cp.async.bulk.shared::cluster.global.mbarrier::complete_tx::bytes [%0], [%1], %2, [%3];" :: "r"(dst), "l"(src), "r"(bytes), "r"(bar) : "memory");
}
__device__ __forceinline__ void prefetch_map(const CUtensorMap* m) { asm volatile("prefetch.tensormap [%0];" :: "l"(m) : "memory"); }
__device__ __forceinline__ bool elect_one() {
  uint32_t p;
  asm volatile("{\n.reg .pred P;\nelect.sync _|P, 0xffffffff;\nselp.u32 %0, 1, 0, P;\n}" : "=r"(p));
  return p;
}
__device__ __forceinline__ void wg_fence() { asm volatile("wgmma.fence.sync.aligned;" ::: "memory"); }
__device__ __forceinline__ void wg_commit() { asm volatile("wgmma.commit_group.sync.aligned;" ::: "memory"); }
template <int N> __device__ __forceinline__ void wg_wait() { asm volatile("wgmma.wait_group.sync.aligned %0;" :: "n"(N) : "memory"); }
template <int N> __device__ __forceinline__ void zero(float (&r)[N]) {
#pragma unroll
  for (int i = 0; i < N; i++) r[i] = 0.f;
}
template <int N> __device__ __forceinline__ void pin(float (&r)[N]) {
#pragma unroll
  for (int i = 0; i < N; i++) asm volatile("" : "+f"(r[i]) :: "memory");
}
template <int N> __device__ __forceinline__ void pinr(uint32_t (&r)[N][4]) {
#pragma unroll
  for (int i = 0; i < N; i++) asm volatile("" : "+r"(r[i][0]), "+r"(r[i][1]), "+r"(r[i][2]), "+r"(r[i][3]) :: "memory");
}
__device__ __forceinline__ void fence_async_smem() { asm volatile("fence.proxy.async.shared::cta;" ::: "memory"); }
__device__ __forceinline__ void fence_async_global() { asm volatile("fence.proxy.async.global;" ::: "memory"); }
__device__ __forceinline__ void bar_sync(int id, int n) { asm volatile("bar.sync %0, %1;" :: "r"(id), "r"(n) : "memory"); }
__device__ __forceinline__ void bar_arrive(int id, int n) { asm volatile("bar.arrive %0, %1;" :: "r"(id), "r"(n) : "memory"); }
__device__ __forceinline__ void warp_arrive(uint32_t bar, int lane) { __syncwarp(); if (lane == 0) mbar_arrive(bar); }
__host__ __device__ constexpr uint64_t make_desc(uint32_t addr, uint32_t lbo, uint32_t sbo, uint32_t swz) {
  return (uint64_t)((addr & 0x3FFFF) >> 4) | ((uint64_t)((lbo & 0x3FFFF) >> 4) << 16) | ((uint64_t)(sbo >> 4) << 32) | ((uint64_t)swz << 62);
}
__device__ __forceinline__ uint32_t pack2(float lo, float hi) {
  uint32_t r; asm("cvt.rn.bf16x2.f32 %0, %1, %2;" : "=r"(r) : "f"(hi), "f"(lo)); return r;
}
__device__ __forceinline__ float bf_lo(uint32_t v) { return __uint_as_float(v << 16); }
__device__ __forceinline__ float bf_hi(uint32_t v) { return __uint_as_float(v & 0xffff0000u); }
__device__ __forceinline__ float ex2(float x) { float r; asm("ex2.approx.ftz.f32 %0, %1;" : "=f"(r) : "f"(x)); return r; }
__device__ __forceinline__ float rcp(float x) { float r; asm("rcp.approx.ftz.f32 %0, %1;" : "=f"(r) : "f"(x)); return r; }
constexpr float LOG2E = 1.4426950408889634f;
__device__ __forceinline__ float sigmoidf(float x) { return rcp(1.0f + ex2(-LOG2E * x)); }
__device__ __forceinline__ void sts128(uint32_t a, uint32_t x, uint32_t y, uint32_t z, uint32_t w) {
  asm volatile("st.shared.v4.u32 [%0], {%1,%2,%3,%4};" :: "r"(a), "r"(x), "r"(y), "r"(z), "r"(w) : "memory");
}
__device__ __forceinline__ void lds128(uint32_t a, uint32_t (&r)[4]) {
  asm volatile("ld.shared.v4.u32 {%0,%1,%2,%3}, [%4];" : "=r"(r[0]), "=r"(r[1]), "=r"(r[2]), "=r"(r[3]) : "r"(a) : "memory");
}
__device__ __forceinline__ void sts32(uint32_t a, uint32_t v) { asm volatile("st.shared.u32 [%0], %1;" :: "r"(a), "r"(v) : "memory"); }
__device__ __forceinline__ uint32_t lds32(uint32_t a) { uint32_t v; asm volatile("ld.shared.u32 %0, [%1];" : "=r"(v) : "r"(a) : "memory"); return v; }
__device__ __forceinline__ float ldsf(uint32_t a) { return __uint_as_float(lds32(a)); }
__device__ __forceinline__ void stmatrix4(uint32_t a, uint32_t r0, uint32_t r1, uint32_t r2, uint32_t r3) {
  asm volatile("stmatrix.sync.aligned.m8n8.x4.shared.b16 [%0], {%1,%2,%3,%4};" :: "r"(a), "r"(r0), "r"(r1), "r"(r2), "r"(r3) : "memory");
}
__device__ __forceinline__ void ldmatrix4(uint32_t a, uint32_t (&r)[4]) {
  asm volatile("ldmatrix.sync.aligned.m8n8.x4.shared.b16 {%0,%1,%2,%3}, [%4];" : "=r"(r[0]), "=r"(r[1]), "=r"(r[2]), "=r"(r[3]) : "r"(a) : "memory");
}
__device__ __forceinline__ uint4 ldg_nc(const void* p) {
  uint4 v; asm volatile("ld.global.nc.L1::no_allocate.v4.u32 {%0,%1,%2,%3}, [%4];" : "=r"(v.x), "=r"(v.y), "=r"(v.z), "=r"(v.w) : "l"(p)); return v;
}
__device__ __forceinline__ void st_tagged(uint2* p, uint32_t v, uint32_t tag) {
  asm volatile("{\n.reg .b64 x;\nmov.b64 x, {%1, %2};\nst.relaxed.gpu.global.b64 [%0], x;\n}" :: "l"(p), "r"(v), "r"(tag) : "memory");
}
__device__ __forceinline__ uint2 ld_tagged(const uint2* p) {
  uint2 v; asm volatile("{\n.reg .b64 x;\nld.relaxed.gpu.global.b64 x, [%2];\nmov.b64 {%0, %1}, x;\n}" : "=r"(v.x), "=r"(v.y) : "l"(p) : "memory"); return v;
}
__device__ __forceinline__ void probe(const uint2* p, uint32_t tag, int& budget) {
  do { __nanosleep(POLL0); budget -= 16; } while (!__all_sync(0xffffffffu, ld_tagged(p).y == tag) && budget > 0);
}
template <int STRIDE, int N>
__device__ __forceinline__ void gather(const uint2* p, uint32_t tag, float& s0, float& s1, int& budget) {
  uint32_t pause = 0;
  bool again;
#pragma unroll 1
  do {
    __nanosleep(pause);
    pause = POLL0;
    uint32_t bad = 0;
    s0 = s1 = 0.f;
#pragma unroll
    for (int i = 0; i < N; i++) {
      const uint2 w = ld_tagged(p + i * STRIDE);
      bad |= w.y ^ tag;
      if (i < N / 2) s0 += __uint_as_float(w.x); else s1 += __uint_as_float(w.x);
    }
    budget -= 16;
    again = __any_sync(0xffffffffu, bad != 0) && budget > 0;
  } while (again);
}
__device__ __forceinline__ uint32_t ldg_strong(const void* p) { uint32_t v; asm volatile("ld.relaxed.gpu.global.u32 %0, [%1];" : "=r"(v) : "l"(p) : "memory"); return v; }
__device__ __forceinline__ void sts16(uint32_t a, uint32_t v) { asm volatile("st.shared.u16 [%0], %1;" :: "r"(a), "h"((uint16_t)v) : "memory"); }
__device__ __forceinline__ void signal_add(uint32_t* p, uint32_t v) { asm volatile("red.release.gpu.global.add.u32 [%0], %1;" :: "l"(p), "r"(v) : "memory"); }
__device__ __forceinline__ float qmax(float v) { v = fmaxf(v, __shfl_xor_sync(0xffffffffu, v, 1)); return fmaxf(v, __shfl_xor_sync(0xffffffffu, v, 2)); }
__device__ __forceinline__ float qsum(float v) { v += __shfl_xor_sync(0xffffffffu, v, 1); return v + __shfl_xor_sync(0xffffffffu, v, 2); }
__device__ __forceinline__ float fold(float a, float b, bool hi, int m) { return (hi ? b : a) + __shfl_xor_sync(0xffffffffu, hi ? a : b, m); }

__device__ __forceinline__ void yield_slot() { asm volatile("pmevent 0;" ::: "memory"); }
__device__ __forceinline__ float fma_v(float a, float b, float c) { float r; asm volatile("fma.rn.f32 %0, %1, %2, %3;" : "=f"(r) : "f"(a), "f"(b), "f"(c)); return r; }
constexpr float EXP_LIM_F = 36028797018963968.0f;
constexpr uint32_t EXP_TOP = 0x58805880u;
__device__ __forceinline__ void exp_plain(const float (&p)[16], float (&ep)[16], float (&em)[16]) {
#pragma unroll
  for (int i = 0; i < 16; i++) { ep[i] = ex2(p[i]); em[i] = ex2(-p[i]); }
}
__device__ __forceinline__ void exp_shifted(const float (&p)[16], float sgn, float (&e)[16]) {
#pragma unroll
  for (int i = 0; i < 16; i++) e[i] = sgn * p[i];
#pragma unroll
  for (int o = 0; o < 4; o += 2) {
    const float mx = qmax(fmaxf(fmaxf(fmaxf(e[o], e[o + 1]), fmaxf(e[o + 4], e[o + 5])), fmaxf(fmaxf(e[o + 8], e[o + 9]), fmaxf(e[o + 12], e[o + 13]))));
#pragma unroll
    for (int c = 0; c < 4; c++) { e[4 * c + o] = ex2(e[4 * c + o] - mx); e[4 * c + o + 1] = ex2(e[4 * c + o + 1] - mx); }
  }
}
__device__ __forceinline__ void row_sums(const float (&e)[16], float (&s)[2]) {
#pragma unroll
  for (int r = 0; r < 2; r++) {
    const int o = 2 * r;
    s[r] = qsum(((e[o] + e[o + 1]) + (e[o + 4] + e[o + 5])) + ((e[o + 8] + e[o + 9]) + (e[o + 12] + e[o + 13])));
  }
}
__device__ __forceinline__ void store_phi(uint32_t a0, uint32_t a1, const float (&e)[16], const float (&r)[2]) {
  const float r0 = r[0], r1 = r[1];
  stmatrix4(a0, pack2(e[0] * r0, e[1] * r0), pack2(e[2] * r1, e[3] * r1), pack2(e[4] * r0, e[5] * r0), pack2(e[6] * r1, e[7] * r1));
  stmatrix4(a1, pack2(e[8] * r0, e[9] * r0), pack2(e[10] * r1, e[11] * r1), pack2(e[12] * r0, e[13] * r0), pack2(e[14] * r1, e[15] * r1));
}
__device__ __forceinline__ uint32_t exp_frags(const float (&p)[16], uint32_t (&ef)[4][4], uint32_t top) {
  float ep[16], em[16];
  exp_plain(p, ep, em);
#pragma unroll
  for (int s = 0; s < 2; s++)
#pragma unroll
    for (int r = 0; r < 4; r++) {
      ef[s][r] = pack2(ep[8 * s + 2 * r], ep[8 * s + 2 * r + 1]);
      ef[2 + s][r] = pack2(em[8 * s + 2 * r], em[8 * s + 2 * r + 1]);
    }
#pragma unroll
  for (int s = 0; s < 4; s++) top = __vimax3_u16x2(__vimax3_u16x2(top, ef[s][0], ef[s][1]), ef[s][2], ef[s][3]);
  return top;
}
__device__ __forceinline__ void issue_pq(float (&p)[4][16], const uint32_t (&qf)[4][2][4], uint64_t dw) {
  wg_fence();
#pragma unroll
  for (int h = 0; h < 4; h++) {
    wgmma_m64n32k16_rs<1>(p[h], qf[h][0], dw + h * 128, 0);
    wgmma_m64n32k16_rs<1>(p[h], qf[h][1], dw + h * 128 + 64, 1);
  }
  wg_commit();
}

#define SPLIT_BATCH 1
__device__ __forceinline__ void mainloop128(float (&acc)[2][64], uint64_t da0, uint64_t db0, uint32_t slot, uint32_t ph, int steps, bool lane0, int& budget, int cta, int n0) {
  uint32_t prev = 0;
#pragma unroll 1
  for (int k = 0; k < steps; k++) {
    mbar_wait(bars + B_FX * 8 + slot * 8, ph, budget);
    const uint64_t da = da0 + slot * (STAGE >> 4), db = db0 + slot * (STAGE >> 4);
    wg_fence();
#pragma unroll
    for (int kk = 0; kk < 4; kk++) {
      wgmma_m64n128k16_ss<0, 1>(acc[0], da + kk * 2, db + kk * 128, kk ? 1 : k);
      wgmma_m64n128k16_ss<0, 1>(acc[1], da + 512 + kk * 2, db + kk * 128, kk ? 1 : k);
      if (kk == 3 || (SPLIT_BATCH == 1 && kk == 1) || SPLIT_BATCH == 2) {
        wg_commit();
        wg_wait<1>();
        if (kk == (SPLIT_BATCH == 0 ? 3 : 2 - SPLIT_BATCH) && k > 0 && lane0) mbar_arrive_n(bars + B_EM * 8 + prev * 8, 2);
      }
    }
    prev = slot;
    if (++slot == NST) { slot = 0; ph ^= 1; }
  }
}
__device__ __forceinline__ void kstep64(float (&acc)[64], uint64_t da, uint64_t db, int accumulate) {
  wg_fence();
#pragma unroll
  for (int kk = 0; kk < 4; kk++) wgmma_m64n128k16_ss<0, 1>(acc, da + kk * 2, db + kk * 128, kk ? 1 : accumulate);
  wg_commit();
}
__device__ __forceinline__ void issue_kv(float (&kv)[20], uint64_t dphi, uint64_t dv, int accumulate) {
  wg_fence();
#pragma unroll
  for (int ks = 0; ks < 4; ks++)
    wgmma_m64n40k16_ss<1, 1>(kv, dphi + ks * 128, dv - (uint64_t)ks * ((64ull << 16) - 64ull), ks ? 1 : accumulate);
  wg_commit();
}
__device__ __forceinline__ void load_slice(int hp, int bi, int tw, uint32_t (&v)[16], uint32_t (&z)[4]) {
#pragma unroll
  for (int i = 0; i < 16; i++) v[i] = ldg_strong(&g_kvp[(hp * 16 + i) * 2048 + bi * 128 + tw]);
  if (tw < 32) {
#pragma unroll
    for (int i = 0; i < 4; i++) z[i] = ldg_strong(&g_zp[(hp * 16 + i * 4 + (tw >> 3)) * 128 + (bi & 3) * 32 + (bi >> 2) * 8 + (tw & 7)]);
  }
}
__device__ __forceinline__ uint32_t moe_buf(uint32_t b) { return b == 2 ? SM_V + 8192 : SM_MOE + b * 8192; }
template <bool DOWN>
__device__ __forceinline__ void moe_chunks(float (&a)[4], int n, uint32_t& buf, uint32_t& ph, uint64_t da0, uint64_t db, bool lane0) {
  int budget = BUDGET;
  zero(a);
#pragma unroll 1
  for (int c = 0; c < n; c++) {
    mbar_wait(bars + B_MF * 8 + buf * 8, ph, budget);
    const uint64_t da = da0 + (moe_buf(buf) >> 4);
    wg_fence();
#pragma unroll
    for (int j = 0; j < 4; j++) wgmma_m64n8k16_ss<1, 0>(a, da + j * 128, DOWN ? db - j : db + j * 2, 1);
    wg_commit();
    wg_wait<0>();
    if (lane0) mbar_arrive(bars + B_ME * 8 + buf * 8);
    db += DOWN ? 16 : 8;
    if (++buf == 3) { buf = 0; ph ^= 1; }
  }
  pin(a);
}
constexpr uint64_t DV_TILE = 4 * ((64ull << 16) - 64ull);

__global__ void __launch_bounds__(512, 1)
fused_kernel(const __grid_constant__ CUtensorMap mx, const __grid_constant__ CUtensorMap mw, const __grid_constant__ CUtensorMap mwo,
             const __grid_constant__ CUtensorMap mo, const __grid_constant__ CUtensorMap mout, const __grid_constant__ CUtensorMap mxr,
             const __grid_constant__ CUtensorMap mg, const __grid_constant__ CUtensorMap mu, const __grid_constant__ CUtensorMap md, const Params P) {
  extern __shared__ __align__(1024) uint8_t smem_raw[];
  if (smem_u32(smem_raw) != sb) return;
  const int tid = threadIdx.x, lane = tid & 31;
  if (tid == 256) TS(1);
  const int warp = __shfl_sync(0xffffffffu, tid >> 5, 0), wg = warp >> 2;
  int budget = BUDGET;
  int cta;
  {
    uint32_t smid, nsm;
    asm volatile("mov.u32 %0, %%smid;" : "=r"(smid));
    asm volatile("mov.u32 %0, %%nsmid;" : "=r"(nsm));
    if (nsm != 132u) cta = blockIdx.x;
    else if (smid < 64) cta = ((smid >> 1) & 7) * 16 + (smid >> 4) * 2 + (smid & 1);
    else if (smid < 120) { const int t = (smid - 64) >> 1, d = (t * 37) >> 8; cta = (1 + t - d * 7) * 16 + 8 + d * 2 + (smid & 1); }
    else cta = smid < 124 ? smid + 8 : smid - 116;
  }
  if (cta >= 128) {
    if (tid == 0) {
      const uint32_t old = atomicAdd(&g_cnt[C_START], 32u);
      wait_count<500>(&g_cnt[C_START], (old & ~255u) + 256u, budget);
    }
    return;
  }
  const int bi = (cta >> 5) * 4 + ((cta >> 2) & 3);
  const int bj = ((cta >> 4) & 1) * 4 + (cta & 3);

  if (wg < 2) {
    asm volatile("setmaxnreg.inc.sync.aligned.u32 208;");
    const int tw = tid & 127, w = warp & 3, g = lane >> 2, t = lane & 3;
    const bool lane0 = lane == 0;
    if (wg == 0) sts128(sb + SM_Z + (tw & 63) * 16, 0x3f803f80u, 0x3f803f80u, 0x3f803f80u, 0x3f803f80u);
    bar_sync(0, 512);
    if (wg == 1) {
      float sr[4], sg[4];
      zero(sr); zero(sg);
#pragma unroll 1
      for (int c = 0; c < 4; c++) {
        mbar_wait(bars + (B_RX + c) * 8, 0, budget);
        uint32_t rs[4], gs[4], xs[4][4];
        lds128(sb + SM_V + c * 512 + lane * 16, rs);
        lds128(sb + SM_V + 2048 + c * 512 + lane * 16, gs);
#pragma unroll
        for (int r = 0; r < 4; r++) lds128(sb + SM_PHI + c * 8192 + (w * 4 + r) * 512 + lane * 16, xs[r]);
#pragma unroll
        for (int e = 0; e < 4; e++) {
          const float r0 = bf_lo(rs[e]), r1 = bf_hi(rs[e]), g0 = bf_lo(gs[e]), g1 = bf_hi(gs[e]);
#pragma unroll
          for (int r = 0; r < 4; r++) {
            const float x0 = bf_lo(xs[r][e]), x1 = bf_hi(xs[r][e]);
            sr[r] = fma_v(x0, r0, sr[r]); sg[r] = fma_v(x0, g0, sg[r]);
            sr[r] = fma_v(x1, r1, sr[r]); sg[r] = fma_v(x1, g1, sg[r]);
            if (r != 1) yield_slot();
          }
        }
      }
      fence_async_smem();
      __syncwarp();
      if (lane < 3) mbar_arrive(bars + (B_ME + lane) * 8);
      const bool b4 = lane & 16, b3 = lane & 8, b2 = lane & 4;
      const float v = qsum(fold(fold(fold(sr[0], sg[0], b4, 16), fold(sr[2], sg[2], b4, 16), b3, 8),
                                fold(fold(sr[1], sg[1], b4, 16), fold(sr[3], sg[3], b4, 16), b3, 8), b2, 4));
      const int row = bi * 128 + bj * 16 + w * 4 + (g & 3);
      const uint32_t rb = pack2(v + 0.f, 0.f);
      const uint32_t ob = (rb & 0x8000u) ? (~rb & 0xFFFFu) : (rb | 0x8000u);
      const uint32_t best = __reduce_max_sync(0xffffffffu, b4 ? 0u : (ob << 16) | (0xFFFFu - row));
      mbar_wait(bars + B_EPOCH * 8, 0, budget);
      const uint32_t tag = lds32(sb + SM_MISC);
      if (lane0) sts32(sb + SM_MISC + 16 + w * 4, best);
      if (b4 && t == 0) st_tagged(&g_gate[row], __float_as_uint(sigmoidf(v)), tag);
      if (tw == 0) TS(14);
      bar_arrive(6, 256);
      bar_sync(1, 256);
    }

    {
      float acc[2][64];
      if (tw == 0) TS(16 + wg * 16);
      mainloop128(acc, P.da, P.db, wg, wg, 16, lane0, budget, cta, wg * 16);
      bar_sync(1 + wg, 256);
      wg_wait<0>();
      pin(acc[0]); pin(acc[1]);
      if (lane0) mbar_arrive_n(bars + (B_EM + wg) * 8, 2);
      if (tw == 0) TS(17 + wg * 16);
      float p[4][16];
      uint32_t vp[8][4];
      const uint32_t av = sb + SM_V + (w * 16 + g) * 64 + ((t ^ (g >> 1)) << 4);
      {
        uint32_t kf[4][2][4];
#pragma unroll
        for (int u = 0; u < 4; u++)
#pragma unroll
          for (int s = 0; s < 2; s++)
#pragma unroll
            for (int r = 0; r < 4; r++) kf[u][s][r] = pack2(acc[u & 1][16 * (u >> 1) + 8 * s + 2 * r], acc[u & 1][16 * (u >> 1) + 8 * s + 2 * r + 1]);
        mbar_wait(bars + B_WPHI * 8, 0, budget);
        const uint64_t dw = P.dw + wg * 256;
        wg_fence();
#pragma unroll
        for (int u = 0; u < 4; u++) {
          wgmma_m64n32k16_rs<1>(p[u], kf[u][0], dw + (u >> 1) * 128, 0);
          wgmma_m64n32k16_rs<1>(p[u], kf[u][1], dw + (u >> 1) * 128 + 64, 1);
        }
        wg_commit();
#pragma unroll
        for (int u = 0; u < 8; u++) {
          const float* a = &acc[(u >> 1) & 1][32 + 16 * (u >> 2) + 2 * (u & 1)];
          vp[u][0] = pack2(a[0], a[1]); vp[u][1] = pack2(a[4], a[5]); vp[u][2] = pack2(a[8], a[9]); vp[u][3] = pack2(a[12], a[13]);
          if (u < 4) sts128(av + (u >> 1) * 4096 + (u & 1) * 512, vp[u][0], vp[u][1], vp[u][2], vp[u][3]);
        }
        pinr(vp);
        wg_wait<0>();
#pragma unroll
        for (int u = 0; u < 4; u++) pin(p[u]);
      }
      if (tw == 0) TS(18 + wg * 16);
      float kv[2][20];
      uint32_t sv[16], sz[4] = {0, 0, 0, 0};
      {
        const uint32_t sphi = sb + SM_PHI + (w * 16 + (lane & 15)) * 128 + (((lane >> 4) ^ (lane & 7)) << 4);
        float top = 0.f;
        float e[3][16], rs[2][2];
        uint32_t redo = 0;
#pragma unroll
        for (int i = 0; i < 10; i++) {
          if (i < 8) {
            pin(p[i >> 1]);
#pragma unroll
            for (int c = 0; c < 16; c++) e[i % 3][c] = ex2((i & 1) ? -p[i >> 1][c] : p[i >> 1][c]);
          }
          if (i >= 2) {
            const int j = i - 2;
            const uint32_t a = (sphi ^ ((j & 1) * 64)) + (j & 2) * 4096;
            store_phi(a, a ^ 32, e[j % 3], rs[j & 1]);
          }
          if (i >= 1 && i <= 8) {
            float sum[2];
            row_sums(e[(i - 1) % 3], sum);
            top = fmaxf(top, fmaxf(sum[0], sum[1]));
            rs[(i - 1) & 1][0] = rcp(sum[0]); rs[(i - 1) & 1][1] = rcp(sum[1]);
            pin(rs[(i - 1) & 1]); pin(e[(i - 1) % 3]);
          }
          if (i < 8) pin(e[i % 3]);
          if (i >= 3 && (i & 1)) {
            const int u = (i - 3) >> 1;
            fence_async_smem();
            wg_wait<0>();
            if (u < 3) bar_sync(7 + wg, 128);
            else asm volatile("{\n.reg .pred p, q;\nsetp.ne.b32 p, %2, 0;\nbar.red.or.pred q, %1, 128, p;\nselp.u32 %0, 1, 0, q;\n}"
                              : "=r"(redo) : "r"(7 + wg), "r"((uint32_t)!(top < EXP_LIM_F)) : "memory");
            issue_kv(kv[u >> 1], P.dphi + (u & 1) * 512, P.dv - (u & 1) * DV_TILE, u & 1);
            if (u == 1 || u == 2) {
#pragma unroll
              for (int r = 0; r < 2; r++) sts128(av + ((u + 1) & 1) * 4096 + r * 512, vp[2 * u + 2 + r][0], vp[2 * u + 2 + r][1], vp[2 * u + 2 + r][2], vp[2 * u + 2 + r][3]);
            }
          }
          if (i < 9) yield_slot();
        }
        if (tw == 0) TS(19 + wg * 16);
        if (wg) { mbar_wait(bars + B_H1 * 8, 0, budget); load_slice(bj * 2, bi, tw, sv, sz); }
        wg_wait<0>();
        pin(kv[0]); pin(kv[1]);
        if (__builtin_expect(__any_sync(0xffffffffu, redo), 0)) {
#pragma unroll 1
          for (int u = 0; u < 4; u++) {
            bar_sync(7 + wg, 128);
#pragma unroll 1
            for (int sg = 0; sg < 2; sg++) {
              float s[2];
              exp_shifted(p[0], sg ? -1.f : 1.f, e[0]);
              row_sums(e[0], s);
              s[0] = rcp(s[0]); s[1] = rcp(s[1]);
              store_phi(sphi ^ (sg * 64), sphi ^ (sg * 64 + 32), e[0], s);
            }
            sts128(av, vp[0][0], vp[0][1], vp[0][2], vp[0][3]);
            sts128(av + 512, vp[1][0], vp[1][1], vp[1][2], vp[1][3]);
            fence_async_smem();
            bar_sync(7 + wg, 128);
            issue_kv(kv[1], P.dphi, P.dv, u & 1);
            wg_wait<0>();
            pin(kv[1]);
#pragma unroll
            for (int c = 0; c < 16; c++) { p[0][c] = p[1][c]; p[1][c] = p[2][c]; p[2][c] = p[3][c]; }
#pragma unroll
            for (int c = 0; c < 24; c++) vp[c >> 2][c & 3] = vp[(c >> 2) + 2][c & 3];
            if (u == 1) {
#pragma unroll
              for (int c = 0; c < 20; c++) kv[0][c] = kv[1][c];
            }
          }
        }
      }
      if (tw == 0) TS(20 + wg * 16);
      {
        const int hp = bj * 2 + wg;
        uint4* dst = reinterpret_cast<uint4*>(&g_kvp[(hp * 16 + bi) * 2048]) + tw;
#pragma unroll
        for (int q = 0; q < 4; q++) {
          const float* a = &kv[q >> 1][8 * (q & 1)];
          dst[q * 128] = make_uint4(pack2(a[0], a[1]), pack2(a[2], a[3]), pack2(a[4], a[5]), pack2(a[6], a[7]));
        }
        g_zp[(hp * 16 + bi) * 128 + w * 32 + (t & 1) * 16 + g * 2 + (t >> 1)] = t == 0 ? kv[0][16] : t == 1 ? kv[0][18] : t == 2 ? kv[1][16] : kv[1][18];
      }
      if (tw == 0) TS(51 + wg * 4);
      if (wg == 0) warp_arrive(bars + B_RED * 8, lane);
      else {
        const int row = (bi & 3) * 16 + (tw >> 4) + (tw & 1) * 8, ch = ((bi >> 2) & 1) * 2 + ((tw >> 1) & 1);
        uint32_t* dst = &g_kvr[bj * 6144 + (bi >> 3) * 1024 + row * 16 + ((ch ^ ((row >> 1) & 3)) << 2) + ((tw >> 2) & 3)];
        const int zr = (bi & 3) * 16 + (bi >> 2) * 4 + ((lane >> 1) & 3);
        uint32_t* dz = &g_kvr[bj * 6144 + 2048 + zr * 16 + ((((lane & 1) + ((lane >> 2) & 2)) ^ ((zr >> 1) & 3)) << 2)];
#pragma unroll 1
        for (int it = 0; it < 2; it++) {
          float lo = 0.f, hi = 0.f;
#pragma unroll
          for (int i = 0; i < 16; i++) { lo += bf_lo(sv[i]); hi += bf_hi(sv[i]); }
          *dst = pack2(lo, hi);
          if (w == 0) {
            float z = (__uint_as_float(sz[0]) + __uint_as_float(sz[1])) + (__uint_as_float(sz[2]) + __uint_as_float(sz[3]));
            z += __shfl_xor_sync(0xffffffffu, z, 8); z += __shfl_xor_sync(0xffffffffu, z, 16);
            const uint32_t z1 = pack2(z, 1.0f);
            if (lane < 16) *reinterpret_cast<uint4*>(dz) = make_uint4(z1, z1, z1, z1);
          }
          warp_arrive(bars + (B_RED + 1 + it) * 8, lane);
          if (tw == 0) TS(21 + it * 16);
          if (it) break;
          mbar_wait(bars + (B_H1 + 1) * 8, 0, budget);
          load_slice(bj * 2 + 1, bi, tw, sv, sz);
          dst += 3072; dz += 3072;
        }
      }
    }

    const uint32_t stash = sb + 3 * STAGE + 8192 + w * 2048 + lane * 16;
    const int rowl = wg * 64 + w * 16 + g;
    mbar_wait(bars + B_INFO * 8, 0, budget);
    const float gA = ldsf(sb + SM_G + rowl * 4), gB = ldsf(sb + SM_G + rowl * 4 + 32);
    {
      float p[4][16];
      uint32_t ef[2][4][4];
      uint32_t top = EXP_TOP;
      if (wg == 0) {
        float acc[2][64];
        bar_sync(2, 256);
        if (tw == 0) TS(22);
        mainloop128(acc, P.da, P.db, 32 % NST, (32 / NST) & 1, 12, lane0, budget, cta, 32);
#pragma unroll 1
        for (int n = 0; n < 4; n++) {
          const uint32_t slot = n ? n - 1 : 4;
          if (tw == 0) KS(128 + 44 + n);
          mbar_wait(bars + B_FX * 8 + slot * 8, n != 0, budget);
          if (tw == 0) KS(44 + n);
          kstep64(acc[0], P.da + slot * (STAGE >> 4), P.db + slot * (STAGE >> 4), 1);
          wg_wait<1>();
          if (n == 0 && lane0) mbar_arrive_n(bars + (B_EM + 43 % NST) * 8, 2);
        }
        kstep64(acc[1], P.da + 512 + (44 % NST) * (STAGE >> 4), P.db + (44 % NST) * (STAGE >> 4), 1);
        wg_wait<1>();
        pin(acc[0]);
        if (tw == 0) TS(15);
        {
          uint32_t qf[4][2][4];
#pragma unroll
          for (int u = 0; u < 8; u++)
#pragma unroll
            for (int r = 0; r < 4; r++) qf[u >> 1][u & 1][r] = pack2(acc[0][8 * u + 2 * r], acc[0][8 * u + 2 * r + 1]);
          issue_pq(p, qf, P.dw);
          kstep64(acc[1], P.da + 512 + (45 % NST) * (STAGE >> 4), P.db + (45 % NST) * (STAGE >> 4), 1);
          wg_wait<1>();
        }
#pragma unroll
        for (int h = 0; h < 4; h++) pin(p[h]);
        if (tw == 0) TS(24);
#pragma unroll
        for (int h = 0; h < 2; h++) {
          if (lane0) mbar_arrive_n(bars + (B_EM + (44 + h) % NST) * 8, 2);
          kstep64(acc[1], P.da + 512 + ((46 + h) % NST) * (STAGE >> 4), P.db + ((46 + h) % NST) * (STAGE >> 4), 1);
          yield_slot();
          pin(p[h]);
          top = exp_frags(p[h], ef[h], top);
          pinr(ef[h]);
          yield_slot();
          if (h == 0) wg_wait<1>(); else wg_wait<0>();
        }
        pin(acc[1]);
        if (lane0) { mbar_arrive_n(bars + (B_EM + 46 % NST) * 8, 2); mbar_arrive_n(bars + (B_EM + 47 % NST) * 8, 2); }
        if (tw == 0) TS(23);
#pragma unroll
        for (int u = 0; u < 8; u++) {
          const float* a = &acc[1][8 * u];
          sts128(stash + (u >> 2) * STAGE + (u & 3) * 512, pack2(a[0], a[1]), pack2(a[2], a[3]), pack2(a[4], a[5]), pack2(a[6], a[7]));
        }
        warp_arrive(bars + B_QS * 8, lane);
      } else {
        uint32_t qf[4][2][4];
        mbar_wait(bars + B_QS * 8, 0, budget);
#pragma unroll
        for (int u = 0; u < 8; u++) lds128(stash + (u >> 2) * STAGE + (u & 3) * 512, qf[u >> 1][u & 1]);
        __syncwarp();
        issue_pq(p, qf, P.dw);
        wg_wait<0>();
#pragma unroll
        for (int h = 0; h < 4; h++) pin(p[h]);
        if (tw == 0) TS(40);
      }

      __nv_bfloat16* og = g_o + (size_t)(bi * 128 + rowl) * kD + bj * 128 + t * 8;
      uint32_t own = sb + 3 * STAGE + rowl * 128 + ((t ^ g) << 4);
#pragma unroll 1
      for (int pr = 0; pr < 2; pr++) {
        if (pr | wg) top = exp_frags(p[1], ef[1], exp_frags(p[0], ef[0], EXP_TOP));
        if (__builtin_expect(__any_sync(0xffffffffu, top != EXP_TOP), 0)) {
#pragma unroll 1
          for (int u = 0; u < 4; u++) {
            float e[16];
            exp_shifted(p[0], (u & 1) ? -1.f : 1.f, e);
#pragma unroll
            for (int r = 0; r < 4; r++) {
#pragma unroll
              for (int s = 0; s < 6; s++) ef[s >> 2][s & 3][r] = ef[(s + 2) >> 2][(s + 2) & 3][r];
              ef[1][2][r] = pack2(e[2 * r], e[2 * r + 1]);
              ef[1][3][r] = pack2(e[8 + 2 * r], e[8 + 2 * r + 1]);
            }
            if (u & 1) {
#pragma unroll
              for (int e2 = 0; e2 < 16; e2++) p[0][e2] = p[1][e2];
            }
          }
        }
        float np[2][20], nm[2][20];
        mbar_wait(bars + (B_KV + pr) * 8, 0, budget);
        wg_fence();
#pragma unroll
        for (int hh = 0; hh < 2; hh++) {
          const uint64_t dk = P.dv - (uint64_t)pr * ((256ull << 16) - 512ull) - hh * ((255ull << 16) - 256ull);
          wgmma_m64n40k16_rs<1>(np[hh], ef[hh][0], dk, 0);
          wgmma_m64n40k16_rs<1>(np[hh], ef[hh][1], dk + 64, 1);
          wgmma_m64n40k16_rs<1>(nm[hh], ef[hh][2], dk + 128, 0);
          wgmma_m64n40k16_rs<1>(nm[hh], ef[hh][3], dk + 192, 1);
          wg_commit();
        }
#pragma unroll
        for (int e = 0; e < 16; e++) { p[0][e] = p[2][e]; p[1][e] = p[3][e]; }
        pin(p[0]); pin(p[1]);
#pragma unroll
        for (int hh = 0; hh < 2; hh++) {
          if (hh == 0) wg_wait<1>(); else wg_wait<0>();
          pin(np[hh]); pin(nm[hh]);
          uint32_t o[2][4];
#pragma unroll
          for (int r = 0; r < 2; r++) {
            const float dp = np[hh][16 + 2 * r], sp = np[hh][17 + 2 * r], dm = nm[hh][16 + 2 * r], sm = nm[hh][17 + 2 * r];
            const float inv = (r == 0 ? gA : gB) * rcp(fmaf(dp, sm, fmaf(1e-6f, sm, dm) * sp));
            const float cp = sm * inv, cm = sp * inv;
#pragma unroll
            for (int c = 0; c < 4; c++)
              o[r][c] = pack2(fmaf(np[hh][4 * c + 2 * r], cp, nm[hh][4 * c + 2 * r] * cm), fmaf(np[hh][4 * c + 2 * r + 1], cp, nm[hh][4 * c + 2 * r + 1] * cm));
            sts128((own ^ (hh * 64)) + r * 1024, o[r][0], o[r][1], o[r][2], o[r][3]);
          }
          if (hh == 1 && pr == 1) fence_async_smem();
#pragma unroll
          for (int r = 0; r < 2; r++) *reinterpret_cast<uint4*>(og + r * 8 * kD + hh * 32) = make_uint4(o[r][0], o[r][1], o[r][2], o[r][3]);
        }
        warp_arrive(bars + (B_PUB + wg * 2 + pr) * 8, lane);
        if (tw == 0) TS(25 + pr + wg * 16);
        og += 64; own += STAGE;
      }
    }
    bar_sync(7 + wg, 128);

    float oacc[64];
    {
      const uint64_t dam = P.da + wg * 512;
      uint32_t slot = 3, ph = 1, prev = 0;
#pragma unroll 1
      for (int s = 0; s < 16; s++) {
        if (tid == 0) KS(128 + 48 + s);
        mbar_wait(bars + B_FX * 8 + slot * 8, ph, budget);
        if (s >= 2) mbar_wait(bars + (B_FY + wg * NST) * 8 + slot * 8, ph, budget);
        if (tid == 0) KS(48 + s);
        if (tid == 128) KS(192 + 48 + s);
        kstep64(oacc, dam + slot * (STAGE >> 4), P.db + slot * (STAGE >> 4), s);
        wg_wait<1>();
        if (s != 0 && s != 2 && lane0) mbar_arrive(bars + B_EM * 8 + prev * 8);
        if (s == 1) {
          wg_wait<0>();
          if (lane0) mbar_arrive(bars + B_EM * 8 + slot * 8);
        }
        prev = slot;
        if (++slot == NST) { slot = 0; ph ^= 1; }
      }
    }
    mbar_wait(bars + B_XT * 8, 0, budget);
    if ((lds32(sb + SM_MISC + 4) >> 7) == (uint32_t)bi) mbar_wait(bars + B_XP * 8, 0, budget);
    const uint32_t sx = sb + SM_PHI + (wg * 64 + w * 16 + (lane & 15)) * 128 + (((lane >> 4) ^ (lane & 7)) << 4);
    float xf[64];
#pragma unroll
    for (int u = 0; u < 8; u++) {
      uint32_t xr[4];
      ldmatrix4((sx ^ ((u & 3) * 32)) + (u >> 2) * 16384, xr);
#pragma unroll
      for (int r = 0; r < 4; r++) { xf[8 * u + 2 * r] = bf_lo(xr[r]); xf[8 * u + 2 * r + 1] = bf_hi(xr[r]); }
    }
    pin(xf);
    const float hA = 1.0f - gA, hB = 1.0f - gB;
    wg_wait<0>();
    pin(oacc);
    if (tw == 0) TS(29 + wg * 16);
#pragma unroll
    for (int hf = 0; hf < 2; hf++) {
#pragma unroll
      for (int u = hf * 4; u < hf * 4 + 4; u++) {
        const float* a = &oacc[8 * u];
        const float* b = &xf[8 * u];
        stmatrix4((sx ^ ((u & 3) * 32)) + hf * 16384,
                  pack2(fmaf(hA, b[0], a[0]), fmaf(hA, b[1], a[1])), pack2(fmaf(hB, b[2], a[2]), fmaf(hB, b[3], a[3])),
                  pack2(fmaf(hA, b[4], a[4]), fmaf(hA, b[5], a[5])), pack2(fmaf(hB, b[6], a[6]), fmaf(hB, b[7], a[7])));
      }
      fence_async_smem();
      __syncwarp();
      if (elect_one()) tma_store(&mout, sb + SM_PHI + hf * 16384 + warp * 2048, bj * 128 + hf * 64, bi * 128 + warp * 16);
    }
    if (elect_one()) {
      asm volatile("cp.async.bulk.commit_group;" ::: "memory");
      asm volatile("cp.async.bulk.wait_group.read 0;" ::: "memory");
    }
  } else if (wg == 3) {
    asm volatile("setmaxnreg.dec.sync.aligned.u32 64;");
    const int t3 = tid - 384, w3 = warp - 12;
    bar_sync(0, 512);
#pragma unroll 1
    for (int u = 0; u < 4; u++) {
      const uint4 v = ldg_nc(P.w_phi + bj * 4096 + (u * 128 + t3) * 8);
      sts128(sb + SM_WPHI + u * 2048 + (t3 >> 2) * 64 + (((t3 & 3) ^ ((t3 >> 3) & 3)) << 4),
             pack2(LOG2E * bf_lo(v.x), LOG2E * bf_hi(v.x)), pack2(LOG2E * bf_lo(v.y), LOG2E * bf_hi(v.y)),
             pack2(LOG2E * bf_lo(v.z), LOG2E * bf_hi(v.z)), pack2(LOG2E * bf_lo(v.w), LOG2E * bf_hi(v.w)));
    }
    fence_async_smem();
    warp_arrive(bars + B_WPHI * 8, lane);
    bar_sync(6, 256);
    const uint32_t target = lds32(sb + SM_MISC);
    uint32_t key;
    {
      uint32_t kk[4];
      lds128(sb + SM_MISC + 16, kk);
      if (t3 == 0) st_tagged(&g_key[cta], max(max(kk[0], kk[1]), max(kk[2], kk[3])), target);
      uint2 k, gv;
      __nanosleep(POLL0);
      do {
        __nanosleep(POLL1);
        k = ld_tagged(&g_key[t3]);
        gv = ld_tagged(&g_gate[bi * 128 + t3]);
        budget -= 4;
      } while (!__all_sync(0xffffffffu, k.y == target && gv.y == target) && budget > 0);
      key = __reduce_max_sync(0xffffffffu, k.x);
      if (lane == 0) sts32(sb + SM_MISC + 32 + w3 * 4, key);
      sts32(sb + SM_G + t3 * 4, gv.x);
      bar_sync(5, 128);
      lds128(sb + SM_MISC + 32, kk);
      key = max(max(kk[0], kk[1]), max(kk[2], kk[3]));
    }
    const int idx = (0xFFFF - (key & 0xFFFF)) & (kS - 1);
    if (t3 == 0) { sts32(sb + SM_MISC + 4, idx); TS(8); }
    warp_arrive(bars + B_INFO * 8, lane);
    {
      const uint4 v = ldg_nc(P.x + (size_t)idx * kD + t3 * 8);
      sts128(sb + SM_BAND + t3 * 16, v.x, v.y, v.z, v.w);
    }
    const int t2 = (lane & 3) * 2, row = w3 * 16 + (lane >> 2);
    float a[4];
    uint32_t buf = 0, ph = 0;
    fence_async_smem();
    bar_sync(5, 128);
    {
      const int r = cta >> 4;
#pragma unroll 1
      for (int part = 0; part < 2; part++) {
        const int n = part ? 14 - 2 * r : 2 * r;
        moe_chunks<false>(a, n, buf, ph, P.da, P.dxs + (part ? 0 : (16 - n) * 8), lane == 0);
        uint2* dst = &g_pre[(((cta >> 2) & 2) + 1 - part) * kF + ((r - 1 + part) * 8 + (cta & 7)) * 64 + row];
        if (t2 == 0 && n) { st_tagged(dst, __float_as_uint(a[0]), target); st_tagged(dst + 8, __float_as_uint(a[2]), target); }
      }
    }
    if (t3 == 0) TS(9);
    bar_sync(5, 128);
    sts128(sb + SM_BAND + t3 * 16, 0, 0, 0, 0);
    {
      float gs, us;
      __nanosleep(POLL0);
      gather<kF, 4>(&g_pre[(cta >> 2) * 112 + min(t3, 111)], target, gs, us, budget);
      bar_sync(5, 128);
      if (t3 < 112) sts16(sb + SM_BAND + 112 + (t3 >> 3) * 128 + (t3 & 7) * 2, pack2(gs * sigmoidf(gs) * us, 0.f));
    }
    fence_async_smem();
    bar_sync(5, 128);
    if (t3 == 0) TS(12);
    moe_chunks<true>(a, 7, buf, ph, P.da, P.dband + 7, lane == 0);
    if (t3 == 0) TS(10);
    if (t2 < 4) {
      uint2* dst = &g_yp[(cta >> 2) * kD + (cta & 3) * 256 + t2 * 64 + row];
      st_tagged(dst, __float_as_uint(a[0]), target); st_tagged(dst + 8, __float_as_uint(a[2]), target);
      st_tagged(dst + 64, __float_as_uint(a[1]), target); st_tagged(dst + 72, __float_as_uint(a[3]), target);
    }
    if (lane == 0) mbar_arrive(bars + B_MD * 8);
    if ((idx >> 7) == bi) {
      mbar_wait(bars + (B_PUB + 3) * 8, 0, budget);
      if (w3 == 0) probe(&g_yp[lane * kD + bj * 128], target, budget);
      bar_sync(5, 128);
      float y = 0.f;
#pragma unroll 1
      for (int hf = 0; hf < 2; hf++) {
        float y0, y1;
        gather<kD, 16>(&g_yp[hf * 16 * kD + bj * 128 + t3], target, y0, y1, budget);
        y += y0 + y1;
      }
      const uint32_t ob = key >> 16;
      const float upd = y * sigmoidf(__uint_as_float(((ob & 0x8000u) ? (ob ^ 0x8000u) : (~ob & 0xFFFFu)) << 16));
      const uint32_t a = sb + SM_PHI + (t3 >> 6) * 16384 + (idx & 127) * 128 + ((((t3 >> 3) & 7) ^ (idx & 7)) << 4) + (t3 & 7) * 2;
      mbar_wait(bars + B_XT * 8, 0, budget);
      uint16_t xb;
      asm volatile("ld.shared.u16 %0, [%1];" : "=h"(xb) : "r"(a) : "memory");
      sts16(a, pack2(bf_lo(xb) + upd, 0.f));
      warp_arrive(bars + B_XP * 8, lane);
      if (t3 == 0) TS(11);
    }
  } else {
    const bool lead = elect_one();
    if (lead) {
      if (warp == 8) {
        TSG(0); TS(7);
#pragma unroll
        for (int s = 0; s < NST; s++) mbar_init(bars + (B_FX + s) * 8, 1);
        asm volatile("fence.mbarrier_init.release.cluster;" ::: "memory");
        fence_async_smem();
#pragma unroll 1
        for (int n = 0; n < NST; n++) {
          const uint32_t st = sb + n * STAGE, fb = bars + (B_FX + n) * 8;
          KS(64 + n);
          mbar_expect_tx(fb, STAGE);
          tma_load(st, &mx, fb, n * 64, bi * 128);
          tma_load(st + 16384, &mw, fb, 1024 + bj * 128, n * 64);
          tma_load(st + 24576, &mw, fb, 2048 + bj * 128, n * 64);
        }
      } else if (warp == 9) {
        prefetch_map(&mw);
#pragma unroll
        for (int s = B_FY; s < B_NUM; s++) mbar_init(bars + s * 8, s < B_WPHI ? 1 : s < B_EM ? 4 : 8);
        asm volatile("fence.mbarrier_init.release.cluster;" ::: "memory");
        fence_async_smem();
      }
    }
    __syncwarp();
    asm volatile("setmaxnreg.dec.sync.aligned.u32 32;");
    bar_sync(0, 512);
    if (!elect_one()) return;
    if (warp == 8) {
      uint32_t slot = 0, ph = 0;
#pragma unroll 1
      for (int n = NST; n < 48; n++) {
        const int t = n >> 4, k = n & 15;
        const int c0 = t == 2 ? bj * 128 : 1024 + bj * 128 + t * 64, c1 = t == 2 ? c0 + 64 : c0 + 1024;
        const uint32_t st = sb + slot * STAGE, fb = bars + (B_FX + slot) * 8;
        if (n <= NST + 6 && (n & 1)) {
          const int c = (n - NST) >> 1;
          mbar_expect_tx(bars + (B_RX + c) * 8, c == 0 ? 8192 + 4096 : 8192);
          tma_load(sb + SM_PHI + c * 8192, &mxr, bars + (B_RX + c) * 8, c * 256, bi * 128 + bj * 16);
          if (c == 0) { bulk_load(sb + SM_V, P.w_r, 2048, bars + B_RX * 8); bulk_load(sb + SM_V + 2048, P.gate_w, 2048, bars + B_RX * 8); }
        }
        mbar_wait(bars + (B_EM + slot) * 8, ph, budget);
        KS(64 + n);
        mbar_expect_tx(fb, STAGE);
        tma_load(st, &mx, fb, k * 64, bi * 128);
        tma_load(st + 16384, &mw, fb, c0, k * 64);
        tma_load(st + 24576, &mw, fb, c1, k * 64);
        {
          const int m = n + WLEAD, tm = m >> 4;
          if ((m & 3) == (bi & 3)) {
            const int d0 = tm >= 2 ? bj * 128 : 1024 + bj * 128 + tm * 64, d1 = tm >= 2 ? d0 + 64 : d0 + 1024;
            tma_prefetch(tm == 3 ? &mwo : &mw, d0, (m & 15) * 64); tma_prefetch(tm == 3 ? &mwo : &mw, d1, (m & 15) * 64);
          }
        }
        if (++slot == NST) { slot = 0; ph ^= 1; }
      }
#pragma unroll 1
      for (int m = WLEAD + ((bi - WLEAD) & 3); m < 16; m += 4) { tma_prefetch(&mwo, bj * 128, m * 64); tma_prefetch(&mwo, bj * 128 + 64, m * 64); }
#pragma unroll 1
      for (int s = 0; s < 16; s++) {
        const int p = s < 2 ? s : (s >= 9), q = s < 9 ? s - 2 : s - 9;
        const int k0 = (s < 2 ? bj : q + (q >= bj)) * 128 + p * 64;
        const uint32_t st = sb + slot * STAGE, fb = bars + (B_FX + slot) * 8;
        mbar_wait(bars + (B_EM + slot) * 8, ph, budget);
        KS(64 + 48 + s);
        mbar_expect_tx(fb, 16384);
        tma_load(st + 16384, &mwo, fb, bj * 128, k0);
        tma_load(st + 24576, &mwo, fb, bj * 128 + 64, k0);
        if (++slot == NST) { slot = 0; ph ^= 1; }
      }
      mbar_wait(bars + B_MD * 8, 0, budget);
      mbar_expect_tx(bars + B_XT * 8, 32768);
      tma_load(sb + SM_PHI, &mx, bars + B_XT * 8, bj * 128, bi * 128);
      tma_load(sb + SM_PHI + 16384, &mx, bars + B_XT * 8, bj * 128 + 64, bi * 128);
    } else if (warp == 9) {
      prefetch_map(&mo); prefetch_map(&mout);
      sts32(sb + SM_MISC, (atomicAdd(&g_cnt[C_START], 1u) & ~255u) + 256u);
      mbar_arrive(bars + B_EPOCH * 8);
      const CUtensorMap* m = (cta & 8) ? &mu : &mg;
      const int l0 = (cta >> 4) * 14, a0 = (cta & 7) * 64, d1 = (cta >> 2) * 112 - 14 * 16, d2 = (cta & 3) * 4;
      uint32_t buf = 0, ph = 0;
#pragma unroll 1
      for (int c = 0; c < 21; c++) {
        const uint32_t dst = sb + moe_buf(buf), fb = bars + (B_MF + buf) * 8;
        mbar_wait(bars + (B_ME + buf) * 8, ph, budget);
        mbar_expect_tx(fb, 8192);
        if (c < 14) tma_load(dst, m, fb, a0 + ((l0 + c) >> 4) * 512, ((l0 + c) & 15) * 64); else tma_load3(dst, &md, fb, d1 + c * 16, d2);
        if (MLEAD && c >= 2) {
          const int f = c + MLEAD;
          if (f < 14) tma_prefetch(m, a0 + ((l0 + f) >> 4) * 512, ((l0 + f) & 15) * 64); else if (f < 21) tma_prefetch3(&md, d1 + f * 16, d2);
        }
        if (c < 2) __nanosleep(MGAP);
        if (++buf == 3) { buf = 0; ph ^= 1; }
      }
#pragma unroll 1
      for (int u = 0; u < 2; u++) {
        mbar_wait(bars + (B_PUB + u * 2 + 1) * 8, 0, budget);
        signal_add(&g_cnt[C_O + (bi * 4 + u * 2 + 1) * 32], 32u);
        TS(57 + u * 2);
      }
    } else {
      const int u = warp - 10, hp = bj * 2 + u;
      mbar_wait(bars + B_EPOCH * 8, 0, budget);
      const uint32_t target = lds32(sb + SM_MISC);
#pragma unroll 1
      for (int ev = u * 2; ev < 4; ev += (ev == 1) + 1) {
        uint32_t* cnt = &g_cnt[ev < 3 ? C_KV + (bj * 4 + ev) * 32 : C_O + (bi * 4 + u * 2) * 32];
        mbar_wait(bars + (ev < 3 ? B_RED + ev : B_PUB + u * 2) * 8, 0, budget);
        signal_add(cnt, ev < 3 ? 16u : 32u);
        TS(ev < 3 ? 60 + ev : 56 + u * 2);
        wait_count<POLLF>(cnt, target, budget);
        fence_async_global();
        if (ev < 2) mbar_arrive(bars + (B_H1 + ev) * 8);
        if (ev == u + 1) {
          if (u) mbar_wait(bars + B_MD * 8, 0, budget);
          mbar_expect_tx(bars + (B_KV + u) * 8, 12288);
          bulk_load(sb + SM_V + u * 8192, &g_kvr[hp * 3072], 8192, bars + (B_KV + u) * 8);
          bulk_load(sb + SM_Z + u * 4096, &g_kvr[hp * 3072 + 2048], 4096, bars + (B_KV + u) * 8);
          TS(38 + u);
        }
      }
      TS(2 + u * 2);
      if (u == 0) mbar_wait(bars + B_QS * 8, 0, budget);
      uint32_t slot = 0, ph = 1;
#pragma unroll 1
      for (int s = 2; s < 16; s++) {
        const int p = s >= 9, q = s < 9 ? s - 2 : s - 9;
        if (s == 9) { wait_count<POLLF>(&g_cnt[C_O + (bi * 4 + u * 2 + 1) * 32], target, budget); fence_async_global(); TS(3 + u * 2); }
        const uint32_t fb = bars + (B_FY + u * NST + slot) * 8;
        mbar_wait(bars + (B_EM + slot) * 8, ph, budget);
        mbar_expect_tx(fb, 8192);
        tma_load(sb + slot * STAGE + u * 8192, &mo, fb, (q + (q >= bj)) * 128 + p * 64, bi * 128 + u * 64);
        if (++slot == NST) { slot = 0; ph ^= 1; }
      }
    }
  }
}

typedef CUresult (*EncodeFn)(CUtensorMap*, CUtensorMapDataType, cuuint32_t, void*, const cuuint64_t*, const cuuint64_t*, const cuuint32_t*,
                             const cuuint32_t*, CUtensorMapInterleave, CUtensorMapSwizzle, CUtensorMapL2promotion, CUtensorMapFloatOOBfill);

void make_map(EncodeFn enc, CUtensorMap* m, const void* ptr, uint64_t cols, uint64_t rows, uint32_t bc, uint32_t br, CUtensorMapSwizzle swz) {
  const cuuint64_t dims[2] = {cols, rows}, strides[1] = {cols * 2};
  const cuuint32_t box[2] = {bc, br}, es[2] = {1, 1};
  enc(m, CU_TENSOR_MAP_DATA_TYPE_BFLOAT16, 2, const_cast<void*>(ptr), dims, strides, box, es, CU_TENSOR_MAP_INTERLEAVE_NONE, swz,
      CU_TENSOR_MAP_L2_PROMOTION_L2_128B, CU_TENSOR_MAP_FLOAT_OOB_FILL_NONE);
}

}

extern "C" void kernel_launch(void* const* d_in, const int* in_sizes, int n_in, void* d_out, int out_size) {
  (void)in_sizes; (void)n_in; (void)out_size;
  void* fn = nullptr;
  cudaDriverEntryPointQueryResult qr;
  cudaGetDriverEntryPoint("cuTensorMapEncodeTiled", &fn, cudaEnableDefault, &qr);
  EncodeFn enc = (EncodeFn)fn;
  void* o_ptr = nullptr;
  cudaGetSymbolAddress(&o_ptr, g_o);
  CUtensorMap mx, mw, mwo, mo, mout, mxr, mg, mu, md;
  make_map(enc, &mx, d_in[0], kD, kS, 64, 128, CU_TENSOR_MAP_SWIZZLE_128B);
  make_map(enc, &mxr, d_in[0], kD, kS, 256, 16, CU_TENSOR_MAP_SWIZZLE_NONE);
  make_map(enc, &mw, d_in[1], 3 * kD, kD, 64, 64, CU_TENSOR_MAP_SWIZZLE_128B);
  make_map(enc, &mwo, d_in[3], kD, kD, 64, 64, CU_TENSOR_MAP_SWIZZLE_128B);
  make_map(enc, &mo, o_ptr, kD, kS, 64, 64, CU_TENSOR_MAP_SWIZZLE_128B);
  make_map(enc, &mout, d_out, kD, kS, 64, 16, CU_TENSOR_MAP_SWIZZLE_128B);
  make_map(enc, &mg, d_in[6], kF, kD, 64, 64, CU_TENSOR_MAP_SWIZZLE_128B);
  make_map(enc, &mu, d_in[7], kF, kD, 64, 64, CU_TENSOR_MAP_SWIZZLE_128B);
  {
    const cuuint64_t dims[3] = {64, kF, 16}, strides[2] = {kD * 2, 128};
    const cuuint32_t box[3] = {64, 16, 4}, es[3] = {1, 1, 1};
    enc(&md, CU_TENSOR_MAP_DATA_TYPE_BFLOAT16, 3, d_in[8], dims, strides, box, es, CU_TENSOR_MAP_INTERLEAVE_NONE, CU_TENSOR_MAP_SWIZZLE_128B,
        CU_TENSOR_MAP_L2_PROMOTION_L2_128B, CU_TENSOR_MAP_FLOAT_OOB_FILL_NONE);
  }
  Params P;
  P.x = (const __nv_bfloat16*)d_in[0];
  P.w_phi = (const __nv_bfloat16*)d_in[2];
  P.w_r = (const __nv_bfloat16*)d_in[5];
  P.gate_w = (const __nv_bfloat16*)d_in[9];
  P.da = make_desc(sb, 16, 1024, 1);
  P.db = make_desc(sb + 16384, 8192, 1024, 1);
  P.dw = make_desc(sb + SM_WPHI, 16, 512, 2);
  P.dphi = make_desc(sb + SM_PHI, 16, 1024, 1);
  P.dv = make_desc(sb + SM_V, SM_Z - SM_V, 512, 2);
  P.dband = make_desc(sb + SM_BAND, 128, 128, 0);
  P.dxs = make_desc(sb + SM_BAND, 16, 128, 0);
  cudaFuncSetAttribute(fused_kernel, cudaFuncAttributeMaxDynamicSharedMemorySize, SM_ALLOC);
  fused_kernel<<<132, 512, SM_ALLOC, cudaStreamPerThread>>>(mx, mw, mwo, mo, mout, mxr, mg, mu, md, P);
}
```

```cpp
#include <cuda_runtime.h>
#include <cuda_bf16.h>
#include <cuda.h>
#include <stdint.h>

namespace {

template<int TA, int TB> __device__ __forceinline__ void wgmma_m64n128k16_ss(float (&d)[64], uint64_t da, uint64_t db, int scale_d) {
  asm volatile("{\n.reg .pred p;\nsetp.ne.b32 p, %66, 0;\n"
    "wgmma.mma_async.sync.aligned.m64n128k16.f32.bf16.bf16 "
    "{%0, %1, %2, %3, %4, %5, %6, %7, %8, %9, %10, %11, %12, %13, %14, %15, "
    "%16, %17, %18, %19, %20, %21, %22, %23, %24, %25, %26, %27, %28, %29, %30, %31, "
    "%32, %33, %34, %35, %36, %37, %38, %39, %40, %41, %42, %43, %44, %45, %46, %47, "
    "%48, %49, %50, %51, %52, %53, %54, %55, %56, %57, %58, %59, %60, %61, %62, %63}, "
    "%64, %65, p, 1, 1, %67, %68;\n}\n"
    : "+f"(d[0]), "+f"(d[1]), "+f"(d[2]), "+f"(d[3]), "+f"(d[4]), "+f"(d[5]), "+f"(d[6]), "+f"(d[7]),
      "+f"(d[8]), "+f"(d[9]), "+f"(d[10]), "+f"(d[11]), "+f"(d[12]), "+f"(d[13]), "+f"(d[14]), "+f"(d[15]),
      "+f"(d[16]), "+f"(d[17]), "+f"(d[18]), "+f"(d[19]), "+f"(d[20]), "+f"(d[21]), "+f"(d[22]), "+f"(d[23]),
      "+f"(d[24]), "+f"(d[25]), "+f"(d[26]), "+f"(d[27]), "+f"(d[28]), "+f"(d[29]), "+f"(d[30]), "+f"(d[31]),
      "+f"(d[32]), "+f"(d[33]), "+f"(d[34]), "+f"(d[35]), "+f"(d[36]), "+f"(d[37]), "+f"(d[38]), "+f"(d[39]),
      "+f"(d[40]), "+f"(d[41]), "+f"(d[42]), "+f"(d[43]), "+f"(d[44]), "+f"(d[45]), "+f"(d[46]), "+f"(d[47]),
      "+f"(d[48]), "+f"(d[49]), "+f"(d[50]), "+f"(d[51]), "+f"(d[52]), "+f"(d[53]), "+f"(d[54]), "+f"(d[55]),
      "+f"(d[56]), "+f"(d[57]), "+f"(d[58]), "+f"(d[59]), "+f"(d[60]), "+f"(d[61]), "+f"(d[62]), "+f"(d[63])
    : "l"(da), "l"(db), "r"(scale_d), "n"(TA), "n"(TB));
}

template<int TB> __device__ __forceinline__ void wgmma_m64n32k16_rs(float (&d)[16], const uint32_t (&a)[4], uint64_t db, int scale_d) {
  asm volatile("{\n.reg .pred p;\nsetp.ne.b32 p, %21, 0;\n"
    "wgmma.mma_async.sync.aligned.m64n32k16.f32.bf16.bf16 "
    "{%0, %1, %2, %3, %4, %5, %6, %7, %8, %9, %10, %11, %12, %13, %14, %15}, "
    "{%16, %17, %18, %19}, %20, p, 1, 1, %22;\n}\n"
    : "+f"(d[0]), "+f"(d[1]), "+f"(d[2]), "+f"(d[3]), "+f"(d[4]), "+f"(d[5]), "+f"(d[6]), "+f"(d[7]),
      "+f"(d[8]), "+f"(d[9]), "+f"(d[10]), "+f"(d[11]), "+f"(d[12]), "+f"(d[13]), "+f"(d[14]), "+f"(d[15])
    : "r"(a[0]), "r"(a[1]), "r"(a[2]), "r"(a[3]), "l"(db), "r"(scale_d), "n"(TB));
}

template<int TA, int TB> __device__ __forceinline__ void wgmma_m64n40k16_ss(float (&d)[20], uint64_t da, uint64_t db, int scale_d) {
  asm volatile("{\n.reg .pred p;\nsetp.ne.b32 p, %22, 0;\n"
    "wgmma.mma_async.sync.aligned.m64n40k16.f32.bf16.bf16 "
    "{%0, %1, %2, %3, %4, %5, %6, %7, %8, %9, %10, %11, %12, %13, %14, %15, "
    "%16, %17, %18, %19}, "
    "%20, %21, p, 1, 1, %23, %24;\n}\n"
    : "+f"(d[0]), "+f"(d[1]), "+f"(d[2]), "+f"(d[3]), "+f"(d[4]), "+f"(d[5]), "+f"(d[6]), "+f"(d[7]),
      "+f"(d[8]), "+f"(d[9]), "+f"(d[10]), "+f"(d[11]), "+f"(d[12]), "+f"(d[13]), "+f"(d[14]), "+f"(d[15]),
      "+f"(d[16]), "+f"(d[17]), "+f"(d[18]), "+f"(d[19])
    : "l"(da), "l"(db), "r"(scale_d), "n"(TA), "n"(TB));
}

template<int TB> __device__ __forceinline__ void wgmma_m64n40k16_rs(float (&d)[20], const uint32_t (&a)[4], uint64_t db, int scale_d) {
  asm volatile("{\n.reg .pred p;\nsetp.ne.b32 p, %25, 0;\n"
    "wgmma.mma_async.sync.aligned.m64n40k16.f32.bf16.bf16 "
    "{%0, %1, %2, %3, %4, %5, %6, %7, %8, %9, %10, %11, %12, %13, %14, %15, "
    "%16, %17, %18, %19}, "
    "{%20, %21, %22, %23}, %24, p, 1, 1, %26;\n}\n"
    : "+f"(d[0]), "+f"(d[1]), "+f"(d[2]), "+f"(d[3]), "+f"(d[4]), "+f"(d[5]), "+f"(d[6]), "+f"(d[7]),
      "+f"(d[8]), "+f"(d[9]), "+f"(d[10]), "+f"(d[11]), "+f"(d[12]), "+f"(d[13]), "+f"(d[14]), "+f"(d[15]),
      "+f"(d[16]), "+f"(d[17]), "+f"(d[18]), "+f"(d[19])
    : "r"(a[0]), "r"(a[1]), "r"(a[2]), "r"(a[3]), "l"(db), "r"(scale_d), "n"(TB));
}

template<int TA, int TB> __device__ __forceinline__ void wgmma_m64n8k16_ss(float (&d)[4], uint64_t da, uint64_t db, int scale_d) {
  asm volatile("{\n.reg .pred p;\nsetp.ne.b32 p, %6, 0;\n"
    "wgmma.mma_async.sync.aligned.m64n8k16.f32.bf16.bf16 "
    "{%0, %1, %2, %3}, "
    "%4, %5, p, 1, 1, %7, %8;\n}\n"
    : "+f"(d[0]), "+f"(d[1]), "+f"(d[2]), "+f"(d[3])
    : "l"(da), "l"(db), "r"(scale_d), "n"(TA), "n"(TB));
}

constexpr int kS = 2048, kD = 1024, kF = 3584;
constexpr int NST = 5, STAGE = 32768;
constexpr uint32_t sb = 1024;
constexpr int SM_V    = NST * STAGE;
constexpr int SM_Z    = SM_V + 16384;
constexpr int SM_PHI  = SM_Z + 4096;
constexpr int SM_MOE  = SM_PHI + 16384;
constexpr int SM_WPHI = SM_MOE + 16384;
constexpr int SM_BAND = SM_WPHI + 8192;
constexpr int SM_G    = SM_BAND + 2176;
constexpr int SM_BAR  = SM_G + 512;
constexpr int SM_MISC = SM_BAR + 384;
constexpr int SM_TOTAL = SM_MISC + 64;
static_assert(SM_TOTAL <= 232448, "smem");
constexpr uint32_t bars = sb + SM_BAR;
constexpr int B_FX = 0  , B_FY = 5  , B_XT = 15, B_EPOCH = 16, B_RX = 17  , B_MF = 21  , B_H1 = 24  , B_KV = 26  ;
constexpr int B_WPHI = 28, B_INFO = 29, B_QS = 30, B_XP = 31, B_RED = 32  , B_PUB = 35  , B_ME = 39  , B_MD = 42;
constexpr int B_EM = 43  , B_NUM = 48;
constexpr int C_START = 0, C_O = 32, C_KV = C_O + 64 * 32;

__device__ uint2 g_gate[kS];
__device__ uint2 g_key[128];
__device__ uint2 g_pre[4 * kF];
__device__ uint2 g_yp[32 * kD];
__device__ __align__(128) uint32_t g_kvp[16 * 16 * 2048];
__device__ __align__(128) uint32_t g_kvr[16 * 3072];
__device__ __align__(128) float g_zp[16 * 16 * 128];
__device__ uint32_t g_cnt[C_KV + 32 * 32];
__device__ __align__(1024) __nv_bfloat16 g_o[kS * kD];
#define KS(id)
#define RG(id)
#define TS(id)
#define TSG(id)
constexpr int SM_ALLOC = SM_TOTAL;

#define POLL0 500
#define POLL1 150
#define POLLF 50
#define RSTEP 2
#define POLLR 500
#define EARLY_N 2
#define EARLY_GAP 100
#define WLEAD 11
#define MLEAD 0
#define MGAP 300

struct Params {
  const __nv_bfloat16 *x, *w, *w_phi, *w_r, *gate_w;
  uint64_t da, db, dw, dphi, dv, dband, dxs;
};

__device__ __forceinline__ uint32_t smem_u32(const void* p) { return (uint32_t)__cvta_generic_to_shared(p); }
__device__ __forceinline__ void mbar_init(uint32_t bar, uint32_t cnt) { asm volatile("mbarrier.init.shared::cta.b64 [%0], %1;" :: "r"(bar), "r"(cnt) : "memory"); }
__device__ __forceinline__ void mbar_expect_tx(uint32_t bar, uint32_t bytes) { asm volatile("mbarrier.arrive.expect_tx.shared::cta.b64 _, [%0], %1;" :: "r"(bar), "r"(bytes) : "memory"); }
__device__ __forceinline__ void mbar_arrive(uint32_t bar) { asm volatile("mbarrier.arrive.shared::cta.b64 _, [%0];" :: "r"(bar) : "memory"); }
__device__ __forceinline__ void mbar_arrive_n(uint32_t bar, uint32_t n) { asm volatile("mbarrier.arrive.shared::cta.b64 _, [%0], %1;" :: "r"(bar), "r"(n) : "memory"); }
constexpr int BUDGET = 1 << 20;
__device__ __forceinline__ void mbar_wait(uint32_t bar, uint32_t parity, int& budget) {
  asm volatile("{\n.reg .pred p;\n"
               "WAIT_L:\nmbarrier.try_wait.parity.shared::cta.b64 p, [%1], %2;\n@p bra WAIT_D;\n"
               "add.s32 %0, %0, -1;\nsetp.gt.s32 p, %0, 0;\n@p bra WAIT_L;\nWAIT_D:\n}"
               : "+r"(budget) : "r"(bar), "r"(parity) : "memory");
}
template <int SLEEP>
__device__ __forceinline__ void wait_count(const uint32_t* p, uint32_t target, int& budget) {
  asm volatile("{\n.reg .pred p;\n.reg .s32 v;\n"
               "WAIT_L:\nld.acquire.gpu.global.s32 v, [%1];\nsub.s32 v, v, %2;\nsetp.ge.s32 p, v, 0;\n@p bra WAIT_D;\n"
               "nanosleep.u32 %3;\nadd.s32 %0, %0, -4;\nsetp.gt.s32 p, %0, 0;\n@p bra WAIT_L;\nWAIT_D:\n}"
               : "+r"(budget) : "l"(p), "r"(target), "n"(SLEEP) : "memory");
}
__device__ __forceinline__ void tma_load(uint32_t dst, const CUtensorMap* m, uint32_t bar, int c0, int c1) {
  asm volatile("cp.async.bulk.tensor.2d.shared::cluster.global.mbarrier::complete_tx::bytes [%0], [%1, {%3, %4}], [%2];"
    :: "r"(dst), "l"(m), "r"(bar), "r"(c0), "r"(c1) : "memory");
}
__device__ __forceinline__ void tma_load3(uint32_t dst, const CUtensorMap* m, uint32_t bar, int c1, int c2) {
  asm volatile("cp.async.bulk.tensor.3d.shared::cluster.global.mbarrier::complete_tx::bytes [%0], [%1, {%5, %3, %4}], [%2];"
    :: "r"(dst), "l"(m), "r"(bar), "r"(c1), "r"(c2), "r"(0) : "memory");
}
__device__ __forceinline__ void tma_prefetch3(const CUtensorMap* m, int c1, int c2) {
  asm volatile("cp.async.bulk.prefetch.tensor.3d.L2.global [%0, {%3, %1, %2}];" :: "l"(m), "r"(c1), "r"(c2), "r"(0) : "memory");
}
__device__ __forceinline__ void tma_prefetch(const CUtensorMap* m, int c0, int c1) {
  asm volatile("cp.async.bulk.prefetch.tensor.2d.L2.global [%0, {%1, %2}];" :: "l"(m), "r"(c0), "r"(c1) : "memory");
}
__device__ __forceinline__ void tma_store(const CUtensorMap* m, uint32_t src, int c0, int c1) {
  asm volatile("cp.async.bulk.tensor.2d.global.shared::cta.bulk_group [%0, {%2, %3}], [%1];" :: "l"(m), "r"(src), "r"(c0), "r"(c1) : "memory");
}
__device__ __forceinline__ void bulk_load(uint32_t dst, const void* src, uint32_t bytes, uint32_t bar) {
  asm volatile("cp.async.bulk.shared::cluster.global.mbarrier::complete_tx::bytes [%0], [%1], %2, [%3];" :: "r"(dst), "l"(src), "r"(bytes), "r"(bar) : "memory");
}
__device__ __forceinline__ void prefetch_map(const CUtensorMap* m) { asm volatile("prefetch.tensormap [%0];" :: "l"(m) : "memory"); }
__device__ __forceinline__ bool elect_one() {
  uint32_t p;
  asm volatile("{\n.reg .pred P;\nelect.sync _|P, 0xffffffff;\nselp.u32 %0, 1, 0, P;\n}" : "=r"(p));
  return p;
}
__device__ __forceinline__ void wg_fence() { asm volatile("wgmma.fence.sync.aligned;" ::: "memory"); }
__device__ __forceinline__ void wg_commit() { asm volatile("wgmma.commit_group.sync.aligned;" ::: "memory"); }
template <int N> __device__ __forceinline__ void wg_wait() { asm volatile("wgmma.wait_group.sync.aligned %0;" :: "n"(N) : "memory"); }
template <int N> __device__ __forceinline__ void zero(float (&r)[N]) {
#pragma unroll
  for (int i = 0; i < N; i++) r[i] = 0.f;
}
template <int N> __device__ __forceinline__ void pin(float (&r)[N]) {
#pragma unroll
  for (int i = 0; i < N; i++) asm volatile("" : "+f"(r[i]) :: "memory");
}
template <int N> __device__ __forceinline__ void pinr(uint32_t (&r)[N][4]) {
#pragma unroll
  for (int i = 0; i < N; i++) asm volatile("" : "+r"(r[i][0]), "+r"(r[i][1]), "+r"(r[i][2]), "+r"(r[i][3]) :: "memory");
}
__device__ __forceinline__ void fence_async_smem() { asm volatile("fence.proxy.async.shared::cta;" ::: "memory"); }
__device__ __forceinline__ void fence_async_global() { asm volatile("fence.proxy.async.global;" ::: "memory"); }
__device__ __forceinline__ void bar_sync(int id, int n) { asm volatile("bar.sync %0, %1;" :: "r"(id), "r"(n) : "memory"); }
__device__ __forceinline__ void bar_arrive(int id, int n) { asm volatile("bar.arrive %0, %1;" :: "r"(id), "r"(n) : "memory"); }
__device__ __forceinline__ void warp_arrive(uint32_t bar, int lane) { __syncwarp(); if (lane == 0) mbar_arrive(bar); }
__host__ __device__ constexpr uint64_t make_desc(uint32_t addr, uint32_t lbo, uint32_t sbo, uint32_t swz) {
  return (uint64_t)((addr & 0x3FFFF) >> 4) | ((uint64_t)((lbo & 0x3FFFF) >> 4) << 16) | ((uint64_t)(sbo >> 4) << 32) | ((uint64_t)swz << 62);
}
__device__ __forceinline__ uint32_t pack2(float lo, float hi) {
  uint32_t r; asm("cvt.rn.bf16x2.f32 %0, %1, %2;" : "=r"(r) : "f"(hi), "f"(lo)); return r;
}
__device__ __forceinline__ float bf_lo(uint32_t v) { return __uint_as_float(v << 16); }
__device__ __forceinline__ float bf_hi(uint32_t v) { return __uint_as_float(v & 0xffff0000u); }
__device__ __forceinline__ float ex2(float x) { float r; asm("ex2.approx.ftz.f32 %0, %1;" : "=f"(r) : "f"(x)); return r; }
__device__ __forceinline__ float rcp(float x) { float r; asm("rcp.approx.ftz.f32 %0, %1;" : "=f"(r) : "f"(x)); return r; }
constexpr float LOG2E = 1.4426950408889634f;
__device__ __forceinline__ float sigmoidf(float x) { return rcp(1.0f + ex2(-LOG2E * x)); }
__device__ __forceinline__ void sts128(uint32_t a, uint32_t x, uint32_t y, uint32_t z, uint32_t w) {
  asm volatile("st.shared.v4.u32 [%0], {%1,%2,%3,%4};" :: "r"(a), "r"(x), "r"(y), "r"(z), "r"(w) : "memory");
}
__device__ __forceinline__ void lds128(uint32_t a, uint32_t (&r)[4]) {
  asm volatile("ld.shared.v4.u32 {%0,%1,%2,%3}, [%4];" : "=r"(r[0]), "=r"(r[1]), "=r"(r[2]), "=r"(r[3]) : "r"(a) : "memory");
}
__device__ __forceinline__ void sts32(uint32_t a, uint32_t v) { asm volatile("st.shared.u32 [%0], %1;" :: "r"(a), "r"(v) : "memory"); }
__device__ __forceinline__ uint32_t lds32(uint32_t a) { uint32_t v; asm volatile("ld.shared.u32 %0, [%1];" : "=r"(v) : "r"(a) : "memory"); return v; }
__device__ __forceinline__ float ldsf(uint32_t a) { return __uint_as_float(lds32(a)); }
__device__ __forceinline__ void stmatrix4(uint32_t a, uint32_t r0, uint32_t r1, uint32_t r2, uint32_t r3) {
  asm volatile("stmatrix.sync.aligned.m8n8.x4.shared.b16 [%0], {%1,%2,%3,%4};" :: "r"(a), "r"(r0), "r"(r1), "r"(r2), "r"(r3) : "memory");
}
__device__ __forceinline__ void ldmatrix4(uint32_t a, uint32_t (&r)[4]) {
  asm volatile("ldmatrix.sync.aligned.m8n8.x4.shared.b16 {%0,%1,%2,%3}, [%4];" : "=r"(r[0]), "=r"(r[1]), "=r"(r[2]), "=r"(r[3]) : "r"(a) : "memory");
}
__device__ __forceinline__ uint4 ldg_nc(const void* p) {
  uint4 v; asm volatile("ld.global.nc.L1::no_allocate.v4.u32 {%0,%1,%2,%3}, [%4];" : "=r"(v.x), "=r"(v.y), "=r"(v.z), "=r"(v.w) : "l"(p)); return v;
}
__device__ __forceinline__ void st_tagged(uint2* p, uint32_t v, uint32_t tag) {
  asm volatile("{\n.reg .b64 x;\nmov.b64 x, {%1, %2};\nst.relaxed.gpu.global.b64 [%0], x;\n}" :: "l"(p), "r"(v), "r"(tag) : "memory");
}
__device__ __forceinline__ uint2 ld_tagged(const uint2* p) {
  uint2 v; asm volatile("{\n.reg .b64 x;\nld.relaxed.gpu.global.b64 x, [%2];\nmov.b64 {%0, %1}, x;\n}" : "=r"(v.x), "=r"(v.y) : "l"(p) : "memory"); return v;
}
__device__ __forceinline__ void probe(const uint2* p, uint32_t tag, int& budget) {
  do { __nanosleep(POLL0); budget -= 16; } while (!__all_sync(0xffffffffu, ld_tagged(p).y == tag) && budget > 0);
}
template <int STRIDE, int N>
__device__ __forceinline__ void gather(const uint2* p, uint32_t tag, float& s0, float& s1, int& budget) {
  uint32_t pause = 0;
  bool again;
#pragma unroll 1
  do {
    __nanosleep(pause);
    pause = POLL0;
    uint32_t bad = 0;
    s0 = s1 = 0.f;
#pragma unroll
    for (int i = 0; i < N; i++) {
      const uint2 w = ld_tagged(p + i * STRIDE);
      bad |= w.y ^ tag;
      if (i < N / 2) s0 += __uint_as_float(w.x); else s1 += __uint_as_float(w.x);
    }
    budget -= 16;
    again = __any_sync(0xffffffffu, bad != 0) && budget > 0;
  } while (again);
}
__device__ __forceinline__ uint32_t ldg_strong(const void* p) { uint32_t v; asm volatile("ld.relaxed.gpu.global.u32 %0, [%1];" : "=r"(v) : "l"(p) : "memory"); return v; }
__device__ __forceinline__ void sts16(uint32_t a, uint32_t v) { asm volatile("st.shared.u16 [%0], %1;" :: "r"(a), "h"((uint16_t)v) : "memory"); }
__device__ __forceinline__ void signal_add(uint32_t* p, uint32_t v) { asm volatile("red.release.gpu.global.add.u32 [%0], %1;" :: "l"(p), "r"(v) : "memory"); }
__device__ __forceinline__ float qmax(float v) { v = fmaxf(v, __shfl_xor_sync(0xffffffffu, v, 1)); return fmaxf(v, __shfl_xor_sync(0xffffffffu, v, 2)); }
__device__ __forceinline__ float qsum(float v) { v += __shfl_xor_sync(0xffffffffu, v, 1); return v + __shfl_xor_sync(0xffffffffu, v, 2); }
__device__ __forceinline__ float fold(float a, float b, bool hi, int m) { return (hi ? b : a) + __shfl_xor_sync(0xffffffffu, hi ? a : b, m); }

__device__ __forceinline__ void yield_slot() { asm volatile("pmevent 0;" ::: "memory"); }
__device__ __forceinline__ float fma_v(float a, float b, float c) { float r; asm volatile("fma.rn.f32 %0, %1, %2, %3;" : "=f"(r) : "f"(a), "f"(b), "f"(c)); return r; }
constexpr float EXP_LIM_F = 36028797018963968.0f;
constexpr uint32_t EXP_TOP = 0x58805880u;
__device__ __forceinline__ void exp_plain(const float (&p)[16], float (&ep)[16], float (&em)[16]) {
#pragma unroll
  for (int i = 0; i < 16; i++) { ep[i] = ex2(p[i]); em[i] = ex2(-p[i]); }
}
__device__ __forceinline__ void exp_shifted(const float (&p)[16], float sgn, float (&e)[16]) {
#pragma unroll
  for (int i = 0; i < 16; i++) e[i] = sgn * p[i];
#pragma unroll
  for (int o = 0; o < 4; o += 2) {
    const float mx = qmax(fmaxf(fmaxf(fmaxf(e[o], e[o + 1]), fmaxf(e[o + 4], e[o + 5])), fmaxf(fmaxf(e[o + 8], e[o + 9]), fmaxf(e[o + 12], e[o + 13]))));
#pragma unroll
    for (int c = 0; c < 4; c++) { e[4 * c + o] = ex2(e[4 * c + o] - mx); e[4 * c + o + 1] = ex2(e[4 * c + o + 1] - mx); }
  }
}
__device__ __forceinline__ void pack_sums(const float (&e)[16], uint32_t (&pk)[2][4], float (&s)[2]) {
#pragma unroll
  for (int i = 0; i < 8; i++) pk[i >> 2][i & 3] = pack2(e[2 * i], e[2 * i + 1]);
#pragma unroll
  for (int o = 0; o < 4; o += 2) s[o >> 1] = ((e[o] + e[o + 1]) + (e[o + 4] + e[o + 5])) + ((e[o + 8] + e[o + 9]) + (e[o + 12] + e[o + 13]));
}
__device__ __forceinline__ uint32_t rcp2(float s) { const float r = rcp(s); return pack2(r, r); }
__device__ __forceinline__ uint32_t mul2(uint32_t a, uint32_t b) { uint32_t r; asm("mul.rn.bf16x2 %0, %1, %2;" : "=r"(r) : "r"(a), "r"(b)); return r; }
__device__ __forceinline__ void store_phi(uint32_t a, const uint32_t (&pk)[2][4], uint32_t r0, uint32_t r1) {
#pragma unroll
  for (int h = 0; h < 2; h++) stmatrix4(a ^ (h * 32), mul2(pk[h][0], r0), mul2(pk[h][1], r1), mul2(pk[h][2], r0), mul2(pk[h][3], r1));
}
__device__ __forceinline__ uint32_t exp_frags(const float (&p)[16], uint32_t (&ef)[4][4], uint32_t top) {
  float ep[16], em[16];
  exp_plain(p, ep, em);
#pragma unroll
  for (int s = 0; s < 2; s++)
#pragma unroll
    for (int r = 0; r < 4; r++) {
      ef[s][r] = pack2(ep[8 * s + 2 * r], ep[8 * s + 2 * r + 1]);
      ef[2 + s][r] = pack2(em[8 * s + 2 * r], em[8 * s + 2 * r + 1]);
    }
#pragma unroll
  for (int s = 0; s < 4; s++) top = __vimax3_u16x2(__vimax3_u16x2(top, ef[s][0], ef[s][1]), ef[s][2], ef[s][3]);
  return top;
}
__device__ __forceinline__ void issue_pq(float (&p)[4][16], const uint32_t (&qf)[4][2][4], uint64_t dw) {
  wg_fence();
#pragma unroll
  for (int h = 0; h < 4; h++) {
    wgmma_m64n32k16_rs<1>(p[h], qf[h][0], dw + h * 128, 0);
    wgmma_m64n32k16_rs<1>(p[h], qf[h][1], dw + h * 128 + 64, 1);
  }
  wg_commit();
}

#define SPLIT_BATCH 2
__device__ __forceinline__ void mainloop128(float (&acc)[2][64], uint64_t da0, uint64_t db0, uint32_t slot, uint32_t ph, int steps, bool lane0, int& budget, int cta, int n0) {
  uint32_t prev = 0;
#pragma unroll 1
  for (int k = 0; k < steps; k++) {
    mbar_wait(bars + B_FX * 8 + slot * 8, ph, budget);
    const uint64_t da = da0 + slot * (STAGE >> 4), db = db0 + slot * (STAGE >> 4);
#pragma unroll
    for (int kk = 0; kk < 4; kk++) {
      if (SPLIT_BATCH == 2 || !(kk & 1)) {
        wg_wait<1>();
        if (kk == 3 - SPLIT_BATCH && k > 0 && lane0) mbar_arrive_n(bars + B_EM * 8 + prev * 8, 2);
        wg_fence();
      }
      wgmma_m64n128k16_ss<0, 1>(acc[0], da + kk * 2, db + kk * 128, kk ? 1 : k);
      wgmma_m64n128k16_ss<0, 1>(acc[1], da + 512 + kk * 2, db + kk * 128, kk ? 1 : k);
      if (SPLIT_BATCH == 2 || (kk & 1)) wg_commit();
    }
    prev = slot;
    if (++slot == NST) { slot = 0; ph ^= 1; }
  }
}
__device__ __forceinline__ void kstep64(float (&acc)[64], uint64_t da, uint64_t db, int accumulate) {
  wg_fence();
#pragma unroll
  for (int kk = 0; kk < 4; kk++) wgmma_m64n128k16_ss<0, 1>(acc, da + kk * 2, db + kk * 128, kk ? 1 : accumulate);
  wg_commit();
}
__device__ __forceinline__ void issue_kv(float (&kv)[20], uint64_t dphi, uint64_t dv, int accumulate) {
  wg_fence();
#pragma unroll
  for (int ks = 0; ks < 4; ks++)
    wgmma_m64n40k16_ss<1, 1>(kv, dphi + ks * 128, dv - (uint64_t)ks * ((64ull << 16) - 64ull), ks ? 1 : accumulate);
  wg_commit();
}
__device__ __forceinline__ void load_slice(int hp, int bi, int tw, uint32_t (&v)[16], uint32_t (&z)[4]) {
#pragma unroll
  for (int i = 0; i < 16; i++) v[i] = ldg_strong(&g_kvp[(hp * 16 + i) * 2048 + bi * 128 + tw]);
  if (tw < 32) {
#pragma unroll
    for (int i = 0; i < 4; i++) z[i] = ldg_strong(&g_zp[(hp * 16 + i * 4 + (tw >> 3)) * 128 + (bi & 3) * 32 + (bi >> 2) * 8 + (tw & 7)]);
  }
}
__device__ __forceinline__ uint32_t moe_buf(uint32_t b) { return b == 2 ? SM_V + 8192 : SM_MOE + b * 8192; }
template <bool DOWN>
__device__ __forceinline__ void moe_chunks(float (&a)[4], int n, uint32_t& buf, uint32_t& ph, uint64_t da0, uint64_t db, bool lane0) {
  int budget = BUDGET;
  zero(a);
#pragma unroll 1
  for (int c = 0; c < n; c++) {
    mbar_wait(bars + B_MF * 8 + buf * 8, ph, budget);
    const uint64_t da = da0 + (moe_buf(buf) >> 4);
    wg_fence();
#pragma unroll
    for (int j = 0; j < 4; j++) wgmma_m64n8k16_ss<1, 0>(a, da + j * 128, DOWN ? db - j : db + j * 2, 1);
    wg_commit();
    wg_wait<0>();
    if (lane0) mbar_arrive(bars + B_ME * 8 + buf * 8);
    db += DOWN ? 16 : 8;
    if (++buf == 3) { buf = 0; ph ^= 1; }
  }
  pin(a);
}
constexpr uint64_t DV_TILE = 4 * ((64ull << 16) - 64ull);

template <bool BY_SM>
__global__ void __launch_bounds__(512, 1)
fused_kernel(const __grid_constant__ CUtensorMap mx, const __grid_constant__ CUtensorMap mw, const __grid_constant__ CUtensorMap mwo,
             const __grid_constant__ CUtensorMap mo, const __grid_constant__ CUtensorMap mout, const __grid_constant__ CUtensorMap mxr,
             const __grid_constant__ CUtensorMap mg, const __grid_constant__ CUtensorMap mu, const __grid_constant__ CUtensorMap md, const Params P) {
  extern __shared__ __align__(1024) uint8_t smem_raw[];
  if (smem_u32(smem_raw) != sb) return;
  const int tid = threadIdx.x, lane = tid & 31;
  if (tid == 256) TS(1);
  const int warp = __shfl_sync(0xffffffffu, tid >> 5, 0), wg = warp >> 2;
  int budget = BUDGET;
  if (warp == 10 && elect_one()) { prefetch_map(&mx); prefetch_map(&mw); }
  int cta;
  {
    uint32_t smid;
    asm volatile("mov.u32 %0, %%smid;" : "=r"(smid));
    if (!BY_SM) cta = blockIdx.x;
    else if (smid < 64) cta = ((smid >> 1) & 7) * 16 + (smid >> 4) * 2 + (smid & 1);
    else if (smid < 120) { const int t = (smid - 64) >> 1, d = (t * 37) >> 8; cta = (1 + t - d * 7) * 16 + 8 + d * 2 + (smid & 1); }
    else cta = smid < 124 ? smid + 8 : smid - 116;
  }
  if (cta >= 128) {
    if (tid == 0) {
      const uint32_t old = atomicAdd(&g_cnt[C_START], 32u);
      wait_count<500>(&g_cnt[C_START], (old & ~255u) + 256u, budget);
    }
    return;
  }
  const int bi = (cta >> 5) * 4 + ((cta >> 2) & 3);
  const int bj = ((cta >> 4) & 1) * 4 + (cta & 3);

  if (wg < 2) {
    if ((warp & 3) < EARLY_N && lane < (wg ? 8 : 16)) {
      const int n = warp & 3;
      const __nv_bfloat16* p = wg ? P.w + (size_t)(n * 64 + bi + (lane >> 1) * 16) * (3 * kD) + 1024 + (lane & 1) * 1024 + bj * 128
                                  : P.x + (size_t)(bi * 128 + bj * 16 + lane) * kD + n * 64;
      if (n) __nanosleep(n * EARLY_GAP);
      asm volatile("prefetch.global.L2 [%0];" :: "l"(p));
    }
    __syncwarp();
    asm volatile("setmaxnreg.inc.sync.aligned.u32 208;");
    const int tw = tid & 127, w = warp & 3, g = lane >> 2, t = lane & 3;
    const bool lane0 = lane == 0;
    if (wg == 0) sts128(sb + SM_Z + (tw & 63) * 16, 0x3f803f80u, 0x3f803f80u, 0x3f803f80u, 0x3f803f80u);
    bar_sync(0, 512);
    if (wg == 1) {
      float sr[4], sg[4];
      zero(sr); zero(sg);
#pragma unroll 1
      for (int c = 0; c < 4; c++) {
        RG(48 + c * 2);
        mbar_wait(bars + (B_RX + c) * 8, 0, budget);
        RG(49 + c * 2);
        uint32_t rs[4], gs[4], xs[4][4];
        lds128(sb + SM_V + c * 512 + lane * 16, rs);
        lds128(sb + SM_V + 2048 + c * 512 + lane * 16, gs);
#pragma unroll
        for (int r = 0; r < 4; r++) lds128(sb + SM_PHI + c * 8192 + (w * 4 + r) * 512 + lane * 16, xs[r]);
#pragma unroll
        for (int e = 0; e < 4; e++) {
          const float r0 = bf_lo(rs[e]), r1 = bf_hi(rs[e]), g0 = bf_lo(gs[e]), g1 = bf_hi(gs[e]);
#pragma unroll
          for (int r = 0; r < 4; r++) {
            const float x0 = bf_lo(xs[r][e]), x1 = bf_hi(xs[r][e]);
            sr[r] = fma_v(x0, r0, sr[r]); sg[r] = fma_v(x0, g0, sg[r]);
            sr[r] = fma_v(x1, r1, sr[r]); sg[r] = fma_v(x1, g1, sg[r]);
            if (r != 1) yield_slot();
          }
        }
      }
      RG(56);
      fence_async_smem();
      __syncwarp();
      if (lane < 3) mbar_arrive(bars + (B_ME + lane) * 8);
      const bool b4 = lane & 16, b3 = lane & 8, b2 = lane & 4;
      const float v = qsum(fold(fold(fold(sr[0], sg[0], b4, 16), fold(sr[2], sg[2], b4, 16), b3, 8),
                                fold(fold(sr[1], sg[1], b4, 16), fold(sr[3], sg[3], b4, 16), b3, 8), b2, 4));
      const int row = bi * 128 + bj * 16 + w * 4 + (g & 3);
      const uint32_t rb = pack2(v + 0.f, 0.f);
      const uint32_t ob = (rb & 0x8000u) ? (~rb & 0xFFFFu) : (rb | 0x8000u);
      const uint32_t best = __reduce_max_sync(0xffffffffu, b4 ? 0u : (ob << 16) | (0xFFFFu - row));
      mbar_wait(bars + B_EPOCH * 8, 0, budget);
      const uint32_t tag = lds32(sb + SM_MISC);
      if (lane0) sts32(sb + SM_MISC + 16 + w * 4, best);
      if (b4 && t == 0) st_tagged(&g_gate[row], __float_as_uint(sigmoidf(v)), tag);
      if (tw == 0) TS(14);
      bar_arrive(6, 256);
      bar_sync(1, 256);
    }

    {
      float acc[2][64];
      if (tw == 0) TS(16 + wg * 16);
      mainloop128(acc, P.da, P.db, wg, wg, 16, lane0, budget, cta, wg * 16);
      bar_sync(1 + wg, 256);
      wg_wait<0>();
      pin(acc[0]); pin(acc[1]);
      if (lane0) mbar_arrive_n(bars + (B_EM + wg) * 8, 2);
      if (tw == 0) TS(17 + wg * 16);
      float p[4][16];
      uint32_t vp[8][4];
      const uint32_t av = sb + SM_V + (w * 16 + g) * 64 + ((t ^ (g >> 1)) << 4);
      {
        uint32_t kf[4][2][4];
#pragma unroll
        for (int u = 0; u < 4; u++)
#pragma unroll
          for (int s = 0; s < 2; s++)
#pragma unroll
            for (int r = 0; r < 4; r++) kf[u][s][r] = pack2(acc[u & 1][16 * (u >> 1) + 8 * s + 2 * r], acc[u & 1][16 * (u >> 1) + 8 * s + 2 * r + 1]);
        mbar_wait(bars + B_WPHI * 8, 0, budget);
        const uint64_t dw = P.dw + wg * 256;
        wg_fence();
#pragma unroll
        for (int u = 0; u < 4; u++) {
          wgmma_m64n32k16_rs<1>(p[u], kf[u][0], dw + (u >> 1) * 128, 0);
          wgmma_m64n32k16_rs<1>(p[u], kf[u][1], dw + (u >> 1) * 128 + 64, 1);
        }
        wg_commit();
#pragma unroll
        for (int u = 0; u < 8; u++) {
          const float* a = &acc[(u >> 1) & 1][32 + 16 * (u >> 2) + 2 * (u & 1)];
          vp[u][0] = pack2(a[0], a[1]); vp[u][1] = pack2(a[4], a[5]); vp[u][2] = pack2(a[8], a[9]); vp[u][3] = pack2(a[12], a[13]);
          if (u < 4) sts128(av + (u >> 1) * 4096 + (u & 1) * 512, vp[u][0], vp[u][1], vp[u][2], vp[u][3]);
        }
        pinr(vp);
        wg_wait<0>();
#pragma unroll
        for (int u = 0; u < 4; u++) pin(p[u]);
      }
      if (tw == 0) TS(18 + wg * 16);
      float kv[2][20];
      uint32_t sv[16], sz[4] = {0, 0, 0, 0};
      {
        const uint32_t sphi = sb + SM_PHI + (w * 16 + (lane & 15)) * 128 + (((lane >> 4) ^ (lane & 7)) << 4);
        float top = 0.f;
        uint32_t pk[4][2][4];
        float ps[2], sa[4], sc[4];
        uint32_t redo = 0;
#pragma unroll
        for (int i = 0; i < 11; i++) {
          if (i >= 3) {
            const int j = i - 3;
            const float s0 = sc[0] + sc[2], s1 = sc[1] + sc[3];
            top = fmaxf(top, fmaxf(s0, s1));
            store_phi((sphi ^ ((j & 1) * 64)) + (j & 2) * 4096, pk[j & 3], rcp2(s0), rcp2(s1));
          }
          if (i >= 2 && i <= 9) {
            sc[0] = sa[0] + sa[2]; sc[1] = sa[1] + sa[3];
            sc[2] = __shfl_xor_sync(0xffffffffu, sc[0], 2); sc[3] = __shfl_xor_sync(0xffffffffu, sc[1], 2);
          }
          if (i >= 1 && i <= 8) {
            sa[0] = ps[0]; sa[1] = ps[1];
            sa[2] = __shfl_xor_sync(0xffffffffu, sa[0], 1); sa[3] = __shfl_xor_sync(0xffffffffu, sa[1], 1);
          }
          if (i < 8) {
            pin(p[i >> 1]);
            float e[16];
#pragma unroll
            for (int c = 0; c < 16; c++) e[c] = ex2((i & 1) ? -p[i >> 1][c] : p[i >> 1][c]);
            pack_sums(e, pk[i & 3], ps);
            pinr(pk[i & 3]); pin(ps);
          }
          if (i < 10) yield_slot();
          if (i >= 2 && i <= 9) pin(sc);
          if (i >= 1 && i <= 8) pin(sa);
          RG(i * 4);
          if (i >= 4 && !(i & 1)) {
            const int u = (i - 4) >> 1;
            fence_async_smem();
            wg_wait<0>();
            RG(i * 4 + 1);
            if (u < 3) bar_sync(7 + wg, 128);
            else asm volatile("{\n.reg .pred p, q;\nsetp.ne.b32 p, %2, 0;\nbar.red.or.pred q, %1, 128, p;\nselp.u32 %0, 1, 0, q;\n}"
                              : "=r"(redo) : "r"(7 + wg), "r"((uint32_t)!(top < EXP_LIM_F)) : "memory");
            RG(i * 4 + 2);
            issue_kv(kv[u >> 1], P.dphi + (u & 1) * 512, P.dv - (u & 1) * DV_TILE, u & 1);
            if (u == 1 || u == 2) {
#pragma unroll
              for (int r = 0; r < 2; r++) sts128(av + ((u + 1) & 1) * 4096 + r * 512, vp[2 * u + 2 + r][0], vp[2 * u + 2 + r][1], vp[2 * u + 2 + r][2], vp[2 * u + 2 + r][3]);
            }
            if (u < 3) yield_slot();
            RG(i * 4 + 3);
          }
        }
        if (tw == 0) TS(19 + wg * 16);
        if (wg) { mbar_wait(bars + B_H1 * 8, 0, budget); load_slice(bj * 2, bi, tw, sv, sz); }
        wg_wait<0>();
        pin(kv[0]); pin(kv[1]);
        if (__builtin_expect(__any_sync(0xffffffffu, redo), 0)) {
#pragma unroll 1
          for (int u = 0; u < 4; u++) {
            bar_sync(7 + wg, 128);
#pragma unroll 1
            for (int sg = 0; sg < 2; sg++) {
              float e[16];
              exp_shifted(p[0], sg ? -1.f : 1.f, e);
              pack_sums(e, pk[0], ps);
              store_phi(sphi ^ (sg * 64), pk[0], rcp2(qsum(ps[0])), rcp2(qsum(ps[1])));
            }
            sts128(av, vp[0][0], vp[0][1], vp[0][2], vp[0][3]);
            sts128(av + 512, vp[1][0], vp[1][1], vp[1][2], vp[1][3]);
            fence_async_smem();
            bar_sync(7 + wg, 128);
            issue_kv(kv[1], P.dphi, P.dv, u & 1);
            wg_wait<0>();
            pin(kv[1]);
#pragma unroll
            for (int c = 0; c < 16; c++) { p[0][c] = p[1][c]; p[1][c] = p[2][c]; p[2][c] = p[3][c]; }
#pragma unroll
            for (int c = 0; c < 24; c++) vp[c >> 2][c & 3] = vp[(c >> 2) + 2][c & 3];
            if (u == 1) {
#pragma unroll
              for (int c = 0; c < 20; c++) kv[0][c] = kv[1][c];
            }
          }
        }
      }
      if (tw == 0) TS(20 + wg * 16);
      {
        const int hp = bj * 2 + wg;
        uint4* dst = reinterpret_cast<uint4*>(&g_kvp[(hp * 16 + bi) * 2048]) + tw;
#pragma unroll
        for (int q = 0; q < 4; q++) {
          const float* a = &kv[q >> 1][8 * (q & 1)];
          dst[q * 128] = make_uint4(pack2(a[0], a[1]), pack2(a[2], a[3]), pack2(a[4], a[5]), pack2(a[6], a[7]));
        }
        g_zp[(hp * 16 + bi) * 128 + w * 32 + (t & 1) * 16 + g * 2 + (t >> 1)] = t == 0 ? kv[0][16] : t == 1 ? kv[0][18] : t == 2 ? kv[1][16] : kv[1][18];
      }
      if (tw == 0) TS(51 + wg * 4);
      if (wg == 0) warp_arrive(bars + B_RED * 8, lane);
      else {
        const int row = (bi & 3) * 16 + (tw >> 4) + (tw & 1) * 8, ch = ((bi >> 2) & 1) * 2 + ((tw >> 1) & 1);
        uint32_t* dst = &g_kvr[bj * 6144 + (bi >> 3) * 1024 + row * 16 + ((ch ^ ((row >> 1) & 3)) << 2) + ((tw >> 2) & 3)];
        const int zr = (bi & 3) * 16 + (bi >> 2) * 4 + ((lane >> 1) & 3);
        uint32_t* dz = &g_kvr[bj * 6144 + 2048 + zr * 16 + ((((lane & 1) + ((lane >> 2) & 2)) ^ ((zr >> 1) & 3)) << 2)];
#pragma unroll 1
        for (int it = 0; it < 2; it++) {
          float lo = 0.f, hi = 0.f;
#pragma unroll
          for (int i = 0; i < 16; i++) { lo += bf_lo(sv[i]); hi += bf_hi(sv[i]); }
          *dst = pack2(lo, hi);
          if (w == 0) {
            float z = (__uint_as_float(sz[0]) + __uint_as_float(sz[1])) + (__uint_as_float(sz[2]) + __uint_as_float(sz[3]));
            z += __shfl_xor_sync(0xffffffffu, z, 8); z += __shfl_xor_sync(0xffffffffu, z, 16);
            const uint32_t z1 = pack2(z, 1.0f);
            if (lane < 16) *reinterpret_cast<uint4*>(dz) = make_uint4(z1, z1, z1, z1);
          }
          warp_arrive(bars + (B_RED + 1 + it) * 8, lane);
          if (tw == 0) TS(21 + it * 16);
          if (it) break;
          mbar_wait(bars + (B_H1 + 1) * 8, 0, budget);
          load_slice(bj * 2 + 1, bi, tw, sv, sz);
          dst += 3072; dz += 3072;
        }
      }
    }

    const uint32_t stash = sb + 3 * STAGE + 8192 + w * 2048 + lane * 16;
    const int rowl = wg * 64 + w * 16 + g;
    mbar_wait(bars + B_INFO * 8, 0, budget);
    const float gA = ldsf(sb + SM_G + rowl * 4), gB = ldsf(sb + SM_G + rowl * 4 + 32);
    {
      float p[4][16];
      uint32_t ef[2][4][4];
      uint32_t top = EXP_TOP;
      if (wg == 0) {
        float acc[2][64];
        bar_sync(2, 256);
        if (tw == 0) TS(22);
        mainloop128(acc, P.da, P.db, 32 % NST, (32 / NST) & 1, 12, lane0, budget, cta, 32);
#pragma unroll 1
        for (int n = 0; n < 4; n++) {
          const uint32_t slot = n ? n - 1 : 4;
          if (tw == 0) KS(128 + 44 + n);
          mbar_wait(bars + B_FX * 8 + slot * 8, n != 0, budget);
          if (tw == 0) KS(44 + n);
          kstep64(acc[0], P.da + slot * (STAGE >> 4), P.db + slot * (STAGE >> 4), 1);
          wg_wait<1>();
          if (n == 0 && lane0) mbar_arrive_n(bars + (B_EM + 43 % NST) * 8, 2);
        }
        kstep64(acc[1], P.da + 512 + (44 % NST) * (STAGE >> 4), P.db + (44 % NST) * (STAGE >> 4), 1);
        wg_wait<1>();
        pin(acc[0]);
        if (tw == 0) TS(15);
        {
          uint32_t qf[4][2][4];
#pragma unroll
          for (int u = 0; u < 8; u++)
#pragma unroll
            for (int r = 0; r < 4; r++) qf[u >> 1][u & 1][r] = pack2(acc[0][8 * u + 2 * r], acc[0][8 * u + 2 * r + 1]);
          issue_pq(p, qf, P.dw);
          kstep64(acc[1], P.da + 512 + (45 % NST) * (STAGE >> 4), P.db + (45 % NST) * (STAGE >> 4), 1);
          wg_wait<1>();
        }
#pragma unroll
        for (int h = 0; h < 4; h++) pin(p[h]);
        if (tw == 0) TS(24);
#pragma unroll
        for (int h = 0; h < 2; h++) {
          if (lane0) mbar_arrive_n(bars + (B_EM + (44 + h) % NST) * 8, 2);
          kstep64(acc[1], P.da + 512 + ((46 + h) % NST) * (STAGE >> 4), P.db + ((46 + h) % NST) * (STAGE >> 4), 1);
          yield_slot();
          pin(p[h]);
          top = exp_frags(p[h], ef[h], top);
          pinr(ef[h]);
          yield_slot();
          if (h == 0) wg_wait<1>(); else wg_wait<0>();
        }
        pin(acc[1]);
        if (lane0) { mbar_arrive_n(bars + (B_EM + 46 % NST) * 8, 2); mbar_arrive_n(bars + (B_EM + 47 % NST) * 8, 2); }
        if (tw == 0) TS(23);
#pragma unroll
        for (int u = 0; u < 8; u++) {
          const float* a = &acc[1][8 * u];
          sts128(stash + (u >> 2) * STAGE + (u & 3) * 512, pack2(a[0], a[1]), pack2(a[2], a[3]), pack2(a[4], a[5]), pack2(a[6], a[7]));
        }
        warp_arrive(bars + B_QS * 8, lane);
      } else {
        uint32_t qf[4][2][4];
        mbar_wait(bars + B_QS * 8, 0, budget);
#pragma unroll
        for (int u = 0; u < 8; u++) lds128(stash + (u >> 2) * STAGE + (u & 3) * 512, qf[u >> 1][u & 1]);
        __syncwarp();
        issue_pq(p, qf, P.dw);
        wg_wait<0>();
#pragma unroll
        for (int h = 0; h < 4; h++) pin(p[h]);
        if (tw == 0) TS(40);
      }

      __nv_bfloat16* og = g_o + (size_t)(bi * 128 + rowl) * kD + bj * 128 + t * 8;
      uint32_t own = sb + 3 * STAGE + rowl * 128 + ((t ^ g) << 4);
#pragma unroll 1
      for (int pr = 0; pr < 2; pr++) {
        if (pr | wg) top = exp_frags(p[1], ef[1], exp_frags(p[0], ef[0], EXP_TOP));
        if (__builtin_expect(__any_sync(0xffffffffu, top != EXP_TOP), 0)) {
#pragma unroll 1
          for (int u = 0; u < 4; u++) {
            float e[16];
            exp_shifted(p[0], (u & 1) ? -1.f : 1.f, e);
#pragma unroll
            for (int r = 0; r < 4; r++) {
#pragma unroll
              for (int s = 0; s < 6; s++) ef[s >> 2][s & 3][r] = ef[(s + 2) >> 2][(s + 2) & 3][r];
              ef[1][2][r] = pack2(e[2 * r], e[2 * r + 1]);
              ef[1][3][r] = pack2(e[8 + 2 * r], e[8 + 2 * r + 1]);
            }
            if (u & 1) {
#pragma unroll
              for (int e2 = 0; e2 < 16; e2++) p[0][e2] = p[1][e2];
            }
          }
        }
        float np[2][20], nm[2][20];
        mbar_wait(bars + (B_KV + pr) * 8, 0, budget);
        wg_fence();
#pragma unroll
        for (int hh = 0; hh < 2; hh++) {
          const uint64_t dk = P.dv - (uint64_t)pr * ((256ull << 16) - 512ull) - hh * ((255ull << 16) - 256ull);
          wgmma_m64n40k16_rs<1>(np[hh], ef[hh][0], dk, 0);
          wgmma_m64n40k16_rs<1>(np[hh], ef[hh][1], dk + 64, 1);
          wgmma_m64n40k16_rs<1>(nm[hh], ef[hh][2], dk + 128, 0);
          wgmma_m64n40k16_rs<1>(nm[hh], ef[hh][3], dk + 192, 1);
          wg_commit();
        }
#pragma unroll
        for (int e = 0; e < 16; e++) { p[0][e] = p[2][e]; p[1][e] = p[3][e]; }
        pin(p[0]); pin(p[1]);
#pragma unroll
        for (int hh = 0; hh < 2; hh++) {
          if (hh == 0) wg_wait<1>(); else wg_wait<0>();
          pin(np[hh]); pin(nm[hh]);
          uint32_t o[2][4];
#pragma unroll
          for (int r = 0; r < 2; r++) {
            const float dp = np[hh][16 + 2 * r], sp = np[hh][17 + 2 * r], dm = nm[hh][16 + 2 * r], sm = nm[hh][17 + 2 * r];
            const float inv = (r == 0 ? gA : gB) * rcp(fmaf(dp, sm, fmaf(1e-6f, sm, dm) * sp));
            const float cp = sm * inv, cm = sp * inv;
#pragma unroll
            for (int c = 0; c < 4; c++)
              o[r][c] = pack2(fmaf(np[hh][4 * c + 2 * r], cp, nm[hh][4 * c + 2 * r] * cm), fmaf(np[hh][4 * c + 2 * r + 1], cp, nm[hh][4 * c + 2 * r + 1] * cm));
            sts128((own ^ (hh * 64)) + r * 1024, o[r][0], o[r][1], o[r][2], o[r][3]);
          }
          if (hh == 1 && pr == 1) fence_async_smem();
#pragma unroll
          for (int r = 0; r < 2; r++) *reinterpret_cast<uint4*>(og + r * 8 * kD + hh * 32) = make_uint4(o[r][0], o[r][1], o[r][2], o[r][3]);
        }
        warp_arrive(bars + (B_PUB + wg * 2 + pr) * 8, lane);
        if (tw == 0) TS(25 + pr + wg * 16);
        og += 64; own += STAGE;
      }
    }
    bar_sync(7 + wg, 128);

    float oacc[64];
    {
      const uint64_t dam = P.da + wg * 512;
      uint32_t slot = 3, ph = 1, prev = 0;
#pragma unroll 1
      for (int s = 0; s < 16; s++) {
        if (tid == 0) KS(128 + 48 + s);
        mbar_wait(bars + B_FX * 8 + slot * 8, ph, budget);
        if (s >= 2) mbar_wait(bars + (B_FY + wg * NST) * 8 + slot * 8, ph, budget);
        if (tid == 0) KS(48 + s);
        if (tid == 128) KS(192 + 48 + s);
        kstep64(oacc, dam + slot * (STAGE >> 4), P.db + slot * (STAGE >> 4), s);
        wg_wait<1>();
        if (s != 0 && s != 2 && lane0) mbar_arrive(bars + B_EM * 8 + prev * 8);
        if (s == 1) {
          wg_wait<0>();
          if (lane0) mbar_arrive(bars + B_EM * 8 + slot * 8);
        }
        prev = slot;
        if (++slot == NST) { slot = 0; ph ^= 1; }
      }
    }
    mbar_wait(bars + B_XT * 8, 0, budget);
    if ((lds32(sb + SM_MISC + 4) >> 7) == (uint32_t)bi) mbar_wait(bars + B_XP * 8, 0, budget);
    const uint32_t sx = sb + SM_PHI + (wg * 64 + w * 16 + (lane & 15)) * 128 + (((lane >> 4) ^ (lane & 7)) << 4);
    float xf[64];
#pragma unroll
    for (int u = 0; u < 8; u++) {
      uint32_t xr[4];
      ldmatrix4((sx ^ ((u & 3) * 32)) + (u >> 2) * 16384, xr);
#pragma unroll
      for (int r = 0; r < 4; r++) { xf[8 * u + 2 * r] = bf_lo(xr[r]); xf[8 * u + 2 * r + 1] = bf_hi(xr[r]); }
    }
    pin(xf);
    const float hA = 1.0f - gA, hB = 1.0f - gB;
    wg_wait<0>();
    pin(oacc);
    if (tw == 0) TS(29 + wg * 16);
#pragma unroll
    for (int hf = 0; hf < 2; hf++) {
#pragma unroll
      for (int u = hf * 4; u < hf * 4 + 4; u++) {
        const float* a = &oacc[8 * u];
        const float* b = &xf[8 * u];
        stmatrix4((sx ^ ((u & 3) * 32)) + hf * 16384,
                  pack2(fmaf(hA, b[0], a[0]), fmaf(hA, b[1], a[1])), pack2(fmaf(hB, b[2], a[2]), fmaf(hB, b[3], a[3])),
                  pack2(fmaf(hA, b[4], a[4]), fmaf(hA, b[5], a[5])), pack2(fmaf(hB, b[6], a[6]), fmaf(hB, b[7], a[7])));
      }
      fence_async_smem();
      __syncwarp();
      if (elect_one()) tma_store(&mout, sb + SM_PHI + hf * 16384 + warp * 2048, bj * 128 + hf * 64, bi * 128 + warp * 16);
    }
    if (elect_one()) {
      asm volatile("cp.async.bulk.commit_group;" ::: "memory");
      asm volatile("cp.async.bulk.wait_group.read 0;" ::: "memory");
    }
  } else if (wg == 3) {
    asm volatile("setmaxnreg.dec.sync.aligned.u32 64;");
    const int t3 = tid - 384, w3 = warp - 12;
    if (t3 == 0) TSG(0);
    bar_sync(0, 512);
#pragma unroll 1
    for (int u = 0; u < 4; u++) {
      const uint4 v = ldg_nc(P.w_phi + bj * 4096 + (u * 128 + t3) * 8);
      sts128(sb + SM_WPHI + u * 2048 + (t3 >> 2) * 64 + (((t3 & 3) ^ ((t3 >> 3) & 3)) << 4),
             pack2(LOG2E * bf_lo(v.x), LOG2E * bf_hi(v.x)), pack2(LOG2E * bf_lo(v.y), LOG2E * bf_hi(v.y)),
             pack2(LOG2E * bf_lo(v.z), LOG2E * bf_hi(v.z)), pack2(LOG2E * bf_lo(v.w), LOG2E * bf_hi(v.w)));
    }
    fence_async_smem();
    warp_arrive(bars + B_WPHI * 8, lane);
    bar_sync(6, 256);
    const uint32_t target = lds32(sb + SM_MISC);
    uint32_t key;
    {
      uint32_t kk[4];
      lds128(sb + SM_MISC + 16, kk);
      if (t3 == 0) st_tagged(&g_key[cta], max(max(kk[0], kk[1]), max(kk[2], kk[3])), target);
      uint2 k, gv;
      __nanosleep(POLLR);
      do {
        __nanosleep(POLL1);
        k = ld_tagged(&g_key[t3]);
        gv = ld_tagged(&g_gate[bi * 128 + t3]);
        budget -= 4;
      } while (!__all_sync(0xffffffffu, k.y == target && gv.y == target) && budget > 0);
      key = __reduce_max_sync(0xffffffffu, k.x);
      if (lane == 0) sts32(sb + SM_MISC + 32 + w3 * 4, key);
      sts32(sb + SM_G + t3 * 4, gv.x);
      bar_sync(5, 128);
      lds128(sb + SM_MISC + 32, kk);
      key = max(max(kk[0], kk[1]), max(kk[2], kk[3]));
    }
    const int idx = (0xFFFF - (key & 0xFFFF)) & (kS - 1);
    if (t3 == 0) { sts32(sb + SM_MISC + 4, idx); TS(8); }
    warp_arrive(bars + B_INFO * 8, lane);
    {
      const uint4 v = ldg_nc(P.x + (size_t)idx * kD + t3 * 8);
      sts128(sb + SM_BAND + t3 * 16, v.x, v.y, v.z, v.w);
    }
    const int t2 = (lane & 3) * 2, row = w3 * 16 + (lane >> 2);
    float a[4];
    uint32_t buf = 0, ph = 0;
    fence_async_smem();
    bar_sync(5, 128);
    {
      const int r = cta >> 4;
#pragma unroll 1
      for (int part = 0; part < 2; part++) {
        const int n = part ? 14 - 2 * r : 2 * r;
        moe_chunks<false>(a, n, buf, ph, P.da, P.dxs + (part ? 0 : (16 - n) * 8), lane == 0);
        uint2* dst = &g_pre[(((cta >> 2) & 2) + 1 - part) * kF + ((r - 1 + part) * 8 + (cta & 7)) * 64 + row];
        if (t2 == 0 && n) { st_tagged(dst, __float_as_uint(a[0]), target); st_tagged(dst + 8, __float_as_uint(a[2]), target); }
      }
    }
    if (t3 == 0) TS(9);
    bar_sync(5, 128);
    sts128(sb + SM_BAND + t3 * 16, 0, 0, 0, 0);
    {
      float gs, us;
      __nanosleep(POLL0);
      gather<kF, 4>(&g_pre[(cta >> 2) * 112 + min(t3, 111)], target, gs, us, budget);
      bar_sync(5, 128);
      if (t3 < 112) sts16(sb + SM_BAND + 112 + (t3 >> 3) * 128 + (t3 & 7) * 2, pack2(gs * sigmoidf(gs) * us, 0.f));
    }
    fence_async_smem();
    bar_sync(5, 128);
    if (t3 == 0) TS(12);
    moe_chunks<true>(a, 7, buf, ph, P.da, P.dband + 7, lane == 0);
    if (t3 == 0) TS(10);
    if (t2 < 4) {
      uint2* dst = &g_yp[(cta >> 2) * kD + (cta & 3) * 256 + t2 * 64 + row];
      st_tagged(dst, __float_as_uint(a[0]), target); st_tagged(dst + 8, __float_as_uint(a[2]), target);
      st_tagged(dst + 64, __float_as_uint(a[1]), target); st_tagged(dst + 72, __float_as_uint(a[3]), target);
    }
    if (lane == 0) mbar_arrive(bars + B_MD * 8);
    if ((idx >> 7) == bi) {
      mbar_wait(bars + (B_PUB + 3) * 8, 0, budget);
      if (w3 == 0) probe(&g_yp[lane * kD + bj * 128], target, budget);
      bar_sync(5, 128);
      float y = 0.f;
#pragma unroll 1
      for (int hf = 0; hf < 2; hf++) {
        float y0, y1;
        gather<kD, 16>(&g_yp[hf * 16 * kD + bj * 128 + t3], target, y0, y1, budget);
        y += y0 + y1;
      }
      const uint32_t ob = key >> 16;
      const float upd = y * sigmoidf(__uint_as_float(((ob & 0x8000u) ? (ob ^ 0x8000u) : (~ob & 0xFFFFu)) << 16));
      const uint32_t a = sb + SM_PHI + (t3 >> 6) * 16384 + (idx & 127) * 128 + ((((t3 >> 3) & 7) ^ (idx & 7)) << 4) + (t3 & 7) * 2;
      mbar_wait(bars + B_XT * 8, 0, budget);
      uint16_t xb;
      asm volatile("ld.shared.u16 %0, [%1];" : "=h"(xb) : "r"(a) : "memory");
      sts16(a, pack2(bf_lo(xb) + upd, 0.f));
      warp_arrive(bars + B_XP * 8, lane);
      if (t3 == 0) TS(11);
    }
  } else {
    asm volatile("setmaxnreg.dec.sync.aligned.u32 32;");
    if (warp == 8) {
      if (elect_one()) {
        TS(7);
#pragma unroll
        for (int s = 0; s < NST; s++) mbar_init(bars + (B_FX + s) * 8, 1);
        asm volatile("fence.mbarrier_init.release.cluster;" ::: "memory");
        fence_async_smem();
      }
      __syncwarp();
      bar_arrive(0, 512);
      if (elect_one()) {
#pragma unroll 1
        for (int n = 0; n < NST; n++) {
          const uint32_t st = sb + n * STAGE, fb = bars + (B_FX + n) * 8;
          KS(64 + n);
          mbar_expect_tx(fb, STAGE);
          tma_load(st, &mx, fb, n * 64, bi * 128);
          tma_load(st + 16384, &mw, fb, 1024 + bj * 128, n * 64);
          tma_load(st + 24576, &mw, fb, 2048 + bj * 128, n * 64);
        }
      }
      __syncwarp();
      bar_sync(10, 64);
    } else {
      if (warp == 9) {
        if (elect_one()) {
#pragma unroll
          for (int s = B_FY; s < B_NUM; s++) mbar_init(bars + s * 8, s < B_WPHI ? 1 : s < B_EM ? 4 : 8);
          asm volatile("fence.mbarrier_init.release.cluster;" ::: "memory");
          fence_async_smem();
        }
        __syncwarp();
        bar_arrive(10, 64);
      }
      bar_sync(0, 512);
    }
    if (!elect_one()) return;
    if (warp == 8) {
      uint32_t slot = 0, ph = 0;
#pragma unroll 1
      for (int n = NST; n < 48; n++) {
        const int t = n >> 4, k = n & 15;
        const int c0 = t == 2 ? bj * 128 : 1024 + bj * 128 + t * 64, c1 = t == 2 ? c0 + 64 : c0 + 1024;
        const uint32_t st = sb + slot * STAGE, fb = bars + (B_FX + slot) * 8;
        if (n <= NST + 3 * RSTEP && (n - NST) % RSTEP == 0) {
          const int c = (n - NST) / RSTEP;
          mbar_expect_tx(bars + (B_RX + c) * 8, c == 0 ? 8192 + 4096 : 8192);
          tma_load(sb + SM_PHI + c * 8192, &mxr, bars + (B_RX + c) * 8, c * 256, bi * 128 + bj * 16);
          if (c == 0) { bulk_load(sb + SM_V, P.w_r, 2048, bars + B_RX * 8); bulk_load(sb + SM_V + 2048, P.gate_w, 2048, bars + B_RX * 8); }
        }
        mbar_wait(bars + (B_EM + slot) * 8, ph, budget);
        KS(64 + n);
        mbar_expect_tx(fb, STAGE);
        tma_load(st, &mx, fb, k * 64, bi * 128);
        tma_load(st + 16384, &mw, fb, c0, k * 64);
        tma_load(st + 24576, &mw, fb, c1, k * 64);
        {
          const int m = n + WLEAD, tm = m >> 4;
          if ((m & 3) == (bi & 3)) {
            const int d0 = tm >= 2 ? bj * 128 : 1024 + bj * 128 + tm * 64, d1 = tm >= 2 ? d0 + 64 : d0 + 1024;
            tma_prefetch(tm == 3 ? &mwo : &mw, d0, (m & 15) * 64); tma_prefetch(tm == 3 ? &mwo : &mw, d1, (m & 15) * 64);
          }
        }
        if (++slot == NST) { slot = 0; ph ^= 1; }
      }
#pragma unroll 1
      for (int m = WLEAD + ((bi - WLEAD) & 3); m < 16; m += 4) { tma_prefetch(&mwo, bj * 128, m * 64); tma_prefetch(&mwo, bj * 128 + 64, m * 64); }
#pragma unroll 1
      for (int s = 0; s < 16; s++) {
        const int p = s < 2 ? s : (s >= 9), q = s < 9 ? s - 2 : s - 9;
        const int k0 = (s < 2 ? bj : q + (q >= bj)) * 128 + p * 64;
        const uint32_t st = sb + slot * STAGE, fb = bars + (B_FX + slot) * 8;
        mbar_wait(bars + (B_EM + slot) * 8, ph, budget);
        KS(64 + 48 + s);
        mbar_expect_tx(fb, 16384);
        tma_load(st + 16384, &mwo, fb, bj * 128, k0);
        tma_load(st + 24576, &mwo, fb, bj * 128 + 64, k0);
        if (++slot == NST) { slot = 0; ph ^= 1; }
      }
      mbar_wait(bars + B_MD * 8, 0, budget);
      mbar_expect_tx(bars + B_XT * 8, 32768);
      tma_load(sb + SM_PHI, &mx, bars + B_XT * 8, bj * 128, bi * 128);
      tma_load(sb + SM_PHI + 16384, &mx, bars + B_XT * 8, bj * 128 + 64, bi * 128);
    } else if (warp == 9) {
      prefetch_map(&mo); prefetch_map(&mout);
      sts32(sb + SM_MISC, (atomicAdd(&g_cnt[C_START], 1u) & ~255u) + 256u);
      mbar_arrive(bars + B_EPOCH * 8);
      const CUtensorMap* m = (cta & 8) ? &mu : &mg;
      const int l0 = (cta >> 4) * 14, a0 = (cta & 7) * 64, d1 = (cta >> 2) * 112 - 14 * 16, d2 = (cta & 3) * 4;
      uint32_t buf = 0, ph = 0;
#pragma unroll 1
      for (int c = 0; c < 21; c++) {
        const uint32_t dst = sb + moe_buf(buf), fb = bars + (B_MF + buf) * 8;
        mbar_wait(bars + (B_ME + buf) * 8, ph, budget);
        mbar_expect_tx(fb, 8192);
        if (c < 14) tma_load(dst, m, fb, a0 + ((l0 + c) >> 4) * 512, ((l0 + c) & 15) * 64); else tma_load3(dst, &md, fb, d1 + c * 16, d2);
        if (MLEAD && c >= 2) {
          const int f = c + MLEAD;
          if (f < 14) tma_prefetch(m, a0 + ((l0 + f) >> 4) * 512, ((l0 + f) & 15) * 64); else if (f < 21) tma_prefetch3(&md, d1 + f * 16, d2);
        }
        if (c < 2) __nanosleep(MGAP);
        if (++buf == 3) { buf = 0; ph ^= 1; }
      }
#pragma unroll 1
      for (int u = 0; u < 2; u++) {
        mbar_wait(bars + (B_PUB + u * 2 + 1) * 8, 0, budget);
        signal_add(&g_cnt[C_O + (bi * 4 + u * 2 + 1) * 32], 32u);
        TS(57 + u * 2);
      }
    } else {
      const int u = warp - 10, hp = bj * 2 + u;
      mbar_wait(bars + B_EPOCH * 8, 0, budget);
      const uint32_t target = lds32(sb + SM_MISC);
#pragma unroll 1
      for (int ev = u * 2; ev < 4; ev += (ev == 1) + 1) {
        uint32_t* cnt = &g_cnt[ev < 3 ? C_KV + (bj * 4 + ev) * 32 : C_O + (bi * 4 + u * 2) * 32];
        mbar_wait(bars + (ev < 3 ? B_RED + ev : B_PUB + u * 2) * 8, 0, budget);
        signal_add(cnt, ev < 3 ? 16u : 32u);
        TS(ev < 3 ? 60 + ev : 56 + u * 2);
        wait_count<POLLF>(cnt, target, budget);
        fence_async_global();
        if (ev < 2) mbar_arrive(bars + (B_H1 + ev) * 8);
        if (ev == u + 1) {
          if (u) mbar_wait(bars + B_MD * 8, 0, budget);
          mbar_expect_tx(bars + (B_KV + u) * 8, 12288);
          bulk_load(sb + SM_V + u * 8192, &g_kvr[hp * 3072], 8192, bars + (B_KV + u) * 8);
          bulk_load(sb + SM_Z + u * 4096, &g_kvr[hp * 3072 + 2048], 4096, bars + (B_KV + u) * 8);
          TS(38 + u);
        }
      }
      TS(2 + u * 2);
      if (u == 0) mbar_wait(bars + B_QS * 8, 0, budget);
      uint32_t slot = 0, ph = 1;
#pragma unroll 1
      for (int s = 2; s < 16; s++) {
        const int p = s >= 9, q = s < 9 ? s - 2 : s - 9;
        if (s == 9) { wait_count<POLLF>(&g_cnt[C_O + (bi * 4 + u * 2 + 1) * 32], target, budget); fence_async_global(); TS(3 + u * 2); }
        const uint32_t fb = bars + (B_FY + u * NST + slot) * 8;
        mbar_wait(bars + (B_EM + slot) * 8, ph, budget);
        mbar_expect_tx(fb, 8192);
        tma_load(sb + slot * STAGE + u * 8192, &mo, fb, (q + (q >= bj)) * 128 + p * 64, bi * 128 + u * 64);
        if (++slot == NST) { slot = 0; ph ^= 1; }
      }
    }
  }
}

typedef CUresult (*EncodeFn)(CUtensorMap*, CUtensorMapDataType, cuuint32_t, void*, const cuuint64_t*, const cuuint64_t*, const cuuint32_t*,
                             const cuuint32_t*, CUtensorMapInterleave, CUtensorMapSwizzle, CUtensorMapL2promotion, CUtensorMapFloatOOBfill);

void make_map(EncodeFn enc, CUtensorMap* m, const void* ptr, uint64_t cols, uint64_t rows, uint32_t bc, uint32_t br, CUtensorMapSwizzle swz) {
  const cuuint64_t dims[2] = {cols, rows}, strides[1] = {cols * 2};
  const cuuint32_t box[2] = {bc, br}, es[2] = {1, 1};
  enc(m, CU_TENSOR_MAP_DATA_TYPE_BFLOAT16, 2, const_cast<void*>(ptr), dims, strides, box, es, CU_TENSOR_MAP_INTERLEAVE_NONE, swz,
      CU_TENSOR_MAP_L2_PROMOTION_L2_128B, CU_TENSOR_MAP_FLOAT_OOB_FILL_NONE);
}

}

extern "C" void kernel_launch(void* const* d_in, const int* in_sizes, int n_in, void* d_out, int out_size) {
  (void)in_sizes; (void)n_in; (void)out_size;
  void* fn = nullptr;
  cudaDriverEntryPointQueryResult qr;
  cudaGetDriverEntryPoint("cuTensorMapEncodeTiled", &fn, cudaEnableDefault, &qr);
  EncodeFn enc = (EncodeFn)fn;
  void* o_ptr = nullptr;
  cudaGetSymbolAddress(&o_ptr, g_o);
  CUtensorMap mx, mw, mwo, mo, mout, mxr, mg, mu, md;
  make_map(enc, &mx, d_in[0], kD, kS, 64, 128, CU_TENSOR_MAP_SWIZZLE_128B);
  make_map(enc, &mxr, d_in[0], kD, kS, 256, 16, CU_TENSOR_MAP_SWIZZLE_NONE);
  make_map(enc, &mw, d_in[1], 3 * kD, kD, 64, 64, CU_TENSOR_MAP_SWIZZLE_128B);
  make_map(enc, &mwo, d_in[3], kD, kD, 64, 64, CU_TENSOR_MAP_SWIZZLE_128B);
  make_map(enc, &mo, o_ptr, kD, kS, 64, 64, CU_TENSOR_MAP_SWIZZLE_128B);
  make_map(enc, &mout, d_out, kD, kS, 64, 16, CU_TENSOR_MAP_SWIZZLE_128B);
  make_map(enc, &mg, d_in[6], kF, kD, 64, 64, CU_TENSOR_MAP_SWIZZLE_128B);
  make_map(enc, &mu, d_in[7], kF, kD, 64, 64, CU_TENSOR_MAP_SWIZZLE_128B);
  {
    const cuuint64_t dims[3] = {64, kF, 16}, strides[2] = {kD * 2, 128};
    const cuuint32_t box[3] = {64, 16, 4}, es[3] = {1, 1, 1};
    enc(&md, CU_TENSOR_MAP_DATA_TYPE_BFLOAT16, 3, d_in[8], dims, strides, box, es, CU_TENSOR_MAP_INTERLEAVE_NONE, CU_TENSOR_MAP_SWIZZLE_128B,
        CU_TENSOR_MAP_L2_PROMOTION_L2_128B, CU_TENSOR_MAP_FLOAT_OOB_FILL_NONE);
  }
  Params P;
  P.x = (const __nv_bfloat16*)d_in[0];
  P.w = (const __nv_bfloat16*)d_in[1];
  P.w_phi = (const __nv_bfloat16*)d_in[2];
  P.w_r = (const __nv_bfloat16*)d_in[5];
  P.gate_w = (const __nv_bfloat16*)d_in[9];
  P.da = make_desc(sb, 16, 1024, 1);
  P.db = make_desc(sb + 16384, 8192, 1024, 1);
  P.dw = make_desc(sb + SM_WPHI, 16, 512, 2);
  P.dphi = make_desc(sb + SM_PHI, 16, 1024, 1);
  P.dv = make_desc(sb + SM_V, SM_Z - SM_V, 512, 2);
  P.dband = make_desc(sb + SM_BAND, 128, 128, 0);
  P.dxs = make_desc(sb + SM_BAND, 16, 128, 0);
  int dev = 0, sms = 0;
  cudaGetDevice(&dev);
  cudaDeviceGetAttribute(&sms, cudaDevAttrMultiProcessorCount, dev);
  auto kern = sms == 132 ? fused_kernel<true> : fused_kernel<false>;
  cudaFuncSetAttribute(kern, cudaFuncAttributeMaxDynamicSharedMemorySize, SM_ALLOC);
  kern<<<132, 512, SM_ALLOC, cudaStreamPerThread>>>(mx, mw, mwo, mo, mout, mxr, mg, mu, md, P);
}
```

```cpp
#include <cuda_runtime.h>
#include <cuda_bf16.h>
#include <cuda.h>
#include <stdint.h>

namespace {

template<int TA, int TB> __device__ __forceinline__ void wgmma_m64n128k16_ss(float (&d)[64], uint64_t da, uint64_t db, int scale_d) {
  asm volatile("{\n.reg .pred p;\nsetp.ne.b32 p, %66, 0;\n"
    "wgmma.mma_async.sync.aligned.m64n128k16.f32.bf16.bf16 "
    "{%0, %1, %2, %3, %4, %5, %6, %7, %8, %9, %10, %11, %12, %13, %14, %15, "
    "%16, %17, %18, %19, %20, %21, %22, %23, %24, %25, %26, %27, %28, %29, %30, %31, "
    "%32, %33, %34, %35, %36, %37, %38, %39, %40, %41, %42, %43, %44, %45, %46, %47, "
    "%48, %49, %50, %51, %52, %53, %54, %55, %56, %57, %58, %59, %60, %61, %62, %63}, "
    "%64, %65, p, 1, 1, %67, %68;\n}\n"
    : "+f"(d[0]), "+f"(d[1]), "+f"(d[2]), "+f"(d[3]), "+f"(d[4]), "+f"(d[5]), "+f"(d[6]), "+f"(d[7]),
      "+f"(d[8]), "+f"(d[9]), "+f"(d[10]), "+f"(d[11]), "+f"(d[12]), "+f"(d[13]), "+f"(d[14]), "+f"(d[15]),
      "+f"(d[16]), "+f"(d[17]), "+f"(d[18]), "+f"(d[19]), "+f"(d[20]), "+f"(d[21]), "+f"(d[22]), "+f"(d[23]),
      "+f"(d[24]), "+f"(d[25]), "+f"(d[26]), "+f"(d[27]), "+f"(d[28]), "+f"(d[29]), "+f"(d[30]), "+f"(d[31]),
      "+f"(d[32]), "+f"(d[33]), "+f"(d[34]), "+f"(d[35]), "+f"(d[36]), "+f"(d[37]), "+f"(d[38]), "+f"(d[39]),
      "+f"(d[40]), "+f"(d[41]), "+f"(d[42]), "+f"(d[43]), "+f"(d[44]), "+f"(d[45]), "+f"(d[46]), "+f"(d[47]),
      "+f"(d[48]), "+f"(d[49]), "+f"(d[50]), "+f"(d[51]), "+f"(d[52]), "+f"(d[53]), "+f"(d[54]), "+f"(d[55]),
      "+f"(d[56]), "+f"(d[57]), "+f"(d[58]), "+f"(d[59]), "+f"(d[60]), "+f"(d[61]), "+f"(d[62]), "+f"(d[63])
    : "l"(da), "l"(db), "r"(scale_d), "n"(TA), "n"(TB));
}

template<int TB> __device__ __forceinline__ void wgmma_m64n32k16_rs(float (&d)[16], const uint32_t (&a)[4], uint64_t db, int scale_d) {
  asm volatile("{\n.reg .pred p;\nsetp.ne.b32 p, %21, 0;\n"
    "wgmma.mma_async.sync.aligned.m64n32k16.f32.bf16.bf16 "
    "{%0, %1, %2, %3, %4, %5, %6, %7, %8, %9, %10, %11, %12, %13, %14, %15}, "
    "{%16, %17, %18, %19}, %20, p, 1, 1, %22;\n}\n"
    : "+f"(d[0]), "+f"(d[1]), "+f"(d[2]), "+f"(d[3]), "+f"(d[4]), "+f"(d[5]), "+f"(d[6]), "+f"(d[7]),
      "+f"(d[8]), "+f"(d[9]), "+f"(d[10]), "+f"(d[11]), "+f"(d[12]), "+f"(d[13]), "+f"(d[14]), "+f"(d[15])
    : "r"(a[0]), "r"(a[1]), "r"(a[2]), "r"(a[3]), "l"(db), "r"(scale_d), "n"(TB));
}

template<int TA, int TB> __device__ __forceinline__ void wgmma_m64n40k16_ss(float (&d)[20], uint64_t da, uint64_t db, int scale_d) {
  asm volatile("{\n.reg .pred p;\nsetp.ne.b32 p, %22, 0;\n"
    "wgmma.mma_async.sync.aligned.m64n40k16.f32.bf16.bf16 "
    "{%0, %1, %2, %3, %4, %5, %6, %7, %8, %9, %10, %11, %12, %13, %14, %15, "
    "%16, %17, %18, %19}, "
    "%20, %21, p, 1, 1, %23, %24;\n}\n"
    : "+f"(d[0]), "+f"(d[1]), "+f"(d[2]), "+f"(d[3]), "+f"(d[4]), "+f"(d[5]), "+f"(d[6]), "+f"(d[7]),
      "+f"(d[8]), "+f"(d[9]), "+f"(d[10]), "+f"(d[11]), "+f"(d[12]), "+f"(d[13]), "+f"(d[14]), "+f"(d[15]),
      "+f"(d[16]), "+f"(d[17]), "+f"(d[18]), "+f"(d[19])
    : "l"(da), "l"(db), "r"(scale_d), "n"(TA), "n"(TB));
}

template<int TB> __device__ __forceinline__ void wgmma_m64n40k16_rs(float (&d)[20], const uint32_t (&a)[4], uint64_t db, int scale_d) {
  asm volatile("{\n.reg .pred p;\nsetp.ne.b32 p, %25, 0;\n"
    "wgmma.mma_async.sync.aligned.m64n40k16.f32.bf16.bf16 "
    "{%0, %1, %2, %3, %4, %5, %6, %7, %8, %9, %10, %11, %12, %13, %14, %15, "
    "%16, %17, %18, %19}, "
    "{%20, %21, %22, %23}, %24, p, 1, 1, %26;\n}\n"
    : "+f"(d[0]), "+f"(d[1]), "+f"(d[2]), "+f"(d[3]), "+f"(d[4]), "+f"(d[5]), "+f"(d[6]), "+f"(d[7]),
      "+f"(d[8]), "+f"(d[9]), "+f"(d[10]), "+f"(d[11]), "+f"(d[12]), "+f"(d[13]), "+f"(d[14]), "+f"(d[15]),
      "+f"(d[16]), "+f"(d[17]), "+f"(d[18]), "+f"(d[19])
    : "r"(a[0]), "r"(a[1]), "r"(a[2]), "r"(a[3]), "l"(db), "r"(scale_d), "n"(TB));
}

template<int TA, int TB> __device__ __forceinline__ void wgmma_m64n8k16_ss(float (&d)[4], uint64_t da, uint64_t db, int scale_d) {
  asm volatile("{\n.reg .pred p;\nsetp.ne.b32 p, %6, 0;\n"
    "wgmma.mma_async.sync.aligned.m64n8k16.f32.bf16.bf16 "
    "{%0, %1, %2, %3}, "
    "%4, %5, p, 1, 1, %7, %8;\n}\n"
    : "+f"(d[0]), "+f"(d[1]), "+f"(d[2]), "+f"(d[3])
    : "l"(da), "l"(db), "r"(scale_d), "n"(TA), "n"(TB));
}

constexpr int kS = 2048, kD = 1024, kF = 3584;
constexpr int NST = 5, STAGE = 32768;
constexpr uint32_t sb = 1024;
constexpr int SM_V    = NST * STAGE;
constexpr int SM_Z    = SM_V + 16384;
constexpr int SM_PHI  = SM_Z + 4096;
constexpr int SM_MOE  = SM_PHI + 16384;
constexpr int SM_WPHI = SM_MOE + 16384;
constexpr int SM_BAND = SM_WPHI + 8192;
constexpr int SM_G    = SM_BAND + 2176;
constexpr int SM_BAR  = SM_G + 512;
constexpr int SM_MISC = SM_BAR + 448;
constexpr int SM_TOTAL = SM_MISC + 64;
static_assert(SM_TOTAL <= 232448, "smem");
constexpr uint32_t bars = sb + SM_BAR;
constexpr int B_FX = 0  , B_FY = 5  , B_XT = 15, B_EPOCH = 16, B_RX = 17  , B_MF = 21  , B_H1 = 24  , B_KV = 26  ;
constexpr int B_WPHI = 28, B_INFO = 29, B_QS = 30, B_XP = 31, B_RED = 32  , B_PUB = 36  , B_ME = 40  , B_MD = 43;
constexpr int B_EM = 44  , B_NUM = 49;
constexpr int C_START = 0, C_O = 1, C_KV = C_O + 64;

__device__ uint2 g_gate[kS];
__device__ uint2 g_key[128];
__device__ uint2 g_pre[4 * kF];
__device__ uint2 g_yp[32 * kD];
__device__ __align__(128) uint32_t g_kvp[16 * 16 * 2048];
__device__ __align__(128) uint32_t g_kvr[16 * 3072];
__device__ __align__(128) float g_zp[16 * 16 * 128];
__device__ __align__(128) uint32_t g_cnt[(C_KV + 32) * 32];
__device__ __align__(1024) __nv_bfloat16 g_o[kS * kD];
#define KS(id)
#define RG(id)
#define TS(id)
#define TSG(id)
constexpr int SM_ALLOC = SM_TOTAL;

#define POLL0 500
#define POLL1 150
#define RSTEP 2
#define POLLR 400
#define EARLY_N 2
#define EARLY_GAP 200
#define POLLF 50
#define WLEAD 11
#define MGAP 300

struct Params {
  const __nv_bfloat16 *x, *w, *w_phi, *w_r, *gate_w;
  uint64_t da, db, dw, dphi, dv, dband, dxs;
};

__device__ __forceinline__ uint32_t smem_u32(const void* p) { return (uint32_t)__cvta_generic_to_shared(p); }
__device__ __forceinline__ void mbar_init(uint32_t bar, uint32_t cnt) { asm volatile("mbarrier.init.shared::cta.b64 [%0], %1;" :: "r"(bar), "r"(cnt) : "memory"); }
__device__ __forceinline__ void mbar_expect_tx(uint32_t bar, uint32_t bytes) { asm volatile("mbarrier.arrive.expect_tx.shared::cta.b64 _, [%0], %1;" :: "r"(bar), "r"(bytes) : "memory"); }
__device__ __forceinline__ void mbar_arrive(uint32_t bar) { asm volatile("mbarrier.arrive.shared::cta.b64 _, [%0];" :: "r"(bar) : "memory"); }
__device__ __forceinline__ void mbar_arrive_n(uint32_t bar, uint32_t n) { asm volatile("mbarrier.arrive.shared::cta.b64 _, [%0], %1;" :: "r"(bar), "r"(n) : "memory"); }
constexpr int BUDGET = 1 << 20;
__device__ __forceinline__ void mbar_wait(uint32_t bar, uint32_t parity, int& budget) {
  asm volatile("{\n.reg .pred p;\n"
               "WAIT_L:\nmbarrier.try_wait.parity.shared::cta.b64 p, [%1], %2;\n@p bra WAIT_D;\n"
               "add.s32 %0, %0, -1;\nsetp.gt.s32 p, %0, 0;\n@p bra WAIT_L;\nWAIT_D:\n}"
               : "+r"(budget) : "r"(bar), "r"(parity) : "memory");
}
template <int SLEEP>
__device__ __forceinline__ void wait_count(const uint32_t* p, uint32_t target, int& budget) {
  asm volatile("{\n.reg .pred p;\n.reg .s32 v;\n"
               "WAIT_L:\nld.acquire.gpu.global.s32 v, [%1];\nsub.s32 v, v, %2;\nsetp.ge.s32 p, v, 0;\n@p bra WAIT_D;\n"
               "nanosleep.u32 %3;\nadd.s32 %0, %0, -4;\nsetp.gt.s32 p, %0, 0;\n@p bra WAIT_L;\nWAIT_D:\n}"
               : "+r"(budget) : "l"(p), "r"(target), "n"(SLEEP) : "memory");
}
__device__ __forceinline__ void tma_load(uint32_t dst, const CUtensorMap* m, uint32_t bar, int c0, int c1) {
  asm volatile("cp.async.bulk.tensor.2d.shared::cluster.global.mbarrier::complete_tx::bytes [%0], [%1, {%3, %4}], [%2];"
    :: "r"(dst), "l"(m), "r"(bar), "r"(c0), "r"(c1) : "memory");
}
__device__ __forceinline__ void tma_load3(uint32_t dst, const CUtensorMap* m, uint32_t bar, int c1, int c2) {
  asm volatile("cp.async.bulk.tensor.3d.shared::cluster.global.mbarrier::complete_tx::bytes [%0], [%1, {%5, %3, %4}], [%2];"
    :: "r"(dst), "l"(m), "r"(bar), "r"(c1), "r"(c2), "r"(0) : "memory");
}
__device__ __forceinline__ void tma_prefetch3(const CUtensorMap* m, int c1, int c2) {
  asm volatile("cp.async.bulk.prefetch.tensor.3d.L2.global [%0, {%3, %1, %2}];" :: "l"(m), "r"(c1), "r"(c2), "r"(0) : "memory");
}
__device__ __forceinline__ void tma_prefetch(const CUtensorMap* m, int c0, int c1) {
  asm volatile("cp.async.bulk.prefetch.tensor.2d.L2.global [%0, {%1, %2}];" :: "l"(m), "r"(c0), "r"(c1) : "memory");
}
__device__ __forceinline__ void tma_store(const CUtensorMap* m, uint32_t src, int c0, int c1) {
  asm volatile("cp.async.bulk.tensor.2d.global.shared::cta.bulk_group [%0, {%2, %3}], [%1];" :: "l"(m), "r"(src), "r"(c0), "r"(c1) : "memory");
}
__device__ __forceinline__ void bulk_load(uint32_t dst, const void* src, uint32_t bytes, uint32_t bar) {
  asm volatile("cp.async.bulk.shared::cluster.global.mbarrier::complete_tx::bytes [%0], [%1], %2, [%3];" :: "r"(dst), "l"(src), "r"(bytes), "r"(bar) : "memory");
}
__device__ __forceinline__ void prefetch_map(const CUtensorMap* m) { asm volatile("prefetch.tensormap [%0];" :: "l"(m) : "memory"); }
__device__ __forceinline__ bool elect_one() {
  uint32_t p;
  asm volatile("{\n.reg .pred P;\nelect.sync _|P, 0xffffffff;\nselp.u32 %0, 1, 0, P;\n}" : "=r"(p));
  return p;
}
__device__ __forceinline__ void wg_fence() { asm volatile("wgmma.fence.sync.aligned;" ::: "memory"); }
__device__ __forceinline__ void wg_commit() { asm volatile("wgmma.commit_group.sync.aligned;" ::: "memory"); }
template <int N> __device__ __forceinline__ void wg_wait() { asm volatile("wgmma.wait_group.sync.aligned %0;" :: "n"(N) : "memory"); }
template <int N> __device__ __forceinline__ void zero(float (&r)[N]) {
#pragma unroll
  for (int i = 0; i < N; i++) r[i] = 0.f;
}
template <int N> __device__ __forceinline__ void pin(float (&r)[N]) {
#pragma unroll
  for (int i = 0; i < N; i++) asm volatile("" : "+f"(r[i]) :: "memory");
}
template <int N> __device__ __forceinline__ void pinr(uint32_t (&r)[N][4]) {
#pragma unroll
  for (int i = 0; i < N; i++) asm volatile("" : "+r"(r[i][0]), "+r"(r[i][1]), "+r"(r[i][2]), "+r"(r[i][3]) :: "memory");
}
__device__ __forceinline__ void fence_async_smem() { asm volatile("fence.proxy.async.shared::cta;" ::: "memory"); }
__device__ __forceinline__ void fence_async_global() { asm volatile("fence.proxy.async.global;" ::: "memory"); }
__device__ __forceinline__ void bar_sync(int id, int n) { asm volatile("bar.sync %0, %1;" :: "r"(id), "r"(n) : "memory"); }
__device__ __forceinline__ void bar_arrive(int id, int n) { asm volatile("bar.arrive %0, %1;" :: "r"(id), "r"(n) : "memory"); }
__device__ __forceinline__ void warp_arrive(uint32_t bar, int lane) { __syncwarp(); if (lane == 0) mbar_arrive(bar); }
__host__ __device__ constexpr uint64_t make_desc(uint32_t addr, uint32_t lbo, uint32_t sbo, uint32_t swz) {
  return (uint64_t)((addr & 0x3FFFF) >> 4) | ((uint64_t)((lbo & 0x3FFFF) >> 4) << 16) | ((uint64_t)(sbo >> 4) << 32) | ((uint64_t)swz << 62);
}
__device__ __forceinline__ uint32_t pack2(float lo, float hi) {
  uint32_t r; asm("cvt.rn.bf16x2.f32 %0, %1, %2;" : "=r"(r) : "f"(hi), "f"(lo)); return r;
}
__device__ __forceinline__ float bf_lo(uint32_t v) { return __uint_as_float(v << 16); }
__device__ __forceinline__ float bf_hi(uint32_t v) { return __uint_as_float(v & 0xffff0000u); }
__device__ __forceinline__ float ex2(float x) { float r; asm("ex2.approx.ftz.f32 %0, %1;" : "=f"(r) : "f"(x)); return r; }
__device__ __forceinline__ float rcp(float x) { float r; asm("rcp.approx.ftz.f32 %0, %1;" : "=f"(r) : "f"(x)); return r; }
constexpr float LOG2E = 1.4426950408889634f;
__device__ __forceinline__ float sigmoidf(float x) { return rcp(1.0f + ex2(-LOG2E * x)); }
__device__ __forceinline__ void sts128(uint32_t a, uint32_t x, uint32_t y, uint32_t z, uint32_t w) {
  asm volatile("st.shared.v4.u32 [%0], {%1,%2,%3,%4};" :: "r"(a), "r"(x), "r"(y), "r"(z), "r"(w) : "memory");
}
__device__ __forceinline__ void lds128(uint32_t a, uint32_t (&r)[4]) {
  asm volatile("ld.shared.v4.u32 {%0,%1,%2,%3}, [%4];" : "=r"(r[0]), "=r"(r[1]), "=r"(r[2]), "=r"(r[3]) : "r"(a) : "memory");
}
__device__ __forceinline__ void sts32(uint32_t a, uint32_t v) { asm volatile("st.shared.u32 [%0], %1;" :: "r"(a), "r"(v) : "memory"); }
__device__ __forceinline__ uint32_t lds32(uint32_t a) { uint32_t v; asm volatile("ld.shared.u32 %0, [%1];" : "=r"(v) : "r"(a) : "memory"); return v; }
__device__ __forceinline__ float ldsf(uint32_t a) { return __uint_as_float(lds32(a)); }
__device__ __forceinline__ void stmatrix4(uint32_t a, uint32_t r0, uint32_t r1, uint32_t r2, uint32_t r3) {
  asm volatile("stmatrix.sync.aligned.m8n8.x4.shared.b16 [%0], {%1,%2,%3,%4};" :: "r"(a), "r"(r0), "r"(r1), "r"(r2), "r"(r3) : "memory");
}
__device__ __forceinline__ void ldmatrix4(uint32_t a, uint32_t (&r)[4]) {
  asm volatile("ldmatrix.sync.aligned.m8n8.x4.shared.b16 {%0,%1,%2,%3}, [%4];" : "=r"(r[0]), "=r"(r[1]), "=r"(r[2]), "=r"(r[3]) : "r"(a) : "memory");
}
__device__ __forceinline__ uint4 ldg_nc(const void* p) {
  uint4 v; asm volatile("ld.global.nc.L1::no_allocate.v4.u32 {%0,%1,%2,%3}, [%4];" : "=r"(v.x), "=r"(v.y), "=r"(v.z), "=r"(v.w) : "l"(p)); return v;
}
__device__ __forceinline__ void st_tagged(uint2* p, uint32_t v, uint32_t tag) {
  asm volatile("{\n.reg .b64 x;\nmov.b64 x, {%1, %2};\nst.relaxed.gpu.global.b64 [%0], x;\n}" :: "l"(p), "r"(v), "r"(tag) : "memory");
}
__device__ __forceinline__ uint2 ld_tagged(const uint2* p) {
  uint2 v; asm volatile("{\n.reg .b64 x;\nld.relaxed.gpu.global.b64 x, [%2];\nmov.b64 {%0, %1}, x;\n}" : "=r"(v.x), "=r"(v.y) : "l"(p) : "memory"); return v;
}
__device__ __forceinline__ void probe(const uint2* p, uint32_t tag, int& budget) {
  do { __nanosleep(POLL0); budget -= 16; } while (!__all_sync(0xffffffffu, ld_tagged(p).y == tag) && budget > 0);
}
template <int STRIDE, int N>
__device__ __forceinline__ void gather(const uint2* p, uint32_t tag, float& s0, float& s1, int& budget) {
  uint32_t pause = 0;
  bool again;
#pragma unroll 1
  do {
    __nanosleep(pause);
    pause = POLL0;
    uint32_t bad = 0;
    s0 = s1 = 0.f;
#pragma unroll
    for (int i = 0; i < N; i++) {
      const uint2 w = ld_tagged(p + i * STRIDE);
      bad |= w.y ^ tag;
      if (i < N / 2) s0 += __uint_as_float(w.x); else s1 += __uint_as_float(w.x);
    }
    budget -= 16;
    again = __any_sync(0xffffffffu, bad != 0) && budget > 0;
  } while (again);
}
__device__ __forceinline__ uint32_t ldg_strong(const void* p) { uint32_t v; asm volatile("ld.relaxed.gpu.global.u32 %0, [%1];" : "=r"(v) : "l"(p) : "memory"); return v; }
__device__ __forceinline__ void sts16(uint32_t a, uint32_t v) { asm volatile("st.shared.u16 [%0], %1;" :: "r"(a), "h"((uint16_t)v) : "memory"); }
__device__ __forceinline__ void signal_add(uint32_t* p, uint32_t v) { asm volatile("red.release.gpu.global.add.u32 [%0], %1;" :: "l"(p), "r"(v) : "memory"); }
__device__ __forceinline__ float qmax(float v) { v = fmaxf(v, __shfl_xor_sync(0xffffffffu, v, 1)); return fmaxf(v, __shfl_xor_sync(0xffffffffu, v, 2)); }
__device__ __forceinline__ float qsum(float v) { v += __shfl_xor_sync(0xffffffffu, v, 1); return v + __shfl_xor_sync(0xffffffffu, v, 2); }
__device__ __forceinline__ float fold(float a, float b, bool hi, int m) { return (hi ? b : a) + __shfl_xor_sync(0xffffffffu, hi ? a : b, m); }

__device__ __forceinline__ void yield_slot() { asm volatile("pmevent 0;" ::: "memory"); }
__device__ __forceinline__ float fma_v(float a, float b, float c) { float r; asm volatile("fma.rn.f32 %0, %1, %2, %3;" : "=f"(r) : "f"(a), "f"(b), "f"(c)); return r; }
constexpr float EXP_LIM_F = 36028797018963968.0f;
constexpr uint32_t EXP_TOP = 0x58805880u;
__device__ __forceinline__ void exp_plain(const float (&p)[16], float (&ep)[16], float (&em)[16]) {
#pragma unroll
  for (int i = 0; i < 16; i++) { ep[i] = ex2(p[i]); em[i] = ex2(-p[i]); }
}
__device__ __forceinline__ void exp_shifted(const float (&p)[16], float sgn, float (&e)[16]) {
#pragma unroll
  for (int i = 0; i < 16; i++) e[i] = sgn * p[i];
#pragma unroll
  for (int o = 0; o < 4; o += 2) {
    const float mx = qmax(fmaxf(fmaxf(fmaxf(e[o], e[o + 1]), fmaxf(e[o + 4], e[o + 5])), fmaxf(fmaxf(e[o + 8], e[o + 9]), fmaxf(e[o + 12], e[o + 13]))));
#pragma unroll
    for (int c = 0; c < 4; c++) { e[4 * c + o] = ex2(e[4 * c + o] - mx); e[4 * c + o + 1] = ex2(e[4 * c + o + 1] - mx); }
  }
}
__device__ __forceinline__ void pack_sums(const float (&e)[16], uint32_t (&pk)[2][4], float (&s)[2]) {
#pragma unroll
  for (int i = 0; i < 8; i++) pk[i >> 2][i & 3] = pack2(e[2 * i], e[2 * i + 1]);
#pragma unroll
  for (int o = 0; o < 4; o += 2) s[o >> 1] = ((e[o] + e[o + 1]) + (e[o + 4] + e[o + 5])) + ((e[o + 8] + e[o + 9]) + (e[o + 12] + e[o + 13]));
}
__device__ __forceinline__ uint32_t rcp2(float s) { const float r = rcp(s); return pack2(r, r); }
__device__ __forceinline__ uint32_t mul2(uint32_t a, uint32_t b) { uint32_t r; asm("mul.rn.bf16x2 %0, %1, %2;" : "=r"(r) : "r"(a), "r"(b)); return r; }
__device__ __forceinline__ void store_phi(uint32_t a, const uint32_t (&pk)[2][4], uint32_t r0, uint32_t r1) {
#pragma unroll
  for (int h = 0; h < 2; h++) stmatrix4(a ^ (h * 32), mul2(pk[h][0], r0), mul2(pk[h][1], r1), mul2(pk[h][2], r0), mul2(pk[h][3], r1));
}
__device__ __forceinline__ uint32_t exp_frags(const float (&p)[16], uint32_t (&ef)[4][4], uint32_t top) {
  float ep[16], em[16];
  exp_plain(p, ep, em);
#pragma unroll
  for (int s = 0; s < 2; s++)
#pragma unroll
    for (int r = 0; r < 4; r++) {
      ef[s][r] = pack2(ep[8 * s + 2 * r], ep[8 * s + 2 * r + 1]);
      ef[2 + s][r] = pack2(em[8 * s + 2 * r], em[8 * s + 2 * r + 1]);
    }
#pragma unroll
  for (int s = 0; s < 4; s++) top = __vimax3_u16x2(__vimax3_u16x2(top, ef[s][0], ef[s][1]), ef[s][2], ef[s][3]);
  return top;
}
__device__ __forceinline__ void issue_pq(float (&p)[4][16], const uint32_t (&qf)[4][2][4], uint64_t dw) {
  wg_fence();
#pragma unroll
  for (int h = 0; h < 4; h++) {
    wgmma_m64n32k16_rs<1>(p[h], qf[h][0], dw + h * 128, 0);
    wgmma_m64n32k16_rs<1>(p[h], qf[h][1], dw + h * 128 + 64, 1);
  }
  wg_commit();
}

#define SPLIT_BATCH 2
__device__ __forceinline__ void mainloop128(float (&acc)[2][64], uint64_t da0, uint64_t db0, uint32_t slot, uint32_t ph, int steps, bool lane0, int& budget, int cta, int n0) {
  uint32_t prev = 0;
#pragma unroll 1
  for (int k = 0; k < steps; k++) {
    mbar_wait(bars + B_FX * 8 + slot * 8, ph, budget);
    const uint64_t da = da0 + slot * (STAGE >> 4), db = db0 + slot * (STAGE >> 4);
#pragma unroll
    for (int kk = 0; kk < 4; kk++) {
      if (SPLIT_BATCH == 2 || !(kk & 1)) {
        wg_wait<1>();
        if (kk == 3 - SPLIT_BATCH && k > 0 && lane0) mbar_arrive_n(bars + B_EM * 8 + prev * 8, 2);
        wg_fence();
      }
      wgmma_m64n128k16_ss<0, 1>(acc[0], da + kk * 2, db + kk * 128, kk ? 1 : k);
      wgmma_m64n128k16_ss<0, 1>(acc[1], da + 512 + kk * 2, db + kk * 128, kk ? 1 : k);
      if (SPLIT_BATCH == 2 || (kk & 1)) wg_commit();
    }
    prev = slot;
    if (++slot == NST) { slot = 0; ph ^= 1; }
  }
}
__device__ __forceinline__ void kstep64(float (&acc)[64], uint64_t da, uint64_t db, int accumulate) {
  wg_fence();
#pragma unroll
  for (int kk = 0; kk < 4; kk++) wgmma_m64n128k16_ss<0, 1>(acc, da + kk * 2, db + kk * 128, kk ? 1 : accumulate);
  wg_commit();
}
__device__ __forceinline__ void issue_kv(float (&kv)[20], uint64_t dphi, uint64_t dv, int accumulate) {
  wg_fence();
#pragma unroll
  for (int ks = 0; ks < 4; ks++)
    wgmma_m64n40k16_ss<1, 1>(kv, dphi + ks * 128, dv - (uint64_t)ks * ((64ull << 16) - 64ull), ks ? 1 : accumulate);
  wg_commit();
}
__device__ __forceinline__ void load_slice(int hp, int bi, int tw, uint32_t (&v)[16], uint32_t (&z)[4]) {
#pragma unroll
  for (int i = 0; i < 16; i++) v[i] = ldg_strong(&g_kvp[(hp * 16 + i) * 2048 + bi * 128 + tw]);
  if (tw < 32) {
#pragma unroll
    for (int i = 0; i < 4; i++) z[i] = ldg_strong(&g_zp[(hp * 16 + i * 4 + (tw >> 3)) * 128 + (bi & 3) * 32 + (bi >> 2) * 8 + (tw & 7)]);
  }
}
__device__ __forceinline__ uint32_t moe_buf(uint32_t b) { return b == 2 ? SM_V + 8192 : SM_MOE + b * 8192; }
template <bool DOWN>
__device__ __forceinline__ void moe_chunks(float (&a)[4], int n, uint32_t& buf, uint32_t& ph, uint64_t da0, uint64_t db, bool lane0) {
  int budget = BUDGET;
  zero(a);
#pragma unroll 1
  for (int c = 0; c < n; c++) {
    mbar_wait(bars + B_MF * 8 + buf * 8, ph, budget);
    const uint64_t da = da0 + (moe_buf(buf) >> 4);
    wg_fence();
#pragma unroll
    for (int j = 0; j < 4; j++) wgmma_m64n8k16_ss<1, 0>(a, da + j * 128, DOWN ? db - j : db + j * 2, 1);
    wg_commit();
    wg_wait<0>();
    if (lane0) mbar_arrive(bars + B_ME * 8 + buf * 8);
    db += DOWN ? 16 : 8;
    if (++buf == 3) { buf = 0; ph ^= 1; }
  }
  pin(a);
}
constexpr uint64_t DV_TILE = 4 * ((64ull << 16) - 64ull);

template <bool BY_SM>
__global__ void __launch_bounds__(512, 1)
fused_kernel(const __grid_constant__ CUtensorMap mx, const __grid_constant__ CUtensorMap mw, const __grid_constant__ CUtensorMap mwo,
             const __grid_constant__ CUtensorMap mo, const __grid_constant__ CUtensorMap mout, const __grid_constant__ CUtensorMap mxr,
             const __grid_constant__ CUtensorMap mg, const __grid_constant__ CUtensorMap mu, const __grid_constant__ CUtensorMap md, const Params P) {
  extern __shared__ __align__(1024) uint8_t smem_raw[];
  if (smem_u32(smem_raw) != sb) return;
  const int tid = threadIdx.x, lane = tid & 31;
  if (tid == 256) TS(1);
  const int warp = __shfl_sync(0xffffffffu, tid >> 5, 0), wg = warp >> 2;
  int budget = BUDGET;
  if (warp == 10 && elect_one()) { prefetch_map(&mx); prefetch_map(&mw); }
  int cta;
  {
    uint32_t smid;
    asm volatile("mov.u32 %0, %%smid;" : "=r"(smid));
    if (!BY_SM) cta = blockIdx.x;
    else if (smid < 64) cta = ((smid >> 1) & 7) * 16 + (smid >> 4) * 2 + (smid & 1);
    else if (smid < 120) { const int t = (smid - 64) >> 1, d = (t * 37) >> 8; cta = (1 + t - d * 7) * 16 + 8 + d * 2 + (smid & 1); }
    else cta = smid < 124 ? smid + 8 : smid - 116;
  }
  if (cta >= 128) {
    if (tid == 0) {
      const uint32_t old = atomicAdd(&g_cnt[C_START], 32u);
      wait_count<500>(&g_cnt[C_START], (old & ~255u) + 256u, budget);
    }
    return;
  }
  const int bi = (cta >> 5) * 4 + ((cta >> 2) & 3);
  const int bj = ((cta >> 4) & 1) * 4 + (cta & 3);

  if (wg == 3) {
    asm volatile("setmaxnreg.dec.sync.aligned.u32 64;");
    const int t3 = tid - 384, w3 = warp - 12;
    if (t3 == 0) TSG(0);
    if (t3 < 17) st_tagged(t3 < 16 ? &g_gate[bi * 128 + bj * 16 + t3] : &g_key[cta], 0, 1);
    bar_sync(0, 512);
#pragma unroll 1
    for (int u = 0; u < 4; u++) {
      const uint4 v = ldg_nc(P.w_phi + bj * 4096 + (u * 128 + t3) * 8);
      sts128(sb + SM_WPHI + u * 2048 + (t3 >> 2) * 64 + (((t3 & 3) ^ ((t3 >> 3) & 3)) << 4),
             pack2(LOG2E * bf_lo(v.x), LOG2E * bf_hi(v.x)), pack2(LOG2E * bf_lo(v.y), LOG2E * bf_hi(v.y)),
             pack2(LOG2E * bf_lo(v.z), LOG2E * bf_hi(v.z)), pack2(LOG2E * bf_lo(v.w), LOG2E * bf_hi(v.w)));
    }
    fence_async_smem();
    warp_arrive(bars + B_WPHI * 8, lane);
    bar_sync(6, 256);
    const uint32_t target = lds32(sb + SM_MISC);
    uint32_t key;
    {
      uint32_t kk[4];
      lds128(sb + SM_MISC + 16, kk);
      if (t3 == 0) st_tagged(&g_key[cta], max(max(kk[0], kk[1]), max(kk[2], kk[3])), target);
      uint2 k, gv;
      __nanosleep(POLLR);
      do {
        __nanosleep(POLL1);
        k = ld_tagged(&g_key[t3]);
        gv = ld_tagged(&g_gate[bi * 128 + t3]);
        budget -= 4;
      } while (!__all_sync(0xffffffffu, k.y == target && gv.y == target) && budget > 0);
      key = __reduce_max_sync(0xffffffffu, k.x);
      if (lane == 0) sts32(sb + SM_MISC + 32 + w3 * 4, key);
      sts32(sb + SM_G + t3 * 4, gv.x);
      bar_sync(5, 128);
      lds128(sb + SM_MISC + 32, kk);
      key = max(max(kk[0], kk[1]), max(kk[2], kk[3]));
    }
    const int idx = (0xFFFF - (key & 0xFFFF)) & (kS - 1);
    if (t3 == 0) { sts32(sb + SM_MISC + 4, idx); TS(8); }
    warp_arrive(bars + B_INFO * 8, lane);
    {
      const uint4 v = ldg_nc(P.x + (size_t)idx * kD + t3 * 8);
      sts128(sb + SM_BAND + t3 * 16, v.x, v.y, v.z, v.w);
    }
    const int t2 = (lane & 3) * 2, row = w3 * 16 + (lane >> 2);
    float a[4];
    uint32_t buf = 0, ph = 0;
    fence_async_smem();
    bar_sync(5, 128);
    {
      const int r = cta >> 4;
#pragma unroll 1
      for (int part = 0; part < 2; part++) {
        const int n = part ? 14 - 2 * r : 2 * r;
        moe_chunks<false>(a, n, buf, ph, P.da, P.dxs + (part ? 0 : (16 - n) * 8), lane == 0);
        uint2* dst = &g_pre[(((cta >> 2) & 2) + 1 - part) * kF + ((r - 1 + part) * 8 + (cta & 7)) * 64 + row];
        if (t2 == 0 && n) { st_tagged(dst, __float_as_uint(a[0]), target); st_tagged(dst + 8, __float_as_uint(a[2]), target); }
      }
    }
    if (t3 == 0) TS(9);
    bar_sync(5, 128);
    sts128(sb + SM_BAND + t3 * 16, 0, 0, 0, 0);
    {
      __nanosleep(POLL0);
      float gs, us;
      gather<kF, 4>(&g_pre[(cta >> 2) * 112 + min(t3, 111)], target, gs, us, budget);
      bar_sync(5, 128);
      if (t3 < 112) sts16(sb + SM_BAND + 112 + (t3 >> 3) * 128 + (t3 & 7) * 2, pack2(gs * sigmoidf(gs) * us, 0.f));
    }
    fence_async_smem();
    bar_sync(5, 128);
    if (t3 == 0) TS(12);
    moe_chunks<true>(a, 7, buf, ph, P.da, P.dband + 7, lane == 0);
    if (t3 == 0) TS(10);
    if (t2 < 4) {
      uint2* dst = &g_yp[(cta >> 2) * kD + (cta & 3) * 256 + t2 * 64 + row];
      st_tagged(dst, __float_as_uint(a[0]), target); st_tagged(dst + 8, __float_as_uint(a[2]), target);
      st_tagged(dst + 64, __float_as_uint(a[1]), target); st_tagged(dst + 72, __float_as_uint(a[3]), target);
    }
    if (lane == 0) mbar_arrive(bars + B_MD * 8);
    if ((idx >> 7) == bi) {
      mbar_wait(bars + (B_PUB + 3) * 8, 0, budget);
      if (w3 == 0) probe(&g_yp[lane * kD + bj * 128], target, budget);
      bar_sync(5, 128);
      float y = 0.f;
#pragma unroll 1
      for (int hf = 0; hf < 2; hf++) {
        float y0, y1;
        gather<kD, 16>(&g_yp[hf * 16 * kD + bj * 128 + t3], target, y0, y1, budget);
        y += y0 + y1;
      }
      const uint32_t ob = key >> 16;
      const float upd = y * sigmoidf(__uint_as_float(((ob & 0x8000u) ? (ob ^ 0x8000u) : (~ob & 0xFFFFu)) << 16));
      const uint32_t a = sb + SM_PHI + (t3 >> 6) * 16384 + (idx & 127) * 128 + ((((t3 >> 3) & 7) ^ (idx & 7)) << 4) + (t3 & 7) * 2;
      mbar_wait(bars + B_XT * 8, 0, budget);
      uint16_t xb;
      asm volatile("ld.shared.u16 %0, [%1];" : "=h"(xb) : "r"(a) : "memory");
      sts16(a, pack2(bf_lo(xb) + upd, 0.f));
      warp_arrive(bars + B_XP * 8, lane);
      if (t3 == 0) TS(11);
    }
  } else if (wg < 2) {
    if ((warp & 3) < EARLY_N && lane < (wg ? 8 : 16)) {
      const int n = warp & 3;
      const __nv_bfloat16* p = wg ? P.w + (size_t)(n * 64 + bi + (lane >> 1) * 16) * (3 * kD) + 1024 + (lane & 1) * 1024 + bj * 128
                                  : P.x + (size_t)(bi * 128 + bj * 16 + lane) * kD + n * 64;
      if (n) __nanosleep(n * EARLY_GAP);
      asm volatile("prefetch.global.L2 [%0];" :: "l"(p));
    }
    __syncwarp();
    asm volatile("setmaxnreg.inc.sync.aligned.u32 208;");
    const int tw = tid & 127, w = warp & 3, g = lane >> 2, t = lane & 3;
    const bool lane0 = lane == 0;
    if (wg == 0) sts128(sb + SM_Z + (tw & 63) * 16, 0x3f803f80u, 0x3f803f80u, 0x3f803f80u, 0x3f803f80u);
    bar_sync(0, 512);
    if (wg == 1) {
      float sr[4], sg[4];
      zero(sr); zero(sg);
#pragma unroll 1
      for (int c = 0; c < 4; c++) {
        RG(48 + c * 2);
        mbar_wait(bars + (B_RX + c) * 8, 0, budget);
        RG(49 + c * 2);
        uint32_t rs[4], gs[4], xs[4][4];
        lds128(sb + SM_V + c * 512 + lane * 16, rs);
        lds128(sb + SM_V + 2048 + c * 512 + lane * 16, gs);
#pragma unroll
        for (int r = 0; r < 4; r++) lds128(sb + SM_PHI + c * 8192 + (w * 4 + r) * 512 + lane * 16, xs[r]);
#pragma unroll
        for (int e = 0; e < 4; e++) {
          const float r0 = bf_lo(rs[e]), r1 = bf_hi(rs[e]), g0 = bf_lo(gs[e]), g1 = bf_hi(gs[e]);
#pragma unroll
          for (int r = 0; r < 4; r++) {
            const float x0 = bf_lo(xs[r][e]), x1 = bf_hi(xs[r][e]);
            sr[r] = fma_v(x0, r0, sr[r]); sg[r] = fma_v(x0, g0, sg[r]);
            sr[r] = fma_v(x1, r1, sr[r]); sg[r] = fma_v(x1, g1, sg[r]);
            if (r != 1) yield_slot();
          }
        }
      }
      RG(56);
      fence_async_smem();
      __syncwarp();
      if (lane < 3) mbar_arrive(bars + (B_ME + lane) * 8);
      const bool b4 = lane & 16, b3 = lane & 8, b2 = lane & 4;
      const float v = qsum(fold(fold(fold(sr[0], sg[0], b4, 16), fold(sr[2], sg[2], b4, 16), b3, 8),
                                fold(fold(sr[1], sg[1], b4, 16), fold(sr[3], sg[3], b4, 16), b3, 8), b2, 4));
      const int row = bi * 128 + bj * 16 + w * 4 + (g & 3);
      const uint32_t rb = pack2(v + 0.f, 0.f);
      const uint32_t ob = (rb & 0x8000u) ? (~rb & 0xFFFFu) : (rb | 0x8000u);
      const uint32_t best = __reduce_max_sync(0xffffffffu, b4 ? 0u : (ob << 16) | (0xFFFFu - row));
      mbar_wait(bars + B_EPOCH * 8, 0, budget);
      const uint32_t tag = lds32(sb + SM_MISC);
      if (lane0) sts32(sb + SM_MISC + 16 + w * 4, best);
      if (b4 && t == 0) st_tagged(&g_gate[row], __float_as_uint(sigmoidf(v)), tag);
      if (tw == 0) TS(14);
      bar_arrive(6, 256);
      bar_sync(1, 256);
    }

    {
      float acc[2][64];
      if (tw == 0) TS(16 + wg * 16);
      mainloop128(acc, P.da, P.db, wg, wg, 16, lane0, budget, cta, wg * 16);
      bar_sync(1 + wg, 256);
      wg_wait<0>();
      pin(acc[0]); pin(acc[1]);
      if (lane0) mbar_arrive_n(bars + (B_EM + wg) * 8, 2);
      if (tw == 0) TS(17 + wg * 16);
      float p[4][16];
      uint32_t vp[8][4];
      const uint32_t av = sb + SM_V + (w * 16 + g) * 64 + ((t ^ (g >> 1)) << 4);
      {
        uint32_t kf[4][2][4];
#pragma unroll
        for (int u = 0; u < 4; u++)
#pragma unroll
          for (int s = 0; s < 2; s++)
#pragma unroll
            for (int r = 0; r < 4; r++) kf[u][s][r] = pack2(acc[u & 1][16 * (u >> 1) + 8 * s + 2 * r], acc[u & 1][16 * (u >> 1) + 8 * s + 2 * r + 1]);
        mbar_wait(bars + B_WPHI * 8, 0, budget);
        const uint64_t dw = P.dw + wg * 256;
        wg_fence();
#pragma unroll
        for (int u = 0; u < 4; u++) {
          wgmma_m64n32k16_rs<1>(p[u], kf[u][0], dw + (u >> 1) * 128, 0);
          wgmma_m64n32k16_rs<1>(p[u], kf[u][1], dw + (u >> 1) * 128 + 64, 1);
        }
        wg_commit();
#pragma unroll
        for (int u = 0; u < 8; u++) {
          const float* a = &acc[(u >> 1) & 1][32 + 16 * (u >> 2) + 2 * (u & 1)];
          vp[u][0] = pack2(a[0], a[1]); vp[u][1] = pack2(a[4], a[5]); vp[u][2] = pack2(a[8], a[9]); vp[u][3] = pack2(a[12], a[13]);
          if (u < 4) sts128(av + (u >> 1) * 4096 + (u & 1) * 512, vp[u][0], vp[u][1], vp[u][2], vp[u][3]);
        }
        pinr(vp);
        wg_wait<0>();
#pragma unroll
        for (int u = 0; u < 4; u++) pin(p[u]);
      }
      if (tw == 0) TS(18 + wg * 16);
      float kv[2][20];
      uint32_t sv[16], sz[4] = {0, 0, 0, 0};
      {
        const uint32_t sphi = sb + SM_PHI + (w * 16 + (lane & 15)) * 128 + (((lane >> 4) ^ (lane & 7)) << 4);
        float top = 0.f;
        uint32_t pk[4][2][4];
        float ps[2], sa[4], sc[4];
        uint32_t redo = 0;
#pragma unroll
        for (int i = 0; i < 11; i++) {
          if (i >= 3) {
            const int j = i - 3;
            const float s0 = sc[0] + sc[2], s1 = sc[1] + sc[3];
            top = fmaxf(top, fmaxf(s0, s1));
            store_phi((sphi ^ ((j & 1) * 64)) + (j & 2) * 4096, pk[j & 3], rcp2(s0), rcp2(s1));
          }
          if (i >= 2 && i <= 9) {
            sc[0] = sa[0] + sa[2]; sc[1] = sa[1] + sa[3];
            sc[2] = __shfl_xor_sync(0xffffffffu, sc[0], 2); sc[3] = __shfl_xor_sync(0xffffffffu, sc[1], 2);
          }
          if (i >= 1 && i <= 8) {
            sa[0] = ps[0]; sa[1] = ps[1];
            sa[2] = __shfl_xor_sync(0xffffffffu, sa[0], 1); sa[3] = __shfl_xor_sync(0xffffffffu, sa[1], 1);
          }
          if (i < 8) {
            pin(p[i >> 1]);
            float e[16];
#pragma unroll
            for (int c = 0; c < 16; c++) e[c] = ex2((i & 1) ? -p[i >> 1][c] : p[i >> 1][c]);
            pack_sums(e, pk[i & 3], ps);
            pinr(pk[i & 3]); pin(ps);
          }
          if (i < 10) yield_slot();
          if (i >= 2 && i <= 9) pin(sc);
          if (i >= 1 && i <= 8) pin(sa);
          RG(i * 4);
          if (i >= 4 && !(i & 1)) {
            const int u = (i - 4) >> 1;
            fence_async_smem();
            wg_wait<0>();
            RG(i * 4 + 1);
            if (u < 3) bar_sync(7 + wg, 128);
            else asm volatile("{\n.reg .pred p, q;\nsetp.ne.b32 p, %2, 0;\nbar.red.or.pred q, %1, 128, p;\nselp.u32 %0, 1, 0, q;\n}"
                              : "=r"(redo) : "r"(7 + wg), "r"((uint32_t)!(top < EXP_LIM_F)) : "memory");
            RG(i * 4 + 2);
            issue_kv(kv[u >> 1], P.dphi + (u & 1) * 512, P.dv - (u & 1) * DV_TILE, u & 1);
            if (u == 1 || u == 2) {
#pragma unroll
              for (int r = 0; r < 2; r++) sts128(av + ((u + 1) & 1) * 4096 + r * 512, vp[2 * u + 2 + r][0], vp[2 * u + 2 + r][1], vp[2 * u + 2 + r][2], vp[2 * u + 2 + r][3]);
            }
            if (u < 3) yield_slot();
            RG(i * 4 + 3);
          }
        }
        if (tw == 0) TS(19 + wg * 16);
        if (wg) { mbar_wait(bars + B_H1 * 8, 0, budget); load_slice(bj * 2, bi, tw, sv, sz); }
        wg_wait<0>();
        pin(kv[0]); pin(kv[1]);
        if (__builtin_expect(__any_sync(0xffffffffu, redo), 0)) {
#pragma unroll 1
          for (int u = 0; u < 4; u++) {
            bar_sync(7 + wg, 128);
#pragma unroll 1
            for (int sg = 0; sg < 2; sg++) {
              float e[16];
              exp_shifted(p[0], sg ? -1.f : 1.f, e);
              pack_sums(e, pk[0], ps);
              store_phi(sphi ^ (sg * 64), pk[0], rcp2(qsum(ps[0])), rcp2(qsum(ps[1])));
            }
            sts128(av, vp[0][0], vp[0][1], vp[0][2], vp[0][3]);
            sts128(av + 512, vp[1][0], vp[1][1], vp[1][2], vp[1][3]);
            fence_async_smem();
            bar_sync(7 + wg, 128);
            issue_kv(kv[1], P.dphi, P.dv, u & 1);
            wg_wait<0>();
            pin(kv[1]);
#pragma unroll
            for (int c = 0; c < 16; c++) { p[0][c] = p[1][c]; p[1][c] = p[2][c]; p[2][c] = p[3][c]; }
#pragma unroll
            for (int c = 0; c < 24; c++) vp[c >> 2][c & 3] = vp[(c >> 2) + 2][c & 3];
            if (u == 1) {
#pragma unroll
              for (int c = 0; c < 20; c++) kv[0][c] = kv[1][c];
            }
          }
        }
      }
      if (tw == 0) TS(20 + wg * 16);
      {
        const int hp = bj * 2 + wg;
        uint4* dst = reinterpret_cast<uint4*>(&g_kvp[(hp * 16 + bi) * 2048]) + tw;
#pragma unroll
        for (int q = 0; q < 4; q++) {
          const float* a = &kv[q >> 1][8 * (q & 1)];
          dst[q * 128] = make_uint4(pack2(a[0], a[1]), pack2(a[2], a[3]), pack2(a[4], a[5]), pack2(a[6], a[7]));
        }
        g_zp[(hp * 16 + bi) * 128 + w * 32 + (t & 1) * 16 + g * 2 + (t >> 1)] = t == 0 ? kv[0][16] : t == 1 ? kv[0][18] : t == 2 ? kv[1][16] : kv[1][18];
      }
      if (tw == 0) TS(51 + wg * 4);
      if (wg == 0) warp_arrive(bars + B_RED * 8, lane);
      else {
        const int row = (bi & 3) * 16 + (tw >> 4) + (tw & 1) * 8, ch = ((bi >> 2) & 1) * 2 + ((tw >> 1) & 1);
        uint32_t* dst = &g_kvr[bj * 6144 + (bi >> 3) * 1024 + row * 16 + ((ch ^ ((row >> 1) & 3)) << 2) + ((tw >> 2) & 3)];
        const int zr = (bi & 3) * 16 + (bi >> 2) * 4 + ((lane >> 1) & 3);
        uint32_t* dz = &g_kvr[bj * 6144 + 2048 + zr * 16 + ((((lane & 1) + ((lane >> 2) & 2)) ^ ((zr >> 1) & 3)) << 2)];
#pragma unroll 1
        for (int it = 0; it < 2; it++) {
          float lo = 0.f, hi = 0.f;
#pragma unroll
          for (int i = 0; i < 16; i++) { lo += bf_lo(sv[i]); hi += bf_hi(sv[i]); }
          *dst = pack2(lo, hi);
          if (w == 0) {
            float z = (__uint_as_float(sz[0]) + __uint_as_float(sz[1])) + (__uint_as_float(sz[2]) + __uint_as_float(sz[3]));
            z += __shfl_xor_sync(0xffffffffu, z, 8); z += __shfl_xor_sync(0xffffffffu, z, 16);
            const uint32_t z1 = pack2(z, 1.0f);
            if (lane < 16) *reinterpret_cast<uint4*>(dz) = make_uint4(z1, z1, z1, z1);
          }
          warp_arrive(bars + (B_RED + 1 + it) * 8, lane);
          if (tw == 0) TS(21 + it * 16);
          if (it) break;
          mbar_wait(bars + (B_H1 + 1) * 8, 0, budget);
          load_slice(bj * 2 + 1, bi, tw, sv, sz);
          dst += 3072; dz += 3072;
        }
      }
    }

    const uint32_t stash = sb + 3 * STAGE + 8192 + w * 2048 + lane * 16;
    const int rowl = wg * 64 + w * 16 + g;
    mbar_wait(bars + B_INFO * 8, 0, budget);
    const float gA = ldsf(sb + SM_G + rowl * 4), gB = ldsf(sb + SM_G + rowl * 4 + 32);
    {
      float p[4][16];
      uint32_t ef[2][4][4];
      uint32_t top = EXP_TOP;
      if (wg == 0) {
        float acc[2][64];
        bar_sync(2, 256);
        if (tw == 0) TS(22);
        mainloop128(acc, P.da, P.db, 32 % NST, (32 / NST) & 1, 12, lane0, budget, cta, 32);
#pragma unroll 1
        for (int n = 0; n < 4; n++) {
          const uint32_t slot = n ? n - 1 : 4;
          if (tw == 0) KS(128 + 44 + n);
          mbar_wait(bars + B_FX * 8 + slot * 8, n != 0, budget);
          if (tw == 0) KS(44 + n);
          kstep64(acc[0], P.da + slot * (STAGE >> 4), P.db + slot * (STAGE >> 4), 1);
          wg_wait<1>();
          if (n == 0 && lane0) mbar_arrive_n(bars + (B_EM + 43 % NST) * 8, 2);
        }
        kstep64(acc[1], P.da + 512 + (44 % NST) * (STAGE >> 4), P.db + (44 % NST) * (STAGE >> 4), 1);
        wg_wait<1>();
        pin(acc[0]);
        if (tw == 0) TS(15);
        {
          uint32_t qf[4][2][4];
#pragma unroll
          for (int u = 0; u < 8; u++)
#pragma unroll
            for (int r = 0; r < 4; r++) qf[u >> 1][u & 1][r] = pack2(acc[0][8 * u + 2 * r], acc[0][8 * u + 2 * r + 1]);
          issue_pq(p, qf, P.dw);
          kstep64(acc[1], P.da + 512 + (45 % NST) * (STAGE >> 4), P.db + (45 % NST) * (STAGE >> 4), 1);
          wg_wait<1>();
        }
#pragma unroll
        for (int h = 0; h < 4; h++) pin(p[h]);
        if (tw == 0) TS(24);
#pragma unroll
        for (int h = 0; h < 2; h++) {
          if (lane0) mbar_arrive_n(bars + (B_EM + (44 + h) % NST) * 8, 2);
          kstep64(acc[1], P.da + 512 + ((46 + h) % NST) * (STAGE >> 4), P.db + ((46 + h) % NST) * (STAGE >> 4), 1);
          yield_slot();
          pin(p[h]);
          top = exp_frags(p[h], ef[h], top);
          pinr(ef[h]);
          yield_slot();
          if (h == 0) wg_wait<1>(); else wg_wait<0>();
        }
        pin(acc[1]);
        if (lane0) { mbar_arrive_n(bars + (B_EM + 46 % NST) * 8, 2); mbar_arrive_n(bars + (B_EM + 47 % NST) * 8, 2); }
        if (tw == 0) TS(23);
#pragma unroll
        for (int u = 0; u < 8; u++) {
          const float* a = &acc[1][8 * u];
          sts128(stash + (u >> 2) * STAGE + (u & 3) * 512, pack2(a[0], a[1]), pack2(a[2], a[3]), pack2(a[4], a[5]), pack2(a[6], a[7]));
        }
        warp_arrive(bars + B_QS * 8, lane);
      } else {
        uint32_t qf[4][2][4];
        mbar_wait(bars + B_QS * 8, 0, budget);
#pragma unroll
        for (int u = 0; u < 8; u++) lds128(stash + (u >> 2) * STAGE + (u & 3) * 512, qf[u >> 1][u & 1]);
        __syncwarp();
        issue_pq(p, qf, P.dw);
        wg_wait<0>();
#pragma unroll
        for (int h = 0; h < 4; h++) pin(p[h]);
        if (tw == 0) TS(40);
      }

      __nv_bfloat16* og = g_o + (size_t)(bi * 128 + rowl) * kD + bj * 128 + t * 8;
      uint32_t own = sb + 3 * STAGE + rowl * 128 + ((t ^ g) << 4);
#pragma unroll 1
      for (int pr = 0; pr < 2; pr++) {
        if (pr | wg) top = exp_frags(p[1], ef[1], exp_frags(p[0], ef[0], EXP_TOP));
        if (__builtin_expect(__any_sync(0xffffffffu, top != EXP_TOP), 0)) {
#pragma unroll 1
          for (int u = 0; u < 4; u++) {
            float e[16];
            exp_shifted(p[0], (u & 1) ? -1.f : 1.f, e);
#pragma unroll
            for (int r = 0; r < 4; r++) {
#pragma unroll
              for (int s = 0; s < 6; s++) ef[s >> 2][s & 3][r] = ef[(s + 2) >> 2][(s + 2) & 3][r];
              ef[1][2][r] = pack2(e[2 * r], e[2 * r + 1]);
              ef[1][3][r] = pack2(e[8 + 2 * r], e[8 + 2 * r + 1]);
            }
            if (u & 1) {
#pragma unroll
              for (int e2 = 0; e2 < 16; e2++) p[0][e2] = p[1][e2];
            }
          }
        }
        float np[2][20], nm[2][20];
        mbar_wait(bars + (B_KV + pr) * 8, 0, budget);
        wg_fence();
#pragma unroll
        for (int hh = 0; hh < 2; hh++) {
          const uint64_t dk = P.dv - (uint64_t)pr * ((256ull << 16) - 512ull) - hh * ((255ull << 16) - 256ull);
          wgmma_m64n40k16_rs<1>(np[hh], ef[hh][0], dk, 0);
          wgmma_m64n40k16_rs<1>(np[hh], ef[hh][1], dk + 64, 1);
          wgmma_m64n40k16_rs<1>(nm[hh], ef[hh][2], dk + 128, 0);
          wgmma_m64n40k16_rs<1>(nm[hh], ef[hh][3], dk + 192, 1);
          wg_commit();
        }
#pragma unroll
        for (int e = 0; e < 16; e++) { p[0][e] = p[2][e]; p[1][e] = p[3][e]; }
        pin(p[0]); pin(p[1]);
#pragma unroll
        for (int hh = 0; hh < 2; hh++) {
          if (hh == 0) wg_wait<1>(); else wg_wait<0>();
          pin(np[hh]); pin(nm[hh]);
          uint32_t o[2][4];
#pragma unroll
          for (int r = 0; r < 2; r++) {
            const float dp = np[hh][16 + 2 * r], sp = np[hh][17 + 2 * r], dm = nm[hh][16 + 2 * r], sm = nm[hh][17 + 2 * r];
            const float inv = (r == 0 ? gA : gB) * rcp(fmaf(dp, sm, fmaf(1e-6f, sm, dm) * sp));
            const float cp = sm * inv, cm = sp * inv;
#pragma unroll
            for (int c = 0; c < 4; c++)
              o[r][c] = pack2(fmaf(np[hh][4 * c + 2 * r], cp, nm[hh][4 * c + 2 * r] * cm), fmaf(np[hh][4 * c + 2 * r + 1], cp, nm[hh][4 * c + 2 * r + 1] * cm));
            sts128((own ^ (hh * 64)) + r * 1024, o[r][0], o[r][1], o[r][2], o[r][3]);
          }
          if (hh == 1 && pr == 1) fence_async_smem();
#pragma unroll
          for (int r = 0; r < 2; r++) *reinterpret_cast<uint4*>(og + r * 8 * kD + hh * 32) = make_uint4(o[r][0], o[r][1], o[r][2], o[r][3]);
        }
        warp_arrive(bars + (B_PUB + wg * 2 + pr) * 8, lane);
        if (tw == 0) TS(25 + pr + wg * 16);
        og += 64; own += STAGE;
      }
    }
    bar_sync(7 + wg, 128);

    float oacc[64];
    {
      const uint64_t dam = P.da + wg * 512;
      uint32_t slot = 3, ph = 1, prev = 0;
#pragma unroll 1
      for (int s = 0; s < 16; s++) {
        if (tid == 0) KS(128 + 48 + s);
        mbar_wait(bars + B_FX * 8 + slot * 8, ph, budget);
        if (s >= 2) mbar_wait(bars + (B_FY + wg * NST) * 8 + slot * 8, ph, budget);
        if (tid == 0) KS(48 + s);
        if (tid == 128) KS(192 + 48 + s);
        kstep64(oacc, dam + slot * (STAGE >> 4), P.db + slot * (STAGE >> 4), s);
        wg_wait<1>();
        if (s != 0 && s != 2 && lane0) mbar_arrive(bars + B_EM * 8 + prev * 8);
        if (s == 1) {
          wg_wait<0>();
          if (lane0) mbar_arrive(bars + B_EM * 8 + slot * 8);
        }
        prev = slot;
        if (++slot == NST) { slot = 0; ph ^= 1; }
      }
    }
    mbar_wait(bars + B_XT * 8, 0, budget);
    if ((lds32(sb + SM_MISC + 4) >> 7) == (uint32_t)bi) mbar_wait(bars + B_XP * 8, 0, budget);
    const uint32_t sx = sb + SM_PHI + (wg * 64 + w * 16 + (lane & 15)) * 128 + (((lane >> 4) ^ (lane & 7)) << 4);
    float xf[64];
#pragma unroll
    for (int u = 0; u < 8; u++) {
      uint32_t xr[4];
      ldmatrix4((sx ^ ((u & 3) * 32)) + (u >> 2) * 16384, xr);
#pragma unroll
      for (int r = 0; r < 4; r++) { xf[8 * u + 2 * r] = bf_lo(xr[r]); xf[8 * u + 2 * r + 1] = bf_hi(xr[r]); }
    }
    pin(xf);
    const float hA = 1.0f - gA, hB = 1.0f - gB;
    wg_wait<0>();
    pin(oacc);
    if (tw == 0) TS(29 + wg * 16);
#pragma unroll
    for (int hf = 0; hf < 2; hf++) {
#pragma unroll
      for (int u = hf * 4; u < hf * 4 + 4; u++) {
        const float* a = &oacc[8 * u];
        const float* b = &xf[8 * u];
        stmatrix4((sx ^ ((u & 3) * 32)) + hf * 16384,
                  pack2(fmaf(hA, b[0], a[0]), fmaf(hA, b[1], a[1])), pack2(fmaf(hB, b[2], a[2]), fmaf(hB, b[3], a[3])),
                  pack2(fmaf(hA, b[4], a[4]), fmaf(hA, b[5], a[5])), pack2(fmaf(hB, b[6], a[6]), fmaf(hB, b[7], a[7])));
      }
      fence_async_smem();
      __syncwarp();
      if (elect_one()) tma_store(&mout, sb + SM_PHI + hf * 16384 + warp * 2048, bj * 128 + hf * 64, bi * 128 + warp * 16);
    }
    if (elect_one()) {
      asm volatile("cp.async.bulk.commit_group;" ::: "memory");
      asm volatile("cp.async.bulk.wait_group.read 0;" ::: "memory");
    }
  } else {
    asm volatile("setmaxnreg.dec.sync.aligned.u32 32;");
    if (warp == 8) {
      if (elect_one()) {
        TS(7);
#pragma unroll
        for (int s = 0; s < NST; s++) mbar_init(bars + (B_FX + s) * 8, 1);
        asm volatile("fence.mbarrier_init.release.cluster;" ::: "memory");
        fence_async_smem();
      }
      __syncwarp();
      bar_arrive(0, 512);
      if (elect_one()) {
#pragma unroll 1
        for (int n = 0; n < NST; n++) {
          const uint32_t st = sb + n * STAGE, fb = bars + (B_FX + n) * 8;
          KS(64 + n);
          mbar_expect_tx(fb, STAGE);
          tma_load(st, &mx, fb, n * 64, bi * 128);
          tma_load(st + 16384, &mw, fb, 1024 + bj * 128, n * 64);
          tma_load(st + 24576, &mw, fb, 2048 + bj * 128, n * 64);
        }
      }
      __syncwarp();
      bar_sync(10, 64);
    } else {
      if (warp == 9) {
        if (elect_one()) {
#pragma unroll
          for (int s = B_FY; s < B_NUM; s++) mbar_init(bars + s * 8, s < B_WPHI ? 1 : s < B_EM ? 4 : 8);
          asm volatile("fence.mbarrier_init.release.cluster;" ::: "memory");
          fence_async_smem();
        }
        __syncwarp();
        bar_arrive(10, 64);
      }
      bar_sync(0, 512);
    }
    if (!elect_one()) return;
    if (warp == 8) {
      uint32_t slot = 0, ph = 0;
#pragma unroll 1
      for (int n = NST; n < 48; n++) {
        const int t = n >> 4, k = n & 15;
        const int c0 = t == 2 ? bj * 128 : 1024 + bj * 128 + t * 64, c1 = t == 2 ? c0 + 64 : c0 + 1024;
        const uint32_t st = sb + slot * STAGE, fb = bars + (B_FX + slot) * 8;
        if (n <= NST + 3 * RSTEP && (n - NST) % RSTEP == 0) {
          const int c = (n - NST) / RSTEP;
          mbar_expect_tx(bars + (B_RX + c) * 8, c == 0 ? 8192 + 4096 : 8192);
          tma_load(sb + SM_PHI + c * 8192, &mxr, bars + (B_RX + c) * 8, c * 256, bi * 128 + bj * 16);
          if (c == 0) { bulk_load(sb + SM_V, P.w_r, 2048, bars + B_RX * 8); bulk_load(sb + SM_V + 2048, P.gate_w, 2048, bars + B_RX * 8); }
        }
        mbar_wait(bars + (B_EM + slot) * 8, ph, budget);
        KS(64 + n);
        mbar_expect_tx(fb, STAGE);
        tma_load(st, &mx, fb, k * 64, bi * 128);
        tma_load(st + 16384, &mw, fb, c0, k * 64);
        tma_load(st + 24576, &mw, fb, c1, k * 64);
        {
          const int m = n + WLEAD, tm = m >> 4;
          if ((m & 3) == (bi & 3)) {
            const int d0 = tm >= 2 ? bj * 128 : 1024 + bj * 128 + tm * 64, d1 = tm >= 2 ? d0 + 64 : d0 + 1024;
            tma_prefetch(tm == 3 ? &mwo : &mw, d0, (m & 15) * 64); tma_prefetch(tm == 3 ? &mwo : &mw, d1, (m & 15) * 64);
          }
        }
        if (++slot == NST) { slot = 0; ph ^= 1; }
      }
#pragma unroll 1
      for (int m = WLEAD + ((bi - WLEAD) & 3); m < 16; m += 4) { tma_prefetch(&mwo, bj * 128, m * 64); tma_prefetch(&mwo, bj * 128 + 64, m * 64); }
#pragma unroll 1
      for (int s = 0; s < 16; s++) {
        const int p = s < 2 ? s : (s >= 9), q = s < 9 ? s - 2 : s - 9;
        const int k0 = (s < 2 ? bj : q + (q >= bj)) * 128 + p * 64;
        const uint32_t st = sb + slot * STAGE, fb = bars + (B_FX + slot) * 8;
        mbar_wait(bars + (B_EM + slot) * 8, ph, budget);
        KS(64 + 48 + s);
        mbar_expect_tx(fb, 16384);
        tma_load(st + 16384, &mwo, fb, bj * 128, k0);
        tma_load(st + 24576, &mwo, fb, bj * 128 + 64, k0);
        if (++slot == NST) { slot = 0; ph ^= 1; }
      }
      mbar_wait(bars + B_MD * 8, 0, budget);
      mbar_expect_tx(bars + B_XT * 8, 32768);
      tma_load(sb + SM_PHI, &mx, bars + B_XT * 8, bj * 128, bi * 128);
      tma_load(sb + SM_PHI + 16384, &mx, bars + B_XT * 8, bj * 128 + 64, bi * 128);
    } else if (warp == 9) {
      prefetch_map(&mo); prefetch_map(&mout);
      sts32(sb + SM_MISC, (atomicAdd(&g_cnt[C_START], 1u) & ~255u) + 256u);
      mbar_arrive(bars + B_EPOCH * 8);
      const CUtensorMap* m = (cta & 8) ? &mu : &mg;
      const int l0 = (cta >> 4) * 14, a0 = (cta & 7) * 64, d1 = (cta >> 2) * 112 - 14 * 16, d2 = (cta & 3) * 4;
      uint32_t buf = 0, ph = 0;
#pragma unroll 1
      for (int c = 0; c < 21; c++) {
        const uint32_t dst = sb + moe_buf(buf), fb = bars + (B_MF + buf) * 8;
        mbar_wait(bars + (B_ME + buf) * 8, ph, budget);
        mbar_expect_tx(fb, 8192);
        if (c < 14) tma_load(dst, m, fb, a0 + ((l0 + c) >> 4) * 512, ((l0 + c) & 15) * 64); else tma_load3(dst, &md, fb, d1 + c * 16, d2);
        if (c == 16) {
#pragma unroll 1
          for (int f = 17; f < 21; f++) { __nanosleep(MGAP); tma_prefetch3(&md, d1 + f * 16, d2); }
        }
        if (c < 2) __nanosleep(MGAP);
        if (++buf == 3) { buf = 0; ph ^= 1; }
      }
#pragma unroll 1
      for (int u = 0; u < 2; u++) {
        mbar_wait(bars + (B_PUB + u * 2 + 1) * 8, 0, budget);
        signal_add(&g_cnt[(C_O + bi * 4 + u * 2 + 1) * 32], 32u);
        TS(57 + u * 2);
      }
    } else {
      const int u = warp - 10, hp = bj * 2 + u;
      mbar_wait(bars + B_EPOCH * 8, 0, budget);
      const uint32_t target = lds32(sb + SM_MISC);
#pragma unroll 1
      for (int e = u * 2; e < 4; e += (e == 1) + 1) {
        uint32_t* cnt = &g_cnt[(e < 3 ? C_KV + bj * 4 + e : C_O + bi * 4 + u * 2) * 32];
        mbar_wait(bars + (e < 3 ? B_RED + e : B_PUB + u * 2) * 8, 0, budget);
        signal_add(cnt, e < 3 ? 16u : 32u);
        TS(e < 3 ? 60 + e : 56 + u * 2);
        if (e == 0) __nanosleep(1000);
        if (e == 2) mbar_wait(bars + B_MD * 8, 0, budget);
        wait_count<POLLF>(cnt, target, budget);
        fence_async_global();
        if (e < 2) mbar_arrive(bars + (B_H1 + e) * 8);
        if (e == u + 1) {
          mbar_expect_tx(bars + (B_KV + u) * 8, 12288);
          bulk_load(sb + SM_V + u * 8192, &g_kvr[hp * 3072], 8192, bars + (B_KV + u) * 8);
          bulk_load(sb + SM_Z + u * 4096, &g_kvr[hp * 3072 + 2048], 4096, bars + (B_KV + u) * 8);
          TS(38 + u);
        }
      }
      TS(2 + u * 2);
      if (u == 0) mbar_wait(bars + B_QS * 8, 0, budget);
      uint32_t slot = 0, ph = 1;
#pragma unroll 1
      for (int s = 2; s < 16; s++) {
        const int p = s >= 9, q = s < 9 ? s - 2 : s - 9;
        if (s == 9) { wait_count<POLLF>(&g_cnt[(C_O + bi * 4 + u * 2 + 1) * 32], target, budget); fence_async_global(); TS(3 + u * 2); }
        const uint32_t fb = bars + (B_FY + u * NST + slot) * 8;
        mbar_wait(bars + (B_EM + slot) * 8, ph, budget);
        mbar_expect_tx(fb, 8192);
        tma_load(sb + slot * STAGE + u * 8192, &mo, fb, (q + (q >= bj)) * 128 + p * 64, bi * 128 + u * 64);
        if (++slot == NST) { slot = 0; ph ^= 1; }
      }
    }
  }
}

typedef CUresult (*EncodeFn)(CUtensorMap*, CUtensorMapDataType, cuuint32_t, void*, const cuuint64_t*, const cuuint64_t*, const cuuint32_t*,
                             const cuuint32_t*, CUtensorMapInterleave, CUtensorMapSwizzle, CUtensorMapL2promotion, CUtensorMapFloatOOBfill);

void make_map(EncodeFn enc, CUtensorMap* m, const void* ptr, uint64_t cols, uint64_t rows, uint32_t bc, uint32_t br, CUtensorMapSwizzle swz) {
  const cuuint64_t dims[2] = {cols, rows}, strides[1] = {cols * 2};
  const cuuint32_t box[2] = {bc, br}, es[2] = {1, 1};
  enc(m, CU_TENSOR_MAP_DATA_TYPE_BFLOAT16, 2, const_cast<void*>(ptr), dims, strides, box, es, CU_TENSOR_MAP_INTERLEAVE_NONE, swz,
      CU_TENSOR_MAP_L2_PROMOTION_L2_128B, CU_TENSOR_MAP_FLOAT_OOB_FILL_NONE);
}

}

extern "C" void kernel_launch(void* const* d_in, const int* in_sizes, int n_in, void* d_out, int out_size) {
  (void)in_sizes; (void)n_in; (void)out_size;
  void* fn = nullptr;
  cudaDriverEntryPointQueryResult qr;
  cudaGetDriverEntryPoint("cuTensorMapEncodeTiled", &fn, cudaEnableDefault, &qr);
  EncodeFn enc = (EncodeFn)fn;
  void* o_ptr = nullptr;
  cudaGetSymbolAddress(&o_ptr, g_o);
  CUtensorMap mx, mw, mwo, mo, mout, mxr, mg, mu, md;
  make_map(enc, &mx, d_in[0], kD, kS, 64, 128, CU_TENSOR_MAP_SWIZZLE_128B);
  make_map(enc, &mxr, d_in[0], kD, kS, 256, 16, CU_TENSOR_MAP_SWIZZLE_NONE);
  make_map(enc, &mw, d_in[1], 3 * kD, kD, 64, 64, CU_TENSOR_MAP_SWIZZLE_128B);
  make_map(enc, &mwo, d_in[3], kD, kD, 64, 64, CU_TENSOR_MAP_SWIZZLE_128B);
  make_map(enc, &mo, o_ptr, kD, kS, 64, 64, CU_TENSOR_MAP_SWIZZLE_128B);
  make_map(enc, &mout, d_out, kD, kS, 64, 16, CU_TENSOR_MAP_SWIZZLE_128B);
  make_map(enc, &mg, d_in[6], kF, kD, 64, 64, CU_TENSOR_MAP_SWIZZLE_128B);
  make_map(enc, &mu, d_in[7], kF, kD, 64, 64, CU_TENSOR_MAP_SWIZZLE_128B);
  {
    const cuuint64_t dims[3] = {64, kF, 16}, strides[2] = {kD * 2, 128};
    const cuuint32_t box[3] = {64, 16, 4}, es[3] = {1, 1, 1};
    enc(&md, CU_TENSOR_MAP_DATA_TYPE_BFLOAT16, 3, d_in[8], dims, strides, box, es, CU_TENSOR_MAP_INTERLEAVE_NONE, CU_TENSOR_MAP_SWIZZLE_128B,
        CU_TENSOR_MAP_L2_PROMOTION_L2_128B, CU_TENSOR_MAP_FLOAT_OOB_FILL_NONE);
  }
  Params P;
  P.x = (const __nv_bfloat16*)d_in[0];
  P.w = (const __nv_bfloat16*)d_in[1];
  P.w_phi = (const __nv_bfloat16*)d_in[2];
  P.w_r = (const __nv_bfloat16*)d_in[5];
  P.gate_w = (const __nv_bfloat16*)d_in[9];
  P.da = make_desc(sb, 16, 1024, 1);
  P.db = make_desc(sb + 16384, 8192, 1024, 1);
  P.dw = make_desc(sb + SM_WPHI, 16, 512, 2);
  P.dphi = make_desc(sb + SM_PHI, 16, 1024, 1);
  P.dv = make_desc(sb + SM_V, SM_Z - SM_V, 512, 2);
  P.dband = make_desc(sb + SM_BAND, 128, 128, 0);
  P.dxs = make_desc(sb + SM_BAND, 16, 128, 0);
  int dev = 0, sms = 0;
  cudaGetDevice(&dev);
  cudaDeviceGetAttribute(&sms, cudaDevAttrMultiProcessorCount, dev);
  auto kern = sms == 132 ? fused_kernel<true> : fused_kernel<false>;
  cudaFuncSetAttribute(kern, cudaFuncAttributeMaxDynamicSharedMemorySize, SM_ALLOC);
  kern<<<132, 512, SM_ALLOC, cudaStreamPerThread>>>(mx, mw, mwo, mo, mout, mxr, mg, mu, md, P);
}
```

```cpp
#include <cuda_runtime.h>
#include <cuda_bf16.h>
#include <cuda.h>
#include <stdint.h>

namespace {

template<int TA, int TB> __device__ __forceinline__ void wgmma_m64n128k16_ss(float (&d)[64], uint64_t da, uint64_t db, int scale_d) {
  asm volatile("{\n.reg .pred p;\nsetp.ne.b32 p, %66, 0;\n"
    "wgmma.mma_async.sync.aligned.m64n128k16.f32.bf16.bf16 "
    "{%0, %1, %2, %3, %4, %5, %6, %7, %8, %9, %10, %11, %12, %13, %14, %15, "
    "%16, %17, %18, %19, %20, %21, %22, %23, %24, %25, %26, %27, %28, %29, %30, %31, "
    "%32, %33, %34, %35, %36, %37, %38, %39, %40, %41, %42, %43, %44, %45, %46, %47, "
    "%48, %49, %50, %51, %52, %53, %54, %55, %56, %57, %58, %59, %60, %61, %62, %63}, "
    "%64, %65, p, 1, 1, %67, %68;\n}\n"
    : "+f"(d[0]), "+f"(d[1]), "+f"(d[2]), "+f"(d[3]), "+f"(d[4]), "+f"(d[5]), "+f"(d[6]), "+f"(d[7]),
      "+f"(d[8]), "+f"(d[9]), "+f"(d[10]), "+f"(d[11]), "+f"(d[12]), "+f"(d[13]), "+f"(d[14]), "+f"(d[15]),
      "+f"(d[16]), "+f"(d[17]), "+f"(d[18]), "+f"(d[19]), "+f"(d[20]), "+f"(d[21]), "+f"(d[22]), "+f"(d[23]),
      "+f"(d[24]), "+f"(d[25]), "+f"(d[26]), "+f"(d[27]), "+f"(d[28]), "+f"(d[29]), "+f"(d[30]), "+f"(d[31]),
      "+f"(d[32]), "+f"(d[33]), "+f"(d[34]), "+f"(d[35]), "+f"(d[36]), "+f"(d[37]), "+f"(d[38]), "+f"(d[39]),
      "+f"(d[40]), "+f"(d[41]), "+f"(d[42]), "+f"(d[43]), "+f"(d[44]), "+f"(d[45]), "+f"(d[46]), "+f"(d[47]),
      "+f"(d[48]), "+f"(d[49]), "+f"(d[50]), "+f"(d[51]), "+f"(d[52]), "+f"(d[53]), "+f"(d[54]), "+f"(d[55]),
      "+f"(d[56]), "+f"(d[57]), "+f"(d[58]), "+f"(d[59]), "+f"(d[60]), "+f"(d[61]), "+f"(d[62]), "+f"(d[63])
    : "l"(da), "l"(db), "r"(scale_d), "n"(TA), "n"(TB));
}

template<int TB> __device__ __forceinline__ void wgmma_m64n32k16_rs(float (&d)[16], const uint32_t (&a)[4], uint64_t db, int scale_d) {
  asm volatile("{\n.reg .pred p;\nsetp.ne.b32 p, %21, 0;\n"
    "wgmma.mma_async.sync.aligned.m64n32k16.f32.bf16.bf16 "
    "{%0, %1, %2, %3, %4, %5, %6, %7, %8, %9, %10, %11, %12, %13, %14, %15}, "
    "{%16, %17, %18, %19}, %20, p, 1, 1, %22;\n}\n"
    : "+f"(d[0]), "+f"(d[1]), "+f"(d[2]), "+f"(d[3]), "+f"(d[4]), "+f"(d[5]), "+f"(d[6]), "+f"(d[7]),
      "+f"(d[8]), "+f"(d[9]), "+f"(d[10]), "+f"(d[11]), "+f"(d[12]), "+f"(d[13]), "+f"(d[14]), "+f"(d[15])
    : "r"(a[0]), "r"(a[1]), "r"(a[2]), "r"(a[3]), "l"(db), "r"(scale_d), "n"(TB));
}

template<int TA, int TB> __device__ __forceinline__ void wgmma_m64n40k16_ss(float (&d)[20], uint64_t da, uint64_t db, int scale_d) {
  asm volatile("{\n.reg .pred p;\nsetp.ne.b32 p, %22, 0;\n"
    "wgmma.mma_async.sync.aligned.m64n40k16.f32.bf16.bf16 "
    "{%0, %1, %2, %3, %4, %5, %6, %7, %8, %9, %10, %11, %12, %13, %14, %15, "
    "%16, %17, %18, %19}, "
    "%20, %21, p, 1, 1, %23, %24;\n}\n"
    : "+f"(d[0]), "+f"(d[1]), "+f"(d[2]), "+f"(d[3]), "+f"(d[4]), "+f"(d[5]), "+f"(d[6]), "+f"(d[7]),
      "+f"(d[8]), "+f"(d[9]), "+f"(d[10]), "+f"(d[11]), "+f"(d[12]), "+f"(d[13]), "+f"(d[14]), "+f"(d[15]),
      "+f"(d[16]), "+f"(d[17]), "+f"(d[18]), "+f"(d[19])
    : "l"(da), "l"(db), "r"(scale_d), "n"(TA), "n"(TB));
}

template<int TB> __device__ __forceinline__ void wgmma_m64n40k16_rs(float (&d)[20], const uint32_t (&a)[4], uint64_t db, int scale_d) {
  asm volatile("{\n.reg .pred p;\nsetp.ne.b32 p, %25, 0;\n"
    "wgmma.mma_async.sync.aligned.m64n40k16.f32.bf16.bf16 "
    "{%0, %1, %2, %3, %4, %5, %6, %7, %8, %9, %10, %11, %12, %13, %14, %15, "
    "%16, %17, %18, %19}, "
    "{%20, %21, %22, %23}, %24, p, 1, 1, %26;\n}\n"
    : "+f"(d[0]), "+f"(d[1]), "+f"(d[2]), "+f"(d[3]), "+f"(d[4]), "+f"(d[5]), "+f"(d[6]), "+f"(d[7]),
      "+f"(d[8]), "+f"(d[9]), "+f"(d[10]), "+f"(d[11]), "+f"(d[12]), "+f"(d[13]), "+f"(d[14]), "+f"(d[15]),
      "+f"(d[16]), "+f"(d[17]), "+f"(d[18]), "+f"(d[19])
    : "r"(a[0]), "r"(a[1]), "r"(a[2]), "r"(a[3]), "l"(db), "r"(scale_d), "n"(TB));
}

template<int TA, int TB> __device__ __forceinline__ void wgmma_m64n8k16_ss(float (&d)[4], uint64_t da, uint64_t db, int scale_d) {
  asm volatile("{\n.reg .pred p;\nsetp.ne.b32 p, %6, 0;\n"
    "wgmma.mma_async.sync.aligned.m64n8k16.f32.bf16.bf16 "
    "{%0, %1, %2, %3}, "
    "%4, %5, p, 1, 1, %7, %8;\n}\n"
    : "+f"(d[0]), "+f"(d[1]), "+f"(d[2]), "+f"(d[3])
    : "l"(da), "l"(db), "r"(scale_d), "n"(TA), "n"(TB));
}

constexpr int kS = 2048, kD = 1024, kF = 3584;
constexpr int NST = 5, STAGE = 32768;
constexpr uint32_t sb = 1024;
constexpr int SM_V    = NST * STAGE;
constexpr int SM_Z    = SM_V + 16384;
constexpr int SM_PHI  = SM_Z + 4096;
constexpr int SM_MOE  = SM_PHI + 16384;
constexpr int SM_WPHI = SM_MOE + 16384;
constexpr int SM_BAND = SM_WPHI + 8192;
constexpr int SM_G    = SM_BAND + 2176;
constexpr int SM_BAR  = SM_G + 512;
constexpr int SM_MISC = SM_BAR + 448;
constexpr int SM_TOTAL = SM_MISC + 64;
static_assert(SM_TOTAL <= 232448, "smem");
constexpr uint32_t bars = sb + SM_BAR;
constexpr int B_FX = 0  , B_FY = 5  , B_XT = 15, B_EPOCH = 16, B_RX = 17  , B_MF = 21  , B_RD = 24  , B_KV = 26  , B_M2 = 28;
constexpr int B_WPHI = 29, B_INFO = 30, B_QS = 31, B_XP = 32, B_RED = 33  , B_PUB = 35  , B_ME = 39  , B_MD = 42;
constexpr int B_EM = 43  , B_NUM = 48;
constexpr int C_START = 0, C_O = 1, C_KV = C_O + 64;

__device__ uint2 g_gate[kS];
__device__ uint2 g_key[128];
__device__ uint2 g_pre[4 * kF];
__device__ uint2 g_yp[32 * kD];
__device__ __align__(128) uint32_t g_kvr[16 * 2560];
__device__ __align__(128) uint32_t g_cnt[(C_KV + 32) * 32];
__device__ __align__(1024) __nv_bfloat16 g_o[kS * kD];
#define KS(id)
#define RG(id)
#define TS(id)
#define TSG(id)
constexpr int SM_ALLOC = SM_TOTAL;

#define POLL0 500
#define POLL1 150
#define RSTEP 1
#define POLLR 400
#define EARLY_N 2
#define EARLY_GAP 200
#define POLLF 50
#define RED_CH 10
#define RED_GAP0 250
#define RED_GAP1 0
#define WLEAD 11
#define MGAP 300

struct Params {
  const __nv_bfloat16 *x, *w, *w_phi, *w_r, *gate_w;
  uint64_t da, db, dw, dphi, dv, dband, dxs;
};

__device__ __forceinline__ uint32_t smem_u32(const void* p) { return (uint32_t)__cvta_generic_to_shared(p); }
__device__ __forceinline__ void mbar_init(uint32_t bar, uint32_t cnt) { asm volatile("mbarrier.init.shared::cta.b64 [%0], %1;" :: "r"(bar), "r"(cnt) : "memory"); }
__device__ __forceinline__ void mbar_expect_tx(uint32_t bar, uint32_t bytes) { asm volatile("mbarrier.arrive.expect_tx.shared::cta.b64 _, [%0], %1;" :: "r"(bar), "r"(bytes) : "memory"); }
__device__ __forceinline__ void mbar_arrive(uint32_t bar) { asm volatile("mbarrier.arrive.shared::cta.b64 _, [%0];" :: "r"(bar) : "memory"); }
__device__ __forceinline__ void mbar_arrive_n(uint32_t bar, uint32_t n) { asm volatile("mbarrier.arrive.shared::cta.b64 _, [%0], %1;" :: "r"(bar), "r"(n) : "memory"); }
constexpr int BUDGET = 1 << 20;
__device__ __forceinline__ void mbar_wait(uint32_t bar, uint32_t parity, int& budget) {
  asm volatile("{\n.reg .pred p;\n"
               "WAIT_L:\nmbarrier.try_wait.parity.shared::cta.b64 p, [%1], %2;\n@p bra WAIT_D;\n"
               "add.s32 %0, %0, -1;\nsetp.gt.s32 p, %0, 0;\n@p bra WAIT_L;\nWAIT_D:\n}"
               : "+r"(budget) : "r"(bar), "r"(parity) : "memory");
}
template <int SLEEP>
__device__ __forceinline__ void wait_count(const uint32_t* p, uint32_t target, int& budget) {
  asm volatile("{\n.reg .pred p;\n.reg .s32 v;\n"
               "WAIT_L:\nld.acquire.gpu.global.s32 v, [%1];\nsub.s32 v, v, %2;\nsetp.ge.s32 p, v, 0;\n@p bra WAIT_D;\n"
               "nanosleep.u32 %3;\nadd.s32 %0, %0, -4;\nsetp.gt.s32 p, %0, 0;\n@p bra WAIT_L;\nWAIT_D:\n}"
               : "+r"(budget) : "l"(p), "r"(target), "n"(SLEEP) : "memory");
}
__device__ __forceinline__ void tma_load(uint32_t dst, const CUtensorMap* m, uint32_t bar, int c0, int c1) {
  asm volatile("cp.async.bulk.tensor.2d.shared::cluster.global.mbarrier::complete_tx::bytes [%0], [%1, {%3, %4}], [%2];"
    :: "r"(dst), "l"(m), "r"(bar), "r"(c0), "r"(c1) : "memory");
}
__device__ __forceinline__ void tma_load3(uint32_t dst, const CUtensorMap* m, uint32_t bar, int c1, int c2) {
  asm volatile("cp.async.bulk.tensor.3d.shared::cluster.global.mbarrier::complete_tx::bytes [%0], [%1, {%5, %3, %4}], [%2];"
    :: "r"(dst), "l"(m), "r"(bar), "r"(c1), "r"(c2), "r"(0) : "memory");
}
__device__ __forceinline__ void tma_prefetch3(const CUtensorMap* m, int c1, int c2) {
  asm volatile("cp.async.bulk.prefetch.tensor.3d.L2.global [%0, {%3, %1, %2}];" :: "l"(m), "r"(c1), "r"(c2), "r"(0) : "memory");
}
__device__ __forceinline__ void tma_prefetch(const CUtensorMap* m, int c0, int c1) {
  asm volatile("cp.async.bulk.prefetch.tensor.2d.L2.global [%0, {%1, %2}];" :: "l"(m), "r"(c0), "r"(c1) : "memory");
}
__device__ __forceinline__ void tma_store(const CUtensorMap* m, uint32_t src, int c0, int c1) {
  asm volatile("cp.async.bulk.tensor.2d.global.shared::cta.bulk_group [%0, {%2, %3}], [%1];" :: "l"(m), "r"(src), "r"(c0), "r"(c1) : "memory");
}
__device__ __forceinline__ void bulk_load(uint32_t dst, const void* src, uint32_t bytes, uint32_t bar) {
  asm volatile("cp.async.bulk.shared::cluster.global.mbarrier::complete_tx::bytes [%0], [%1], %2, [%3];" :: "r"(dst), "l"(src), "r"(bytes), "r"(bar) : "memory");
}
__device__ __forceinline__ void bulk_reduce(void* dst, uint32_t src, uint32_t bytes) {
  asm volatile("cp.reduce.async.bulk.global.shared::cta.bulk_group.add.noftz.bf16 [%0], [%1], %2;" :: "l"(dst), "r"(src), "r"(bytes) : "memory");
}
__device__ __forceinline__ void prefetch_map(const CUtensorMap* m) { asm volatile("prefetch.tensormap [%0];" :: "l"(m) : "memory"); }
__device__ __forceinline__ bool elect_one() {
  uint32_t p;
  asm volatile("{\n.reg .pred P;\nelect.sync _|P, 0xffffffff;\nselp.u32 %0, 1, 0, P;\n}" : "=r"(p));
  return p;
}
__device__ __forceinline__ void wg_fence() { asm volatile("wgmma.fence.sync.aligned;" ::: "memory"); }
__device__ __forceinline__ void wg_commit() { asm volatile("wgmma.commit_group.sync.aligned;" ::: "memory"); }
template <int N> __device__ __forceinline__ void wg_wait() { asm volatile("wgmma.wait_group.sync.aligned %0;" :: "n"(N) : "memory"); }
template <int N> __device__ __forceinline__ void zero(float (&r)[N]) {
#pragma unroll
  for (int i = 0; i < N; i++) r[i] = 0.f;
}
template <int N> __device__ __forceinline__ void pin(float (&r)[N]) {
#pragma unroll
  for (int i = 0; i < N; i++) asm volatile("" : "+f"(r[i]) :: "memory");
}
template <int N> __device__ __forceinline__ void pinr(uint32_t (&r)[N][4]) {
#pragma unroll
  for (int i = 0; i < N; i++) asm volatile("" : "+r"(r[i][0]), "+r"(r[i][1]), "+r"(r[i][2]), "+r"(r[i][3]) :: "memory");
}
__device__ __forceinline__ void fence_async_smem() { asm volatile("fence.proxy.async.shared::cta;" ::: "memory"); }
__device__ __forceinline__ void fence_async_global() { asm volatile("fence.proxy.async.global;" ::: "memory"); }
__device__ __forceinline__ void bar_sync(int id, int n) { asm volatile("bar.sync %0, %1;" :: "r"(id), "r"(n) : "memory"); }
__device__ __forceinline__ void bar_arrive(int id, int n) { asm volatile("bar.arrive %0, %1;" :: "r"(id), "r"(n) : "memory"); }
__device__ __forceinline__ void warp_arrive(uint32_t bar, int lane) { __syncwarp(); if (lane == 0) mbar_arrive(bar); }
__host__ __device__ constexpr uint64_t make_desc(uint32_t addr, uint32_t lbo, uint32_t sbo, uint32_t swz) {
  return (uint64_t)((addr & 0x3FFFF) >> 4) | ((uint64_t)((lbo & 0x3FFFF) >> 4) << 16) | ((uint64_t)(sbo >> 4) << 32) | ((uint64_t)swz << 62);
}
__device__ __forceinline__ uint32_t pack2(float lo, float hi) {
  uint32_t r; asm("cvt.rn.bf16x2.f32 %0, %1, %2;" : "=r"(r) : "f"(hi), "f"(lo)); return r;
}
__device__ __forceinline__ float bf_lo(uint32_t v) { return __uint_as_float(v << 16); }
__device__ __forceinline__ float bf_hi(uint32_t v) { return __uint_as_float(v & 0xffff0000u); }
__device__ __forceinline__ float ex2(float x) { float r; asm("ex2.approx.ftz.f32 %0, %1;" : "=f"(r) : "f"(x)); return r; }
__device__ __forceinline__ float rcp(float x) { float r; asm("rcp.approx.ftz.f32 %0, %1;" : "=f"(r) : "f"(x)); return r; }
constexpr float LOG2E = 1.4426950408889634f;
__device__ __forceinline__ float sigmoidf(float x) { return rcp(1.0f + ex2(-LOG2E * x)); }
__device__ __forceinline__ void sts128(uint32_t a, uint32_t x, uint32_t y, uint32_t z, uint32_t w) {
  asm volatile("st.shared.v4.u32 [%0], {%1,%2,%3,%4};" :: "r"(a), "r"(x), "r"(y), "r"(z), "r"(w) : "memory");
}
__device__ __forceinline__ void lds128(uint32_t a, uint32_t (&r)[4]) {
  asm volatile("ld.shared.v4.u32 {%0,%1,%2,%3}, [%4];" : "=r"(r[0]), "=r"(r[1]), "=r"(r[2]), "=r"(r[3]) : "r"(a) : "memory");
}
__device__ __forceinline__ void sts32(uint32_t a, uint32_t v) { asm volatile("st.shared.u32 [%0], %1;" :: "r"(a), "r"(v) : "memory"); }
__device__ __forceinline__ uint32_t lds32(uint32_t a) { uint32_t v; asm volatile("ld.shared.u32 %0, [%1];" : "=r"(v) : "r"(a) : "memory"); return v; }
__device__ __forceinline__ float ldsf(uint32_t a) { return __uint_as_float(lds32(a)); }
__device__ __forceinline__ void stmatrix4(uint32_t a, uint32_t r0, uint32_t r1, uint32_t r2, uint32_t r3) {
  asm volatile("stmatrix.sync.aligned.m8n8.x4.shared.b16 [%0], {%1,%2,%3,%4};" :: "r"(a), "r"(r0), "r"(r1), "r"(r2), "r"(r3) : "memory");
}
__device__ __forceinline__ void ldmatrix4(uint32_t a, uint32_t (&r)[4]) {
  asm volatile("ldmatrix.sync.aligned.m8n8.x4.shared.b16 {%0,%1,%2,%3}, [%4];" : "=r"(r[0]), "=r"(r[1]), "=r"(r[2]), "=r"(r[3]) : "r"(a) : "memory");
}
__device__ __forceinline__ uint4 ldg_nc(const void* p) {
  uint4 v; asm volatile("ld.global.nc.L1::no_allocate.v4.u32 {%0,%1,%2,%3}, [%4];" : "=r"(v.x), "=r"(v.y), "=r"(v.z), "=r"(v.w) : "l"(p)); return v;
}
__device__ __forceinline__ void st_tagged(uint2* p, uint32_t v, uint32_t tag) {
  asm volatile("{\n.reg .b64 x;\nmov.b64 x, {%1, %2};\nst.relaxed.gpu.global.b64 [%0], x;\n}" :: "l"(p), "r"(v), "r"(tag) : "memory");
}
__device__ __forceinline__ uint2 ld_tagged(const uint2* p) {
  uint2 v; asm volatile("{\n.reg .b64 x;\nld.relaxed.gpu.global.b64 x, [%2];\nmov.b64 {%0, %1}, x;\n}" : "=r"(v.x), "=r"(v.y) : "l"(p) : "memory"); return v;
}
__device__ __forceinline__ void probe(const uint2* p, uint32_t tag, int& budget) {
  do { __nanosleep(POLL0); budget -= 16; } while (!__all_sync(0xffffffffu, ld_tagged(p).y == tag) && budget > 0);
}
template <int STRIDE, int N>
__device__ __forceinline__ void gather(const uint2* p, uint32_t tag, float& s0, float& s1, int& budget) {
  uint32_t pause = 0;
  bool again;
#pragma unroll 1
  do {
    __nanosleep(pause);
    pause = POLL0;
    uint32_t bad = 0;
    s0 = s1 = 0.f;
#pragma unroll
    for (int i = 0; i < N; i++) {
      const uint2 w = ld_tagged(p + i * STRIDE);
      bad |= w.y ^ tag;
      if (i < N / 2) s0 += __uint_as_float(w.x); else s1 += __uint_as_float(w.x);
    }
    budget -= 16;
    again = __any_sync(0xffffffffu, bad != 0) && budget > 0;
  } while (again);
}
__device__ __forceinline__ void sts16(uint32_t a, uint32_t v) { asm volatile("st.shared.u16 [%0], %1;" :: "r"(a), "h"((uint16_t)v) : "memory"); }
__device__ __forceinline__ void signal_add(uint32_t* p, uint32_t v) { asm volatile("red.release.gpu.global.add.u32 [%0], %1;" :: "l"(p), "r"(v) : "memory"); }
__device__ __forceinline__ float qmax(float v) { v = fmaxf(v, __shfl_xor_sync(0xffffffffu, v, 1)); return fmaxf(v, __shfl_xor_sync(0xffffffffu, v, 2)); }
__device__ __forceinline__ float qsum(float v) { v += __shfl_xor_sync(0xffffffffu, v, 1); return v + __shfl_xor_sync(0xffffffffu, v, 2); }
__device__ __forceinline__ float fold(float a, float b, bool hi, int m) { return (hi ? b : a) + __shfl_xor_sync(0xffffffffu, hi ? a : b, m); }

__device__ __forceinline__ void yield_slot() { asm volatile("pmevent 0;" ::: "memory"); }
__device__ __forceinline__ float fma_v(float a, float b, float c) { float r; asm volatile("fma.rn.f32 %0, %1, %2, %3;" : "=f"(r) : "f"(a), "f"(b), "f"(c)); return r; }
constexpr float EXP_LIM_F = 36028797018963968.0f;
constexpr uint32_t EXP_TOP = 0x58805880u;
__device__ __forceinline__ void exp_plain(const float (&p)[16], float (&ep)[16], float (&em)[16]) {
#pragma unroll
  for (int i = 0; i < 16; i++) { ep[i] = ex2(p[i]); em[i] = ex2(-p[i]); }
}
__device__ __forceinline__ void exp_shifted(const float (&p)[16], float sgn, float (&e)[16]) {
#pragma unroll
  for (int i = 0; i < 16; i++) e[i] = sgn * p[i];
#pragma unroll
  for (int o = 0; o < 4; o += 2) {
    const float mx = qmax(fmaxf(fmaxf(fmaxf(e[o], e[o + 1]), fmaxf(e[o + 4], e[o + 5])), fmaxf(fmaxf(e[o + 8], e[o + 9]), fmaxf(e[o + 12], e[o + 13]))));
#pragma unroll
    for (int c = 0; c < 4; c++) { e[4 * c + o] = ex2(e[4 * c + o] - mx); e[4 * c + o + 1] = ex2(e[4 * c + o + 1] - mx); }
  }
}
__device__ __forceinline__ void pack_sums(const float (&e)[16], uint32_t (&pk)[2][4], float (&s)[2]) {
#pragma unroll
  for (int i = 0; i < 8; i++) pk[i >> 2][i & 3] = pack2(e[2 * i], e[2 * i + 1]);
#pragma unroll
  for (int o = 0; o < 4; o += 2) s[o >> 1] = ((e[o] + e[o + 1]) + (e[o + 4] + e[o + 5])) + ((e[o + 8] + e[o + 9]) + (e[o + 12] + e[o + 13]));
}
__device__ __forceinline__ uint32_t rcp2(float s) { const float r = rcp(s); return pack2(r, r); }
__device__ __forceinline__ uint32_t mul2(uint32_t a, uint32_t b) { uint32_t r; asm("mul.rn.bf16x2 %0, %1, %2;" : "=r"(r) : "r"(a), "r"(b)); return r; }
__device__ __forceinline__ void store_phi(uint32_t a, const uint32_t (&pk)[2][4], uint32_t r0, uint32_t r1) {
#pragma unroll
  for (int h = 0; h < 2; h++) stmatrix4(a ^ (h * 32), mul2(pk[h][0], r0), mul2(pk[h][1], r1), mul2(pk[h][2], r0), mul2(pk[h][3], r1));
}
__device__ __forceinline__ uint32_t exp_frags(const float (&p)[16], uint32_t (&ef)[4][4], uint32_t top) {
  float ep[16], em[16];
  exp_plain(p, ep, em);
#pragma unroll
  for (int s = 0; s < 2; s++)
#pragma unroll
    for (int r = 0; r < 4; r++) {
      ef[s][r] = pack2(ep[8 * s + 2 * r], ep[8 * s + 2 * r + 1]);
      ef[2 + s][r] = pack2(em[8 * s + 2 * r], em[8 * s + 2 * r + 1]);
    }
#pragma unroll
  for (int s = 0; s < 4; s++) top = __vimax3_u16x2(__vimax3_u16x2(top, ef[s][0], ef[s][1]), ef[s][2], ef[s][3]);
  return top;
}
__device__ __forceinline__ void issue_pq(float (&p)[4][16], const uint32_t (&qf)[4][2][4], uint64_t dw) {
  wg_fence();
#pragma unroll
  for (int h = 0; h < 4; h++) {
    wgmma_m64n32k16_rs<1>(p[h], qf[h][0], dw + h * 128, 0);
    wgmma_m64n32k16_rs<1>(p[h], qf[h][1], dw + h * 128 + 64, 1);
  }
  wg_commit();
}

#define SPLIT_BATCH 2
__device__ __forceinline__ void mainloop128(float (&acc)[2][64], uint64_t da0, uint64_t db0, uint32_t slot, uint32_t ph, int steps, bool lane0, int& budget, int cta, int n0) {
  uint32_t prev = 0;
#pragma unroll 1
  for (int k = 0; k < steps; k++) {
    mbar_wait(bars + B_FX * 8 + slot * 8, ph, budget);
    const uint64_t da = da0 + slot * (STAGE >> 4), db = db0 + slot * (STAGE >> 4);
#pragma unroll
    for (int kk = 0; kk < 4; kk++) {
      if (SPLIT_BATCH == 2 || !(kk & 1)) {
        wg_wait<1>();
        if (kk == 3 - SPLIT_BATCH && k > 0 && lane0) mbar_arrive_n(bars + B_EM * 8 + prev * 8, 2);
        wg_fence();
      }
      wgmma_m64n128k16_ss<0, 1>(acc[0], da + kk * 2, db + kk * 128, kk ? 1 : k);
      wgmma_m64n128k16_ss<0, 1>(acc[1], da + 512 + kk * 2, db + kk * 128, kk ? 1 : k);
      if (SPLIT_BATCH == 2 || (kk & 1)) wg_commit();
    }
    prev = slot;
    if (++slot == NST) { slot = 0; ph ^= 1; }
  }
}
__device__ __forceinline__ void kstep64(float (&acc)[64], uint64_t da, uint64_t db, int accumulate) {
  wg_fence();
#pragma unroll
  for (int kk = 0; kk < 4; kk++) wgmma_m64n128k16_ss<0, 1>(acc, da + kk * 2, db + kk * 128, kk ? 1 : accumulate);
  wg_commit();
}
__device__ __forceinline__ void issue_kv(float (&kv)[20], uint64_t dphi, uint64_t dv, int accumulate) {
  wg_fence();
#pragma unroll
  for (int ks = 0; ks < 4; ks++)
    wgmma_m64n40k16_ss<1, 1>(kv, dphi + ks * 128, dv - (uint64_t)ks * ((64ull << 16) - 64ull), ks ? 1 : accumulate);
  wg_commit();
}
__device__ __forceinline__ uint32_t moe_buf(uint32_t b) { return b == 2 ? SM_V + 8192 : SM_MOE + b * 8192; }
template <bool DOWN>
__device__ __forceinline__ void moe_chunks(float (&a)[4], int n, uint32_t& buf, uint32_t& ph, uint64_t da0, uint64_t db, bool lane0) {
  int budget = BUDGET;
  zero(a);
#pragma unroll 1
  for (int c = 0; c < n; c++) {
    mbar_wait(bars + B_MF * 8 + buf * 8, ph, budget);
    const uint64_t da = da0 + (moe_buf(buf) >> 4);
    wg_fence();
#pragma unroll
    for (int j = 0; j < 4; j++) wgmma_m64n8k16_ss<1, 0>(a, da + j * 128, DOWN ? db - j : db + j * 2, 1);
    wg_commit();
    wg_wait<0>();
    if (lane0) mbar_arrive(bars + B_ME * 8 + buf * 8);
    db += DOWN ? 16 : 8;
    if (++buf >= (DOWN ? 2 : 3)) { buf = 0; ph ^= 1; }
  }
  pin(a);
}
constexpr uint64_t DV_TILE = 4 * ((64ull << 16) - 64ull);

template <bool BY_SM>
__global__ void __launch_bounds__(512, 1)
fused_kernel(const __grid_constant__ CUtensorMap mx, const __grid_constant__ CUtensorMap mw, const __grid_constant__ CUtensorMap mwo,
             const __grid_constant__ CUtensorMap mo, const __grid_constant__ CUtensorMap mout, const __grid_constant__ CUtensorMap mxr,
             const __grid_constant__ CUtensorMap mg, const __grid_constant__ CUtensorMap mu, const __grid_constant__ CUtensorMap md, const Params P) {
  extern __shared__ __align__(1024) uint8_t smem_raw[];
  if (smem_u32(smem_raw) != sb) return;
  const int tid = threadIdx.x, lane = tid & 31;
  if (tid == 256) TS(1);
  const int warp = __shfl_sync(0xffffffffu, tid >> 5, 0), wg = warp >> 2;
  int budget = BUDGET;
  if (warp == 10 && elect_one()) { prefetch_map(&mx); prefetch_map(&mw); }
  int cta;
  {
    uint32_t smid;
    asm volatile("mov.u32 %0, %%smid;" : "=r"(smid));
    if (!BY_SM) cta = blockIdx.x;
    else if (smid < 64) cta = ((smid >> 1) & 7) * 16 + (smid >> 4) * 2 + (smid & 1);
    else if (smid < 120) { const int t = (smid - 64) >> 1, d = (t * 37) >> 8; cta = (1 + t - d * 7) * 16 + 8 + d * 2 + (smid & 1); }
    else cta = smid < 124 ? smid + 8 : smid - 116;
  }
  if (cta >= 128) {
    if (tid == 0) {
      const uint32_t old = atomicAdd(&g_cnt[C_START], 32u);
      wait_count<500>(&g_cnt[C_START], (old & ~255u) + 256u, budget);
    }
    return;
  }
  const int bi = (cta >> 5) * 4 + ((cta >> 2) & 3);
  const int bj = ((cta >> 4) & 1) * 4 + (cta & 3);

  if (wg == 3) {
    asm volatile("setmaxnreg.dec.sync.aligned.u32 64;");
    const int t3 = tid - 384, w3 = warp - 12;
    if (t3 == 0) TSG(0);
    if (t3 < 80) *reinterpret_cast<uint4*>(&g_kvr[cta * 320 + t3 * 4]) = make_uint4(0, 0, 0, 0);
    if (t3 < 17) st_tagged(t3 < 16 ? &g_gate[bi * 128 + bj * 16 + t3] : &g_key[cta], 0, 1);
    bar_sync(0, 512);
#pragma unroll 1
    for (int u = 0; u < 4; u++) {
      const uint4 v = ldg_nc(P.w_phi + bj * 4096 + (u * 128 + t3) * 8);
      sts128(sb + SM_WPHI + u * 2048 + (t3 >> 2) * 64 + (((t3 & 3) ^ ((t3 >> 3) & 3)) << 4),
             pack2(LOG2E * bf_lo(v.x), LOG2E * bf_hi(v.x)), pack2(LOG2E * bf_lo(v.y), LOG2E * bf_hi(v.y)),
             pack2(LOG2E * bf_lo(v.z), LOG2E * bf_hi(v.z)), pack2(LOG2E * bf_lo(v.w), LOG2E * bf_hi(v.w)));
    }
    fence_async_smem();
    warp_arrive(bars + B_WPHI * 8, lane);
    bar_sync(6, 256);
    const uint32_t target = lds32(sb + SM_MISC);
    uint32_t key;
    {
      uint32_t kk[4];
      lds128(sb + SM_MISC + 16, kk);
      if (t3 == 0) st_tagged(&g_key[cta], max(max(kk[0], kk[1]), max(kk[2], kk[3])), target);
      uint2 k, gv;
      __nanosleep(POLLR);
      do {
        __nanosleep(POLL1);
        k = ld_tagged(&g_key[t3]);
        gv = ld_tagged(&g_gate[bi * 128 + t3]);
        budget -= 4;
      } while (!__all_sync(0xffffffffu, k.y == target && gv.y == target) && budget > 0);
      key = __reduce_max_sync(0xffffffffu, k.x);
      if (lane == 0) sts32(sb + SM_MISC + 32 + w3 * 4, key);
      sts32(sb + SM_G + t3 * 4, gv.x);
      bar_sync(5, 128);
      lds128(sb + SM_MISC + 32, kk);
      key = max(max(kk[0], kk[1]), max(kk[2], kk[3]));
    }
    const int idx = (0xFFFF - (key & 0xFFFF)) & (kS - 1);
    if (t3 == 0) { sts32(sb + SM_MISC + 4, idx); TS(8); }
    warp_arrive(bars + B_INFO * 8, lane);
    {
      const uint4 v = ldg_nc(P.x + (size_t)idx * kD + t3 * 8);
      sts128(sb + SM_BAND + t3 * 16, v.x, v.y, v.z, v.w);
    }
    const int t2 = (lane & 3) * 2, row = w3 * 16 + (lane >> 2);
    float a[4];
    uint32_t buf = 0, ph = 0;
    fence_async_smem();
    bar_sync(5, 128);
    {
      const int r = cta >> 4;
#pragma unroll 1
      for (int part = 0; part < 2; part++) {
        const int n = part ? 14 - 2 * r : 2 * r;
        moe_chunks<false>(a, n, buf, ph, P.da, P.dxs + (part ? 0 : (16 - n) * 8), lane == 0);
        uint2* dst = &g_pre[(((cta >> 2) & 2) + 1 - part) * kF + ((r - 1 + part) * 8 + (cta & 7)) * 64 + row];
        if (t2 == 0 && n) { st_tagged(dst, __float_as_uint(a[0]), target); st_tagged(dst + 8, __float_as_uint(a[2]), target); }
      }
    }
    if (t3 == 0) TS(9);
    bar_sync(5, 128);
    sts128(sb + SM_BAND + t3 * 16, 0, 0, 0, 0);
    {
      __nanosleep(POLL0);
      float gs, us;
      gather<kF, 4>(&g_pre[(cta >> 2) * 112 + min(t3, 111)], target, gs, us, budget);
      bar_sync(5, 128);
      if (t3 < 112) sts16(sb + SM_BAND + 112 + (t3 >> 3) * 128 + (t3 & 7) * 2, pack2(gs * sigmoidf(gs) * us, 0.f));
    }
    fence_async_smem();
    bar_sync(5, 128);
    if (t3 == 0) TS(12);
    moe_chunks<true>(a, 7, buf, ph, P.da, P.dband + 7, lane == 0);
    if (t3 == 0) TS(10);
    if (t2 < 4) {
      uint2* dst = &g_yp[(cta >> 2) * kD + (cta & 3) * 256 + t2 * 64 + row];
      st_tagged(dst, __float_as_uint(a[0]), target); st_tagged(dst + 8, __float_as_uint(a[2]), target);
      st_tagged(dst + 64, __float_as_uint(a[1]), target); st_tagged(dst + 72, __float_as_uint(a[3]), target);
    }
    if (lane == 0) mbar_arrive(bars + B_MD * 8);
    if ((idx >> 7) == bi) {
      mbar_wait(bars + (B_PUB + 3) * 8, 0, budget);
      if (w3 == 0) probe(&g_yp[lane * kD + bj * 128], target, budget);
      bar_sync(5, 128);
      float y = 0.f;
#pragma unroll 1
      for (int hf = 0; hf < 2; hf++) {
        float y0, y1;
        gather<kD, 16>(&g_yp[hf * 16 * kD + bj * 128 + t3], target, y0, y1, budget);
        y += y0 + y1;
      }
      const uint32_t ob = key >> 16;
      const float upd = y * sigmoidf(__uint_as_float(((ob & 0x8000u) ? (ob ^ 0x8000u) : (~ob & 0xFFFFu)) << 16));
      const uint32_t a = sb + SM_PHI + (t3 >> 6) * 16384 + (idx & 127) * 128 + ((((t3 >> 3) & 7) ^ (idx & 7)) << 4) + (t3 & 7) * 2;
      mbar_wait(bars + B_XT * 8, 0, budget);
      uint16_t xb;
      asm volatile("ld.shared.u16 %0, [%1];" : "=h"(xb) : "r"(a) : "memory");
      sts16(a, pack2(bf_lo(xb) + upd, 0.f));
      warp_arrive(bars + B_XP * 8, lane);
      if (t3 == 0) TS(11);
    }
  } else if (wg < 2) {
    if ((warp & 3) < EARLY_N && lane < (wg ? 8 : 16)) {
      const int n = warp & 3;
      const __nv_bfloat16* p = wg ? P.w + (size_t)(n * 64 + bi + (lane >> 1) * 16) * (3 * kD) + 1024 + (lane & 1) * 1024 + bj * 128
                                  : P.x + (size_t)(bi * 128 + bj * 16 + lane) * kD + n * 64;
      if (n) __nanosleep(n * EARLY_GAP);
      asm volatile("prefetch.global.L2 [%0];" :: "l"(p));
    }
    __syncwarp();
    asm volatile("setmaxnreg.inc.sync.aligned.u32 208;");
    const int tw = tid & 127, w = warp & 3, g = lane >> 2, t = lane & 3;
    const bool lane0 = lane == 0;
    if (wg == 0) sts128(sb + SM_Z + (tw & 63) * 16, 0x3f803f80u, 0x3f803f80u, 0x3f803f80u, 0x3f803f80u);
    bar_sync(0, 512);
    if (wg == 1) {
      float sr[4], sg[4];
      zero(sr); zero(sg);
#pragma unroll 1
      for (int c = 0; c < 4; c++) {
        RG(48 + c * 2);
        mbar_wait(bars + (B_RX + c) * 8, 0, budget);
        RG(49 + c * 2);
        uint32_t rs[4], gs[4], xs[4][4];
        lds128(sb + SM_V + c * 512 + lane * 16, rs);
        lds128(sb + SM_V + 2048 + c * 512 + lane * 16, gs);
#pragma unroll
        for (int r = 0; r < 4; r++) lds128(sb + SM_PHI + c * 8192 + (w * 4 + r) * 512 + lane * 16, xs[r]);
#pragma unroll
        for (int e = 0; e < 4; e++) {
          const float r0 = bf_lo(rs[e]), r1 = bf_hi(rs[e]), g0 = bf_lo(gs[e]), g1 = bf_hi(gs[e]);
#pragma unroll
          for (int r = 0; r < 4; r++) {
            const float x0 = bf_lo(xs[r][e]), x1 = bf_hi(xs[r][e]);
            sr[r] = fma_v(x0, r0, sr[r]); sg[r] = fma_v(x0, g0, sg[r]);
            sr[r] = fma_v(x1, r1, sr[r]); sg[r] = fma_v(x1, g1, sg[r]);
            if (r != 1) yield_slot();
          }
        }
      }
      RG(56);
      fence_async_smem();
      __syncwarp();
      if (lane < 3) mbar_arrive(bars + (B_ME + lane) * 8);
      const bool b4 = lane & 16, b3 = lane & 8, b2 = lane & 4;
      const float v = qsum(fold(fold(fold(sr[0], sg[0], b4, 16), fold(sr[2], sg[2], b4, 16), b3, 8),
                                fold(fold(sr[1], sg[1], b4, 16), fold(sr[3], sg[3], b4, 16), b3, 8), b2, 4));
      const int row = bi * 128 + bj * 16 + w * 4 + (g & 3);
      const uint32_t rb = pack2(v + 0.f, 0.f);
      const uint32_t ob = (rb & 0x8000u) ? (~rb & 0xFFFFu) : (rb | 0x8000u);
      const uint32_t best = __reduce_max_sync(0xffffffffu, b4 ? 0u : (ob << 16) | (0xFFFFu - row));
      mbar_wait(bars + B_EPOCH * 8, 0, budget);
      const uint32_t tag = lds32(sb + SM_MISC);
      if (lane0) sts32(sb + SM_MISC + 16 + w * 4, best);
      if (b4 && t == 0) st_tagged(&g_gate[row], __float_as_uint(sigmoidf(v)), tag);
      if (tw == 0) TS(14);
      bar_arrive(6, 256);
      bar_sync(1, 256);
    }

    {
      float acc[2][64];
      if (tw == 0) TS(16 + wg * 16);
      mainloop128(acc, P.da, P.db, wg, wg, 16, lane0, budget, cta, wg * 16);
      bar_sync(1 + wg, 256);
      wg_wait<0>();
      pin(acc[0]); pin(acc[1]);
      if (lane0) mbar_arrive_n(bars + (B_EM + wg) * 8, 2);
      if (tw == 0) TS(17 + wg * 16);
      float p[4][16];
      uint32_t vp[8][4];
      const uint32_t av = sb + SM_V + (w * 16 + g) * 64 + ((t ^ (g >> 1)) << 4);
      {
        uint32_t kf[4][2][4];
#pragma unroll
        for (int u = 0; u < 4; u++)
#pragma unroll
          for (int s = 0; s < 2; s++)
#pragma unroll
            for (int r = 0; r < 4; r++) kf[u][s][r] = pack2(acc[u & 1][16 * (u >> 1) + 8 * s + 2 * r], acc[u & 1][16 * (u >> 1) + 8 * s + 2 * r + 1]);
        mbar_wait(bars + B_WPHI * 8, 0, budget);
        const uint64_t dw = P.dw + wg * 256;
        wg_fence();
#pragma unroll
        for (int u = 0; u < 4; u++) {
          wgmma_m64n32k16_rs<1>(p[u], kf[u][0], dw + (u >> 1) * 128, 0);
          wgmma_m64n32k16_rs<1>(p[u], kf[u][1], dw + (u >> 1) * 128 + 64, 1);
        }
        wg_commit();
#pragma unroll
        for (int u = 0; u < 8; u++) {
          const float* a = &acc[(u >> 1) & 1][32 + 16 * (u >> 2) + 2 * (u & 1)];
          vp[u][0] = pack2(a[0], a[1]); vp[u][1] = pack2(a[4], a[5]); vp[u][2] = pack2(a[8], a[9]); vp[u][3] = pack2(a[12], a[13]);
          if (u < 4) sts128(av + (u >> 1) * 4096 + (u & 1) * 512, vp[u][0], vp[u][1], vp[u][2], vp[u][3]);
        }
        pinr(vp);
        wg_wait<0>();
#pragma unroll
        for (int u = 0; u < 4; u++) pin(p[u]);
      }
      if (tw == 0) TS(18 + wg * 16);
      float kv[2][20];
      if (wg) mbar_wait(bars + B_RD * 8, 0, budget);
      {
        const uint32_t sphi = sb + SM_PHI + (w * 16 + (lane & 15)) * 128 + (((lane >> 4) ^ (lane & 7)) << 4);
        float top = 0.f;
        uint32_t pk[4][2][4];
        float ps[2], sa[4], sc[4];
        uint32_t redo = 0;
#pragma unroll
        for (int i = 0; i < 11; i++) {
          if (i >= 3) {
            const int j = i - 3;
            const float s0 = sc[0] + sc[2], s1 = sc[1] + sc[3];
            top = fmaxf(top, fmaxf(s0, s1));
            store_phi((sphi ^ ((j & 1) * 64)) + (j & 2) * 4096, pk[j & 3], rcp2(s0), rcp2(s1));
          }
          if (i >= 2 && i <= 9) {
            sc[0] = sa[0] + sa[2]; sc[1] = sa[1] + sa[3];
            sc[2] = __shfl_xor_sync(0xffffffffu, sc[0], 2); sc[3] = __shfl_xor_sync(0xffffffffu, sc[1], 2);
          }
          if (i >= 1 && i <= 8) {
            sa[0] = ps[0]; sa[1] = ps[1];
            sa[2] = __shfl_xor_sync(0xffffffffu, sa[0], 1); sa[3] = __shfl_xor_sync(0xffffffffu, sa[1], 1);
          }
          if (i < 8) {
            pin(p[i >> 1]);
            float e[16];
#pragma unroll
            for (int c = 0; c < 16; c++) e[c] = ex2((i & 1) ? -p[i >> 1][c] : p[i >> 1][c]);
            pack_sums(e, pk[i & 3], ps);
            pinr(pk[i & 3]); pin(ps);
          }
          if (i < 10) yield_slot();
          if (i >= 2 && i <= 9) pin(sc);
          if (i >= 1 && i <= 8) pin(sa);
          RG(i * 4);
          if (i >= 4 && !(i & 1)) {
            const int u = (i - 4) >> 1;
            fence_async_smem();
            wg_wait<0>();
            RG(i * 4 + 1);
            if (u < 3) bar_sync(7 + wg, 128);
            else asm volatile("{\n.reg .pred p, q;\nsetp.ne.b32 p, %2, 0;\nbar.red.or.pred q, %1, 128, p;\nselp.u32 %0, 1, 0, q;\n}"
                              : "=r"(redo) : "r"(7 + wg), "r"((uint32_t)!(top < EXP_LIM_F)) : "memory");
            RG(i * 4 + 2);
            issue_kv(kv[u >> 1], P.dphi + (u & 1) * 512, P.dv - (u & 1) * DV_TILE, u & 1);
            if (u == 1 || u == 2) {
#pragma unroll
              for (int r = 0; r < 2; r++) sts128(av + ((u + 1) & 1) * 4096 + r * 512, vp[2 * u + 2 + r][0], vp[2 * u + 2 + r][1], vp[2 * u + 2 + r][2], vp[2 * u + 2 + r][3]);
            }
            if (u < 3) yield_slot();
            RG(i * 4 + 3);
          }
        }
        if (tw == 0) TS(19 + wg * 16);
        wg_wait<0>();
        pin(kv[0]); pin(kv[1]);
        if (__builtin_expect(__any_sync(0xffffffffu, redo), 0)) {
#pragma unroll 1
          for (int u = 0; u < 4; u++) {
            bar_sync(7 + wg, 128);
#pragma unroll 1
            for (int sg = 0; sg < 2; sg++) {
              float e[16];
              exp_shifted(p[0], sg ? -1.f : 1.f, e);
              pack_sums(e, pk[0], ps);
              store_phi(sphi ^ (sg * 64), pk[0], rcp2(qsum(ps[0])), rcp2(qsum(ps[1])));
            }
            sts128(av, vp[0][0], vp[0][1], vp[0][2], vp[0][3]);
            sts128(av + 512, vp[1][0], vp[1][1], vp[1][2], vp[1][3]);
            fence_async_smem();
            bar_sync(7 + wg, 128);
            issue_kv(kv[1], P.dphi, P.dv, u & 1);
            wg_wait<0>();
            pin(kv[1]);
#pragma unroll
            for (int c = 0; c < 16; c++) { p[0][c] = p[1][c]; p[1][c] = p[2][c]; p[2][c] = p[3][c]; }
#pragma unroll
            for (int c = 0; c < 24; c++) vp[c >> 2][c & 3] = vp[(c >> 2) + 2][c & 3];
            if (u == 1) {
#pragma unroll
              for (int c = 0; c < 20; c++) kv[0][c] = kv[1][c];
            }
          }
        }
      }
      if (tw == 0) TS(20 + wg * 16);
      bar_sync(7 + wg, 128);
      {
        const int srow = w * 16 + (lane & 15);
        const uint32_t a0 = sb + SM_PHI + srow * 64 + (((lane >> 4) ^ ((srow >> 1) & 3)) << 4);
#pragma unroll
        for (int q = 0; q < 4; q++) {
          const float* a = &kv[q >> 1][8 * (q & 1)];
          stmatrix4((a0 ^ ((q & 1) * 32)) + (q >> 1) * 4096, pack2(a[0], a[1]), pack2(a[2], a[3]), pack2(a[4], a[5]), pack2(a[6], a[7]));
        }
        const uint32_t z = pack2(t == 0 ? kv[0][16] : t == 1 ? kv[1][16] : t == 2 ? kv[0][18] : kv[1][18], 0.0625f);
        sts128(sb + SM_PHI + 8192 + ((w & 1) * 16 + (t >> 1) * 8 + g) * 64 + ((((w & 2) + (t & 1)) ^ (g >> 1)) << 4), z, z, z, z);
      }
      fence_async_smem();
      warp_arrive(bars + (B_RED + wg) * 8, lane);
      if (tw == 0) TS(51 + wg * 4);
    }

    const uint32_t stash = sb + 3 * STAGE + 8192 + w * 2048 + lane * 16;
    const int rowl = wg * 64 + w * 16 + g;
    mbar_wait(bars + B_INFO * 8, 0, budget);
    const float gA = ldsf(sb + SM_G + rowl * 4), gB = ldsf(sb + SM_G + rowl * 4 + 32);
    {
      float p[4][16];
      uint32_t ef[2][4][4];
      uint32_t top = EXP_TOP;
      if (wg == 0) {
        float acc[2][64];
        bar_sync(2, 256);
        if (tw == 0) TS(22);
        mainloop128(acc, P.da, P.db, 32 % NST, (32 / NST) & 1, 12, lane0, budget, cta, 32);
#pragma unroll 1
        for (int n = 0; n < 4; n++) {
          const uint32_t slot = n ? n - 1 : 4;
          if (tw == 0) KS(128 + 44 + n);
          mbar_wait(bars + B_FX * 8 + slot * 8, n != 0, budget);
          if (tw == 0) KS(44 + n);
          kstep64(acc[0], P.da + slot * (STAGE >> 4), P.db + slot * (STAGE >> 4), 1);
          wg_wait<1>();
          if (n == 0 && lane0) mbar_arrive_n(bars + (B_EM + 43 % NST) * 8, 2);
        }
        kstep64(acc[1], P.da + 512 + (44 % NST) * (STAGE >> 4), P.db + (44 % NST) * (STAGE >> 4), 1);
        wg_wait<1>();
        pin(acc[0]);
        if (tw == 0) TS(15);
        {
          uint32_t qf[4][2][4];
#pragma unroll
          for (int u = 0; u < 8; u++)
#pragma unroll
            for (int r = 0; r < 4; r++) qf[u >> 1][u & 1][r] = pack2(acc[0][8 * u + 2 * r], acc[0][8 * u + 2 * r + 1]);
          issue_pq(p, qf, P.dw);
          kstep64(acc[1], P.da + 512 + (45 % NST) * (STAGE >> 4), P.db + (45 % NST) * (STAGE >> 4), 1);
          wg_wait<1>();
        }
#pragma unroll
        for (int h = 0; h < 4; h++) pin(p[h]);
        if (tw == 0) TS(24);
#pragma unroll
        for (int h = 0; h < 2; h++) {
          if (lane0) mbar_arrive_n(bars + (B_EM + (44 + h) % NST) * 8, 2);
          kstep64(acc[1], P.da + 512 + ((46 + h) % NST) * (STAGE >> 4), P.db + ((46 + h) % NST) * (STAGE >> 4), 1);
          yield_slot();
          pin(p[h]);
          top = exp_frags(p[h], ef[h], top);
          pinr(ef[h]);
          yield_slot();
          if (h == 0) wg_wait<1>(); else wg_wait<0>();
        }
        pin(acc[1]);
        if (lane0) { mbar_arrive_n(bars + (B_EM + 46 % NST) * 8, 2); mbar_arrive_n(bars + (B_EM + 47 % NST) * 8, 2); }
        if (tw == 0) TS(23);
#pragma unroll
        for (int u = 0; u < 8; u++) {
          const float* a = &acc[1][8 * u];
          sts128(stash + (u >> 2) * STAGE + (u & 3) * 512, pack2(a[0], a[1]), pack2(a[2], a[3]), pack2(a[4], a[5]), pack2(a[6], a[7]));
        }
        warp_arrive(bars + B_QS * 8, lane);
      } else {
        uint32_t qf[4][2][4];
        mbar_wait(bars + B_QS * 8, 0, budget);
#pragma unroll
        for (int u = 0; u < 8; u++) lds128(stash + (u >> 2) * STAGE + (u & 3) * 512, qf[u >> 1][u & 1]);
        __syncwarp();
        issue_pq(p, qf, P.dw);
        wg_wait<0>();
#pragma unroll
        for (int h = 0; h < 4; h++) pin(p[h]);
        if (tw == 0) TS(40);
      }

      __nv_bfloat16* og = g_o + (size_t)(bi * 128 + rowl) * kD + bj * 128 + t * 8;
      uint32_t own = sb + 3 * STAGE + rowl * 128 + ((t ^ g) << 4);
#pragma unroll 1
      for (int pr = 0; pr < 2; pr++) {
        if (pr | wg) top = exp_frags(p[1], ef[1], exp_frags(p[0], ef[0], EXP_TOP));
        if (__builtin_expect(__any_sync(0xffffffffu, top != EXP_TOP), 0)) {
#pragma unroll 1
          for (int u = 0; u < 4; u++) {
            float e[16];
            exp_shifted(p[0], (u & 1) ? -1.f : 1.f, e);
#pragma unroll
            for (int r = 0; r < 4; r++) {
#pragma unroll
              for (int s = 0; s < 6; s++) ef[s >> 2][s & 3][r] = ef[(s + 2) >> 2][(s + 2) & 3][r];
              ef[1][2][r] = pack2(e[2 * r], e[2 * r + 1]);
              ef[1][3][r] = pack2(e[8 + 2 * r], e[8 + 2 * r + 1]);
            }
            if (u & 1) {
#pragma unroll
              for (int e2 = 0; e2 < 16; e2++) p[0][e2] = p[1][e2];
            }
          }
        }
        float np[2][20], nm[2][20];
        mbar_wait(bars + (B_KV + pr) * 8, 0, budget);
        wg_fence();
#pragma unroll
        for (int hh = 0; hh < 2; hh++) {
          const uint64_t dk = P.dv - (uint64_t)pr * ((384ull << 16) - 512ull) - hh * ((255ull << 16) - 256ull);
          wgmma_m64n40k16_rs<1>(np[hh], ef[hh][0], dk, 0);
          wgmma_m64n40k16_rs<1>(np[hh], ef[hh][1], dk + 64, 1);
          wgmma_m64n40k16_rs<1>(nm[hh], ef[hh][2], dk + 128 - (126ull << 16), 0);
          wgmma_m64n40k16_rs<1>(nm[hh], ef[hh][3], dk + 192 - (126ull << 16), 1);
          wg_commit();
        }
#pragma unroll
        for (int e = 0; e < 16; e++) { p[0][e] = p[2][e]; p[1][e] = p[3][e]; }
        pin(p[0]); pin(p[1]);
#pragma unroll
        for (int hh = 0; hh < 2; hh++) {
          if (hh == 0) wg_wait<1>(); else wg_wait<0>();
          pin(np[hh]); pin(nm[hh]);
          uint32_t o[2][4];
#pragma unroll
          for (int r = 0; r < 2; r++) {
            const float dp = np[hh][16 + 2 * r], sp = np[hh][17 + 2 * r], dm = nm[hh][16 + 2 * r], sm = nm[hh][17 + 2 * r];
            const float inv = (r == 0 ? gA : gB) * rcp(fmaf(dp, sm, fmaf(1e-6f, sm, dm) * sp));
            const float cp = sm * inv, cm = sp * inv;
#pragma unroll
            for (int c = 0; c < 4; c++)
              o[r][c] = pack2(fmaf(np[hh][4 * c + 2 * r], cp, nm[hh][4 * c + 2 * r] * cm), fmaf(np[hh][4 * c + 2 * r + 1], cp, nm[hh][4 * c + 2 * r + 1] * cm));
            sts128((own ^ (hh * 64)) + r * 1024, o[r][0], o[r][1], o[r][2], o[r][3]);
          }
          if (hh == 1 && pr == 1) fence_async_smem();
#pragma unroll
          for (int r = 0; r < 2; r++) *reinterpret_cast<uint4*>(og + r * 8 * kD + hh * 32) = make_uint4(o[r][0], o[r][1], o[r][2], o[r][3]);
        }
        warp_arrive(bars + (B_PUB + wg * 2 + pr) * 8, lane);
        if (tw == 0) TS(25 + pr + wg * 16);
        og += 64; own += STAGE;
      }
    }
    bar_sync(7 + wg, 128);

    float oacc[64];
    {
      const uint64_t dam = P.da + wg * 512;
      uint32_t slot = 3, ph = 1, prev = 0;
#pragma unroll 1
      for (int s = 0; s < 16; s++) {
        if (tid == 0) KS(128 + 48 + s);
        mbar_wait(bars + B_FX * 8 + slot * 8, ph, budget);
        if (s >= 2) mbar_wait(bars + (B_FY + wg * NST) * 8 + slot * 8, ph, budget);
        if (tid == 0) KS(48 + s);
        if (tid == 128) KS(192 + 48 + s);
        kstep64(oacc, dam + slot * (STAGE >> 4), P.db + slot * (STAGE >> 4), s);
        wg_wait<1>();
        if (s != 0 && s != 2 && lane0) mbar_arrive(bars + B_EM * 8 + prev * 8);
        if (s == 1) {
          wg_wait<0>();
          if (lane0) mbar_arrive(bars + B_EM * 8 + slot * 8);
        }
        prev = slot;
        if (++slot == NST) { slot = 0; ph ^= 1; }
      }
    }
    mbar_wait(bars + B_XT * 8, 0, budget);
    if ((lds32(sb + SM_MISC + 4) >> 7) == (uint32_t)bi) mbar_wait(bars + B_XP * 8, 0, budget);
    const uint32_t sx = sb + SM_PHI + (wg * 64 + w * 16 + (lane & 15)) * 128 + (((lane >> 4) ^ (lane & 7)) << 4);
    float xf[64];
#pragma unroll
    for (int u = 0; u < 8; u++) {
      uint32_t xr[4];
      ldmatrix4((sx ^ ((u & 3) * 32)) + (u >> 2) * 16384, xr);
#pragma unroll
      for (int r = 0; r < 4; r++) { xf[8 * u + 2 * r] = bf_lo(xr[r]); xf[8 * u + 2 * r + 1] = bf_hi(xr[r]); }
    }
    pin(xf);
    const float hA = 1.0f - gA, hB = 1.0f - gB;
    wg_wait<0>();
    pin(oacc);
    if (tw == 0) TS(29 + wg * 16);
#pragma unroll
    for (int hf = 0; hf < 2; hf++) {
#pragma unroll
      for (int u = hf * 4; u < hf * 4 + 4; u++) {
        const float* a = &oacc[8 * u];
        const float* b = &xf[8 * u];
        stmatrix4((sx ^ ((u & 3) * 32)) + hf * 16384,
                  pack2(fmaf(hA, b[0], a[0]), fmaf(hA, b[1], a[1])), pack2(fmaf(hB, b[2], a[2]), fmaf(hB, b[3], a[3])),
                  pack2(fmaf(hA, b[4], a[4]), fmaf(hA, b[5], a[5])), pack2(fmaf(hB, b[6], a[6]), fmaf(hB, b[7], a[7])));
      }
      fence_async_smem();
      __syncwarp();
      if (elect_one()) tma_store(&mout, sb + SM_PHI + hf * 16384 + warp * 2048, bj * 128 + hf * 64, bi * 128 + warp * 16);
    }
    if (elect_one()) {
      asm volatile("cp.async.bulk.commit_group;" ::: "memory");
      asm volatile("cp.async.bulk.wait_group.read 0;" ::: "memory");
    }
  } else {
    asm volatile("setmaxnreg.dec.sync.aligned.u32 32;");
    if (warp == 8) {
      if (elect_one()) {
        TS(7);
#pragma unroll
        for (int s = 0; s < NST; s++) mbar_init(bars + (B_FX + s) * 8, 1);
        asm volatile("fence.mbarrier_init.release.cluster;" ::: "memory");
        fence_async_smem();
      }
      __syncwarp();
      bar_arrive(0, 512);
      if (elect_one()) {
#pragma unroll 1
        for (int n = 0; n < NST; n++) {
          const uint32_t st = sb + n * STAGE, fb = bars + (B_FX + n) * 8;
          KS(64 + n);
          mbar_expect_tx(fb, STAGE);
          tma_load(st, &mx, fb, n * 64, bi * 128);
          tma_load(st + 16384, &mw, fb, 1024 + bj * 128, n * 64);
          tma_load(st + 24576, &mw, fb, 2048 + bj * 128, n * 64);
        }
      }
      __syncwarp();
      bar_sync(10, 64);
    } else {
      if (warp == 9) {
        if (elect_one()) {
#pragma unroll
          for (int s = B_FY; s < B_NUM; s++) mbar_init(bars + s * 8, s < B_WPHI ? 1 : s < B_EM ? 4 : 8);
          asm volatile("fence.mbarrier_init.release.cluster;" ::: "memory");
          fence_async_smem();
        }
        __syncwarp();
        bar_arrive(10, 64);
      }
      bar_sync(0, 512);
    }
    if (!elect_one()) return;
    if (warp == 8) {
      uint32_t slot = 0, ph = 0;
#pragma unroll 1
      for (int n = NST; n < 48; n++) {
        const int t = n >> 4, k = n & 15;
        const int c0 = t == 2 ? bj * 128 : 1024 + bj * 128 + t * 64, c1 = t == 2 ? c0 + 64 : c0 + 1024;
        const uint32_t st = sb + slot * STAGE, fb = bars + (B_FX + slot) * 8;
        if (n <= NST + 3 * RSTEP && (n - NST) % RSTEP == 0) {
          const int c = (n - NST) / RSTEP;
          mbar_expect_tx(bars + (B_RX + c) * 8, c == 0 ? 8192 + 4096 : 8192);
          tma_load(sb + SM_PHI + c * 8192, &mxr, bars + (B_RX + c) * 8, c * 256, bi * 128 + bj * 16);
          if (c == 0) { bulk_load(sb + SM_V, P.w_r, 2048, bars + B_RX * 8); bulk_load(sb + SM_V + 2048, P.gate_w, 2048, bars + B_RX * 8); }
        }
        mbar_wait(bars + (B_EM + slot) * 8, ph, budget);
        KS(64 + n);
        mbar_expect_tx(fb, STAGE);
        tma_load(st, &mx, fb, k * 64, bi * 128);
        tma_load(st + 16384, &mw, fb, c0, k * 64);
        tma_load(st + 24576, &mw, fb, c1, k * 64);
        {
          const int m = n + WLEAD, tm = m >> 4;
          if ((m & 3) == (bi & 3)) {
            const int d0 = tm >= 2 ? bj * 128 : 1024 + bj * 128 + tm * 64, d1 = tm >= 2 ? d0 + 64 : d0 + 1024;
            tma_prefetch(tm == 3 ? &mwo : &mw, d0, (m & 15) * 64); tma_prefetch(tm == 3 ? &mwo : &mw, d1, (m & 15) * 64);
          }
        }
        if (++slot == NST) { slot = 0; ph ^= 1; }
      }
#pragma unroll 1
      for (int m = WLEAD + ((bi - WLEAD) & 3); m < 16; m += 4) { tma_prefetch(&mwo, bj * 128, m * 64); tma_prefetch(&mwo, bj * 128 + 64, m * 64); }
#pragma unroll 1
      for (int s = 0; s < 16; s++) {
        const int p = s < 2 ? s : (s >= 9), q = s < 9 ? s - 2 : s - 9;
        const int k0 = (s < 2 ? bj : q + (q >= bj)) * 128 + p * 64;
        const uint32_t st = sb + slot * STAGE, fb = bars + (B_FX + slot) * 8;
        mbar_wait(bars + (B_EM + slot) * 8, ph, budget);
        KS(64 + 48 + s);
        mbar_expect_tx(fb, 16384);
        tma_load(st + 16384, &mwo, fb, bj * 128, k0);
        tma_load(st + 24576, &mwo, fb, bj * 128 + 64, k0);
        if (++slot == NST) { slot = 0; ph ^= 1; }
      }
      mbar_wait(bars + B_MD * 8, 0, budget);
      mbar_expect_tx(bars + B_XT * 8, 32768);
      tma_load(sb + SM_PHI, &mx, bars + B_XT * 8, bj * 128, bi * 128);
      tma_load(sb + SM_PHI + 16384, &mx, bars + B_XT * 8, bj * 128 + 64, bi * 128);
    } else if (warp == 9) {
      prefetch_map(&mo); prefetch_map(&mout);
      uint32_t old;
      asm volatile("atom.add.release.gpu.global.u32 %0, [%1], 1;" : "=r"(old) : "l"(&g_cnt[C_START]) : "memory");
      sts32(sb + SM_MISC, (old & ~255u) + 256u);
      mbar_arrive(bars + B_EPOCH * 8);
      const CUtensorMap* m = (cta & 8) ? &mu : &mg;
      const int l0 = (cta >> 4) * 14, a0 = (cta & 7) * 64, d1 = (cta >> 2) * 112 - 14 * 16, d2 = (cta & 3) * 4;
      uint32_t buf = 0, ph = 0;
#pragma unroll 1
      for (int c = 0; c < 21; c++) {
        const uint32_t dst = sb + moe_buf(buf), fb = bars + (B_MF + buf) * 8;
        mbar_wait(bars + (B_ME + buf) * 8, ph, budget);
        mbar_expect_tx(fb, 8192);
        if (c < 14) tma_load(dst, m, fb, a0 + ((l0 + c) >> 4) * 512, ((l0 + c) & 15) * 64); else tma_load3(dst, &md, fb, d1 + c * 16, d2);
        if (c == 16) {
#pragma unroll 1
          for (int f = 17; f < 21; f++) { __nanosleep(MGAP); tma_prefetch3(&md, d1 + f * 16, d2); }
        }
        if (c < 2) __nanosleep(MGAP);
        if (c == 17) mbar_arrive(bars + B_M2 * 8);
        if (++buf >= (c >= 14 ? 2 : 3)) { buf = 0; ph ^= 1; }
      }
#pragma unroll 1
      for (int u = 0; u < 2; u++) {
        mbar_wait(bars + (B_PUB + u * 2 + 1) * 8, 0, budget);
        signal_add(&g_cnt[(C_O + bi * 4 + u * 2 + 1) * 32], 32u);
        TS(57 + u * 2);
      }
    } else {
      const int u = warp - 10, hp = bj * 2 + u;
      mbar_wait(bars + B_EPOCH * 8, 0, budget);
      const uint32_t target = lds32(sb + SM_MISC);
      mbar_wait(bars + B_INFO * 8, 0, budget);
      wait_count<200>(&g_cnt[C_START], target, budget);
      fence_async_global();
#pragma unroll 1
      for (int e = 0; e < 2; e++) {
        uint32_t* cnt = &g_cnt[(e ? C_O + bi * 4 + u * 2 : C_KV + hp) * 32];
        mbar_wait(bars + (e ? B_PUB + u * 2 : B_RED + u) * 8, 0, budget);
        if (e == 0) {
#pragma unroll 1
          for (int c = 0; c < RED_CH; c++) {
            bulk_reduce(&g_kvr[hp * 2560 + c * (2560 / RED_CH)], sb + SM_PHI + c * (10240 / RED_CH), 10240 / RED_CH);
            if (c + 1 < RED_CH) __nanosleep(u ? RED_GAP1 : RED_GAP0);
          }
          asm volatile("cp.async.bulk.commit_group;" ::: "memory");
          asm volatile("cp.async.bulk.wait_group 0;" ::: "memory");
          TS(21 + u * 16);
          mbar_arrive(bars + (B_RD + u) * 8);
        }
        signal_add(cnt, e ? 32u : 16u);
        TS(e ? 56 + u * 2 : 60 + u);
        if (e == 0) {
          mbar_wait(bars + (u ? B_M2 : B_RED + 1) * 8, 0, budget);
        }
        wait_count<POLLF>(cnt, target, budget);
        fence_async_global();
        if (e == 0) {
          mbar_expect_tx(bars + (B_KV + u) * 8, 10240);
          bulk_load(sb + SM_V + u * 8192, &g_kvr[hp * 2560], 8192, bars + (B_KV + u) * 8);
          bulk_load(sb + SM_Z + u * 2048, &g_kvr[hp * 2560 + 2048], 2048, bars + (B_KV + u) * 8);
          TS(38 + u);
        }
      }
      TS(2 + u * 2);
      if (u == 0) mbar_wait(bars + B_QS * 8, 0, budget);
      uint32_t slot = 0, ph = 1;
#pragma unroll 1
      for (int s = 2; s < 16; s++) {
        const int p = s >= 9, q = s < 9 ? s - 2 : s - 9;
        if (s == 9) { wait_count<POLLF>(&g_cnt[(C_O + bi * 4 + u * 2 + 1) * 32], target, budget); fence_async_global(); TS(3 + u * 2); }
        const uint32_t fb = bars + (B_FY + u * NST + slot) * 8;
        mbar_wait(bars + (B_EM + slot) * 8, ph, budget);
        mbar_expect_tx(fb, 8192);
        tma_load(sb + slot * STAGE + u * 8192, &mo, fb, (q + (q >= bj)) * 128 + p * 64, bi * 128 + u * 64);
        if (++slot == NST) { slot = 0; ph ^= 1; }
      }
    }
  }
}

typedef CUresult (*EncodeFn)(CUtensorMap*, CUtensorMapDataType, cuuint32_t, void*, const cuuint64_t*, const cuuint64_t*, const cuuint32_t*,
                             const cuuint32_t*, CUtensorMapInterleave, CUtensorMapSwizzle, CUtensorMapL2promotion, CUtensorMapFloatOOBfill);

void make_map(EncodeFn enc, CUtensorMap* m, const void* ptr, uint64_t cols, uint64_t rows, uint32_t bc, uint32_t br, CUtensorMapSwizzle swz) {
  const cuuint64_t dims[2] = {cols, rows}, strides[1] = {cols * 2};
  const cuuint32_t box[2] = {bc, br}, es[2] = {1, 1};
  enc(m, CU_TENSOR_MAP_DATA_TYPE_BFLOAT16, 2, const_cast<void*>(ptr), dims, strides, box, es, CU_TENSOR_MAP_INTERLEAVE_NONE, swz,
      CU_TENSOR_MAP_L2_PROMOTION_L2_128B, CU_TENSOR_MAP_FLOAT_OOB_FILL_NONE);
}

}

extern "C" void kernel_launch(void* const* d_in, const int* in_sizes, int n_in, void* d_out, int out_size) {
  (void)in_sizes; (void)n_in; (void)out_size;
  void* fn = nullptr;
  cudaDriverEntryPointQueryResult qr;
  cudaGetDriverEntryPoint("cuTensorMapEncodeTiled", &fn, cudaEnableDefault, &qr);
  EncodeFn enc = (EncodeFn)fn;
  void* o_ptr = nullptr;
  cudaGetSymbolAddress(&o_ptr, g_o);
  CUtensorMap mx, mw, mwo, mo, mout, mxr, mg, mu, md;
  make_map(enc, &mx, d_in[0], kD, kS, 64, 128, CU_TENSOR_MAP_SWIZZLE_128B);
  make_map(enc, &mxr, d_in[0], kD, kS, 256, 16, CU_TENSOR_MAP_SWIZZLE_NONE);
  make_map(enc, &mw, d_in[1], 3 * kD, kD, 64, 64, CU_TENSOR_MAP_SWIZZLE_128B);
  make_map(enc, &mwo, d_in[3], kD, kD, 64, 64, CU_TENSOR_MAP_SWIZZLE_128B);
  make_map(enc, &mo, o_ptr, kD, kS, 64, 64, CU_TENSOR_MAP_SWIZZLE_128B);
  make_map(enc, &mout, d_out, kD, kS, 64, 16, CU_TENSOR_MAP_SWIZZLE_128B);
  make_map(enc, &mg, d_in[6], kF, kD, 64, 64, CU_TENSOR_MAP_SWIZZLE_128B);
  make_map(enc, &mu, d_in[7], kF, kD, 64, 64, CU_TENSOR_MAP_SWIZZLE_128B);
  {
    const cuuint64_t dims[3] = {64, kF, 16}, strides[2] = {kD * 2, 128};
    const cuuint32_t box[3] = {64, 16, 4}, es[3] = {1, 1, 1};
    enc(&md, CU_TENSOR_MAP_DATA_TYPE_BFLOAT16, 3, d_in[8], dims, strides, box, es, CU_TENSOR_MAP_INTERLEAVE_NONE, CU_TENSOR_MAP_SWIZZLE_128B,
        CU_TENSOR_MAP_L2_PROMOTION_L2_128B, CU_TENSOR_MAP_FLOAT_OOB_FILL_NONE);
  }
  Params P;
  P.x = (const __nv_bfloat16*)d_in[0];
  P.w = (const __nv_bfloat16*)d_in[1];
  P.w_phi = (const __nv_bfloat16*)d_in[2];
  P.w_r = (const __nv_bfloat16*)d_in[5];
  P.gate_w = (const __nv_bfloat16*)d_in[9];
  P.da = make_desc(sb, 16, 1024, 1);
  P.db = make_desc(sb + 16384, 8192, 1024, 1);
  P.dw = make_desc(sb + SM_WPHI, 16, 512, 2);
  P.dphi = make_desc(sb + SM_PHI, 16, 1024, 1);
  P.dv = make_desc(sb + SM_V, SM_Z - SM_V, 512, 2);
  P.dband = make_desc(sb + SM_BAND, 128, 128, 0);
  P.dxs = make_desc(sb + SM_BAND, 16, 128, 0);
  int dev = 0, sms = 0;
  cudaGetDevice(&dev);
  cudaDeviceGetAttribute(&sms, cudaDevAttrMultiProcessorCount, dev);
  auto kern = sms == 132 ? fused_kernel<true> : fused_kernel<false>;
  cudaFuncSetAttribute(kern, cudaFuncAttributeMaxDynamicSharedMemorySize, SM_ALLOC);
  kern<<<132, 512, SM_ALLOC, cudaStreamPerThread>>>(mx, mw, mwo, mo, mout, mxr, mg, mu, md, P);
}
```

```cpp
#include <cuda_runtime.h>
#include <cuda_bf16.h>
#include <cuda.h>
#include <stdint.h>

namespace {

template<int TA, int TB> __device__ __forceinline__ void wgmma_m64n128k16_ss(float (&d)[64], uint64_t da, uint64_t db, int scale_d) {
  asm volatile("{\n.reg .pred p;\nsetp.ne.b32 p, %66, 0;\n"
    "wgmma.mma_async.sync.aligned.m64n128k16.f32.bf16.bf16 "
    "{%0, %1, %2, %3, %4, %5, %6, %7, %8, %9, %10, %11, %12, %13, %14, %15, "
    "%16, %17, %18, %19, %20, %21, %22, %23, %24, %25, %26, %27, %28, %29, %30, %31, "
    "%32, %33, %34, %35, %36, %37, %38, %39, %40, %41, %42, %43, %44, %45, %46, %47, "
    "%48, %49, %50, %51, %52, %53, %54, %55, %56, %57, %58, %59, %60, %61, %62, %63}, "
    "%64, %65, p, 1, 1, %67, %68;\n}\n"
    : "+f"(d[0]), "+f"(d[1]), "+f"(d[2]), "+f"(d[3]), "+f"(d[4]), "+f"(d[5]), "+f"(d[6]), "+f"(d[7]),
      "+f"(d[8]), "+f"(d[9]), "+f"(d[10]), "+f"(d[11]), "+f"(d[12]), "+f"(d[13]), "+f"(d[14]), "+f"(d[15]),
      "+f"(d[16]), "+f"(d[17]), "+f"(d[18]), "+f"(d[19]), "+f"(d[20]), "+f"(d[21]), "+f"(d[22]), "+f"(d[23]),
      "+f"(d[24]), "+f"(d[25]), "+f"(d[26]), "+f"(d[27]), "+f"(d[28]), "+f"(d[29]), "+f"(d[30]), "+f"(d[31]),
      "+f"(d[32]), "+f"(d[33]), "+f"(d[34]), "+f"(d[35]), "+f"(d[36]), "+f"(d[37]), "+f"(d[38]), "+f"(d[39]),
      "+f"(d[40]), "+f"(d[41]), "+f"(d[42]), "+f"(d[43]), "+f"(d[44]), "+f"(d[45]), "+f"(d[46]), "+f"(d[47]),
      "+f"(d[48]), "+f"(d[49]), "+f"(d[50]), "+f"(d[51]), "+f"(d[52]), "+f"(d[53]), "+f"(d[54]), "+f"(d[55]),
      "+f"(d[56]), "+f"(d[57]), "+f"(d[58]), "+f"(d[59]), "+f"(d[60]), "+f"(d[61]), "+f"(d[62]), "+f"(d[63])
    : "l"(da), "l"(db), "r"(scale_d), "n"(TA), "n"(TB));
}

template<int TB> __device__ __forceinline__ void wgmma_m64n32k16_rs(float (&d)[16], const uint32_t (&a)[4], uint64_t db, int scale_d) {
  asm volatile("{\n.reg .pred p;\nsetp.ne.b32 p, %21, 0;\n"
    "wgmma.mma_async.sync.aligned.m64n32k16.f32.bf16.bf16 "
    "{%0, %1, %2, %3, %4, %5, %6, %7, %8, %9, %10, %11, %12, %13, %14, %15}, "
    "{%16, %17, %18, %19}, %20, p, 1, 1, %22;\n}\n"
    : "+f"(d[0]), "+f"(d[1]), "+f"(d[2]), "+f"(d[3]), "+f"(d[4]), "+f"(d[5]), "+f"(d[6]), "+f"(d[7]),
      "+f"(d[8]), "+f"(d[9]), "+f"(d[10]), "+f"(d[11]), "+f"(d[12]), "+f"(d[13]), "+f"(d[14]), "+f"(d[15])
    : "r"(a[0]), "r"(a[1]), "r"(a[2]), "r"(a[3]), "l"(db), "r"(scale_d), "n"(TB));
}

template<int TA, int TB> __device__ __forceinline__ void wgmma_m64n40k16_ss(float (&d)[20], uint64_t da, uint64_t db, int scale_d) {
  asm volatile("{\n.reg .pred p;\nsetp.ne.b32 p, %22, 0;\n"
    "wgmma.mma_async.sync.aligned.m64n40k16.f32.bf16.bf16 "
    "{%0, %1, %2, %3, %4, %5, %6, %7, %8, %9, %10, %11, %12, %13, %14, %15, "
    "%16, %17, %18, %19}, "
    "%20, %21, p, 1, 1, %23, %24;\n}\n"
    : "+f"(d[0]), "+f"(d[1]), "+f"(d[2]), "+f"(d[3]), "+f"(d[4]), "+f"(d[5]), "+f"(d[6]), "+f"(d[7]),
      "+f"(d[8]), "+f"(d[9]), "+f"(d[10]), "+f"(d[11]), "+f"(d[12]), "+f"(d[13]), "+f"(d[14]), "+f"(d[15]),
      "+f"(d[16]), "+f"(d[17]), "+f"(d[18]), "+f"(d[19])
    : "l"(da), "l"(db), "r"(scale_d), "n"(TA), "n"(TB));
}

template<int TB> __device__ __forceinline__ void wgmma_m64n40k16_rs(float (&d)[20], const uint32_t (&a)[4], uint64_t db, int scale_d) {
  asm volatile("{\n.reg .pred p;\nsetp.ne.b32 p, %25, 0;\n"
    "wgmma.mma_async.sync.aligned.m64n40k16.f32.bf16.bf16 "
    "{%0, %1, %2, %3, %4, %5, %6, %7, %8, %9, %10, %11, %12, %13, %14, %15, "
    "%16, %17, %18, %19}, "
    "{%20, %21, %22, %23}, %24, p, 1, 1, %26;\n}\n"
    : "+f"(d[0]), "+f"(d[1]), "+f"(d[2]), "+f"(d[3]), "+f"(d[4]), "+f"(d[5]), "+f"(d[6]), "+f"(d[7]),
      "+f"(d[8]), "+f"(d[9]), "+f"(d[10]), "+f"(d[11]), "+f"(d[12]), "+f"(d[13]), "+f"(d[14]), "+f"(d[15]),
      "+f"(d[16]), "+f"(d[17]), "+f"(d[18]), "+f"(d[19])
    : "r"(a[0]), "r"(a[1]), "r"(a[2]), "r"(a[3]), "l"(db), "r"(scale_d), "n"(TB));
}

template<int TA, int TB> __device__ __forceinline__ void wgmma_m64n8k16_ss(float (&d)[4], uint64_t da, uint64_t db, int scale_d) {
  asm volatile("{\n.reg .pred p;\nsetp.ne.b32 p, %6, 0;\n"
    "wgmma.mma_async.sync.aligned.m64n8k16.f32.bf16.bf16 "
    "{%0, %1, %2, %3}, "
    "%4, %5, p, 1, 1, %7, %8;\n}\n"
    : "+f"(d[0]), "+f"(d[1]), "+f"(d[2]), "+f"(d[3])
    : "l"(da), "l"(db), "r"(scale_d), "n"(TA), "n"(TB));
}

constexpr int kS = 2048, kD = 1024, kF = 3584;
constexpr int NST = 5, STAGE = 32768;
constexpr uint32_t sb = 1024;
constexpr int SM_V    = NST * STAGE;
constexpr int SM_Z    = SM_V + 16384;
constexpr int SM_PHI  = SM_Z + 4096;
constexpr int SM_MOE  = SM_PHI + 16384;
constexpr int SM_WPHI = SM_MOE + 16384;
constexpr int SM_BAND = SM_WPHI + 8192;
constexpr int SM_G    = SM_BAND + 2176;
constexpr int SM_BAR  = SM_G + 512;
constexpr int SM_MISC = SM_BAR + 448;
constexpr int SM_TOTAL = SM_MISC + 64;
static_assert(SM_TOTAL <= 232448, "smem");
constexpr uint32_t bars = sb + SM_BAR;
constexpr int B_FX = 0  , B_FY = 5  , B_XT = 15, B_EPOCH = 16, B_RX = 17  , B_MF = 21  , B_RD = 24  , B_KV = 26  , B_M2 = 28, B_P1 = 29;
constexpr int B_WPHI = 30, B_INFO = 31, B_QS = 32, B_XP = 33, B_RED = 34  , B_PUB = 36  , B_ME = 40  , B_MD = 43;
constexpr int B_EM = 44  , B_NUM = 49;
constexpr int C_START = 0, C_O = 1, C_KV = C_O + 64;

__device__ uint2 g_gate[kS];
__device__ uint2 g_key[128];
__device__ uint2 g_pre[4 * kF];
__device__ uint2 g_yp[32 * kD];
__device__ __align__(128) uint32_t g_kvr[16 * 2560];
__device__ __align__(128) uint32_t g_cnt[(C_KV + 32) * 32];
__device__ __align__(1024) __nv_bfloat16 g_o[kS * kD];
#define KS(id)
#define RG(id)
#define TS(id)
#define TSG(id)
constexpr int SM_ALLOC = SM_TOTAL;

#define POLL0 500
#define POLL1 150
#define RSTEP 1
#define POLLR 400
#define EARLY_N 2
#define EARLY_GAP 200
#define POLLF 50
#define RED_CH 10
#define RED_GAP0 250
#define RED_GAP1 0
#define YIELD_EXP 1
#define END_SKEW 3
#define XT_GATE B_QS
#define FIN_YIELD 0
#define MLEAD 0
#define MPACE 0
#define WLEAD 11
#define MGAP 300

struct Params {
  const __nv_bfloat16 *x, *w, *w_phi, *w_r, *gate_w;
  __nv_bfloat16* o;
  uint64_t da, db, dw, dphi, dv, dband, dxs;
};

__device__ __forceinline__ uint32_t smem_u32(const void* p) { return (uint32_t)__cvta_generic_to_shared(p); }
__device__ __forceinline__ void mbar_init(uint32_t bar, uint32_t cnt) { asm volatile("mbarrier.init.shared::cta.b64 [%0], %1;" :: "r"(bar), "r"(cnt) : "memory"); }
__device__ __forceinline__ void mbar_expect_tx(uint32_t bar, uint32_t bytes) { asm volatile("mbarrier.arrive.expect_tx.shared::cta.b64 _, [%0], %1;" :: "r"(bar), "r"(bytes) : "memory"); }
__device__ __forceinline__ void mbar_arrive(uint32_t bar) { asm volatile("mbarrier.arrive.shared::cta.b64 _, [%0];" :: "r"(bar) : "memory"); }
__device__ __forceinline__ void mbar_arrive_n(uint32_t bar, uint32_t n) { asm volatile("mbarrier.arrive.shared::cta.b64 _, [%0], %1;" :: "r"(bar), "r"(n) : "memory"); }
constexpr int BUDGET = 1 << 20;
__device__ __forceinline__ void mbar_wait(uint32_t bar, uint32_t parity, int& budget) {
  asm volatile("{\n.reg .pred p;\n"
               "WAIT_L:\nmbarrier.try_wait.parity.shared::cta.b64 p, [%1], %2;\n@p bra WAIT_D;\n"
               "add.s32 %0, %0, -1;\nsetp.gt.s32 p, %0, 0;\n@p bra WAIT_L;\nWAIT_D:\n}"
               : "+r"(budget) : "r"(bar), "r"(parity) : "memory");
}
template <int SLEEP>
__device__ __forceinline__ void wait_count(const uint32_t* p, uint32_t target, int& budget) {
  asm volatile("{\n.reg .pred p;\n.reg .s32 v;\n"
               "WAIT_L:\nld.acquire.gpu.global.s32 v, [%1];\nsub.s32 v, v, %2;\nsetp.ge.s32 p, v, 0;\n@p bra WAIT_D;\n"
               "nanosleep.u32 %3;\nadd.s32 %0, %0, -4;\nsetp.gt.s32 p, %0, 0;\n@p bra WAIT_L;\nWAIT_D:\n}"
               : "+r"(budget) : "l"(p), "r"(target), "n"(SLEEP) : "memory");
}
__device__ __forceinline__ void tma_load(uint32_t dst, const CUtensorMap* m, uint32_t bar, int c0, int c1) {
  asm volatile("cp.async.bulk.tensor.2d.shared::cluster.global.mbarrier::complete_tx::bytes [%0], [%1, {%3, %4}], [%2];"
    :: "r"(dst), "l"(m), "r"(bar), "r"(c0), "r"(c1) : "memory");
}
__device__ __forceinline__ void tma_load3(uint32_t dst, const CUtensorMap* m, uint32_t bar, int c1, int c2) {
  asm volatile("cp.async.bulk.tensor.3d.shared::cluster.global.mbarrier::complete_tx::bytes [%0], [%1, {%5, %3, %4}], [%2];"
    :: "r"(dst), "l"(m), "r"(bar), "r"(c1), "r"(c2), "r"(0) : "memory");
}
__device__ __forceinline__ void tma_prefetch3(const CUtensorMap* m, int c1, int c2) {
  asm volatile("cp.async.bulk.prefetch.tensor.3d.L2.global [%0, {%3, %1, %2}];" :: "l"(m), "r"(c1), "r"(c2), "r"(0) : "memory");
}
__device__ __forceinline__ void tma_prefetch(const CUtensorMap* m, int c0, int c1) {
  asm volatile("cp.async.bulk.prefetch.tensor.2d.L2.global [%0, {%1, %2}];" :: "l"(m), "r"(c0), "r"(c1) : "memory");
}
__device__ __forceinline__ void tma_store(const CUtensorMap* m, uint32_t src, int c0, int c1) {
  asm volatile("cp.async.bulk.tensor.2d.global.shared::cta.bulk_group [%0, {%2, %3}], [%1];" :: "l"(m), "r"(src), "r"(c0), "r"(c1) : "memory");
}
__device__ __forceinline__ void bulk_load(uint32_t dst, const void* src, uint32_t bytes, uint32_t bar) {
  asm volatile("cp.async.bulk.shared::cluster.global.mbarrier::complete_tx::bytes [%0], [%1], %2, [%3];" :: "r"(dst), "l"(src), "r"(bytes), "r"(bar) : "memory");
}
__device__ __forceinline__ void bulk_reduce(void* dst, uint32_t src, uint32_t bytes) {
  asm volatile("cp.reduce.async.bulk.global.shared::cta.bulk_group.add.noftz.bf16 [%0], [%1], %2;" :: "l"(dst), "r"(src), "r"(bytes) : "memory");
}
__device__ __forceinline__ void prefetch_map(const CUtensorMap* m) { asm volatile("prefetch.tensormap [%0];" :: "l"(m) : "memory"); }
__device__ __forceinline__ bool elect_one() {
  uint32_t p;
  asm volatile("{\n.reg .pred P;\nelect.sync _|P, 0xffffffff;\nselp.u32 %0, 1, 0, P;\n}" : "=r"(p));
  return p;
}
__device__ __forceinline__ void wg_fence() { asm volatile("wgmma.fence.sync.aligned;" ::: "memory"); }
__device__ __forceinline__ void wg_commit() { asm volatile("wgmma.commit_group.sync.aligned;" ::: "memory"); }
template <int N> __device__ __forceinline__ void wg_wait() { asm volatile("wgmma.wait_group.sync.aligned %0;" :: "n"(N) : "memory"); }
template <int N> __device__ __forceinline__ void zero(float (&r)[N]) {
#pragma unroll
  for (int i = 0; i < N; i++) r[i] = 0.f;
}
template <int N> __device__ __forceinline__ void pin(float (&r)[N]) {
#pragma unroll
  for (int i = 0; i < N; i++) asm volatile("" : "+f"(r[i]) :: "memory");
}
template <int N> __device__ __forceinline__ void pinr(uint32_t (&r)[N][4]) {
#pragma unroll
  for (int i = 0; i < N; i++) asm volatile("" : "+r"(r[i][0]), "+r"(r[i][1]), "+r"(r[i][2]), "+r"(r[i][3]) :: "memory");
}
__device__ __forceinline__ void fence_async_smem() { asm volatile("fence.proxy.async.shared::cta;" ::: "memory"); }
__device__ __forceinline__ void fence_async_global() { asm volatile("fence.proxy.async.global;" ::: "memory"); }
__device__ __forceinline__ void bar_sync(int id, int n) { asm volatile("bar.sync %0, %1;" :: "r"(id), "r"(n) : "memory"); }
__device__ __forceinline__ void bar_arrive(int id, int n) { asm volatile("bar.arrive %0, %1;" :: "r"(id), "r"(n) : "memory"); }
__device__ __forceinline__ void warp_arrive(uint32_t bar, int lane) { __syncwarp(); if (lane == 0) mbar_arrive(bar); }
__host__ __device__ constexpr uint64_t make_desc(uint32_t addr, uint32_t lbo, uint32_t sbo, uint32_t swz) {
  return (uint64_t)((addr & 0x3FFFF) >> 4) | ((uint64_t)((lbo & 0x3FFFF) >> 4) << 16) | ((uint64_t)(sbo >> 4) << 32) | ((uint64_t)swz << 62);
}
__device__ __forceinline__ uint32_t pack2(float lo, float hi) {
  uint32_t r; asm("cvt.rn.bf16x2.f32 %0, %1, %2;" : "=r"(r) : "f"(hi), "f"(lo)); return r;
}
__device__ __forceinline__ float bf_lo(uint32_t v) { return __uint_as_float(v << 16); }
__device__ __forceinline__ float bf_hi(uint32_t v) { return __uint_as_float(v & 0xffff0000u); }
__device__ __forceinline__ float ex2(float x) { float r; asm("ex2.approx.ftz.f32 %0, %1;" : "=f"(r) : "f"(x)); return r; }
__device__ __forceinline__ float rcp(float x) { float r; asm("rcp.approx.ftz.f32 %0, %1;" : "=f"(r) : "f"(x)); return r; }
constexpr float LOG2E = 1.4426950408889634f;
__device__ __forceinline__ float sigmoidf(float x) { return rcp(1.0f + ex2(-LOG2E * x)); }
__device__ __forceinline__ void sts128(uint32_t a, uint32_t x, uint32_t y, uint32_t z, uint32_t w) {
  asm volatile("st.shared.v4.u32 [%0], {%1,%2,%3,%4};" :: "r"(a), "r"(x), "r"(y), "r"(z), "r"(w) : "memory");
}
__device__ __forceinline__ void lds128(uint32_t a, uint32_t (&r)[4]) {
  asm volatile("ld.shared.v4.u32 {%0,%1,%2,%3}, [%4];" : "=r"(r[0]), "=r"(r[1]), "=r"(r[2]), "=r"(r[3]) : "r"(a) : "memory");
}
__device__ __forceinline__ void sts32(uint32_t a, uint32_t v) { asm volatile("st.shared.u32 [%0], %1;" :: "r"(a), "r"(v) : "memory"); }
__device__ __forceinline__ uint32_t lds32(uint32_t a) { uint32_t v; asm volatile("ld.shared.u32 %0, [%1];" : "=r"(v) : "r"(a) : "memory"); return v; }
__device__ __forceinline__ float ldsf(uint32_t a) { return __uint_as_float(lds32(a)); }
__device__ __forceinline__ void stmatrix4(uint32_t a, uint32_t r0, uint32_t r1, uint32_t r2, uint32_t r3) {
  asm volatile("stmatrix.sync.aligned.m8n8.x4.shared.b16 [%0], {%1,%2,%3,%4};" :: "r"(a), "r"(r0), "r"(r1), "r"(r2), "r"(r3) : "memory");
}
__device__ __forceinline__ void ldmatrix4(uint32_t a, uint32_t (&r)[4]) {
  asm volatile("ldmatrix.sync.aligned.m8n8.x4.shared.b16 {%0,%1,%2,%3}, [%4];" : "=r"(r[0]), "=r"(r[1]), "=r"(r[2]), "=r"(r[3]) : "r"(a) : "memory");
}
__device__ __forceinline__ uint4 ldg_nc(const void* p) {
  uint4 v; asm volatile("ld.global.nc.L1::no_allocate.v4.u32 {%0,%1,%2,%3}, [%4];" : "=r"(v.x), "=r"(v.y), "=r"(v.z), "=r"(v.w) : "l"(p)); return v;
}
__device__ __forceinline__ void st_tagged(uint2* p, uint32_t v, uint32_t tag) {
  asm volatile("{\n.reg .b64 x;\nmov.b64 x, {%1, %2};\nst.relaxed.gpu.global.b64 [%0], x;\n}" :: "l"(p), "r"(v), "r"(tag) : "memory");
}
__device__ __forceinline__ uint2 ld_tagged(const uint2* p) {
  uint2 v; asm volatile("{\n.reg .b64 x;\nld.relaxed.gpu.global.b64 x, [%2];\nmov.b64 {%0, %1}, x;\n}" : "=r"(v.x), "=r"(v.y) : "l"(p) : "memory"); return v;
}
__device__ __forceinline__ void probe(const uint2* p, uint32_t tag, int& budget) {
  do { __nanosleep(POLL0); budget -= 16; } while (!__all_sync(0xffffffffu, ld_tagged(p).y == tag) && budget > 0);
}
template <int STRIDE, int N>
__device__ __forceinline__ void gather(const uint2* p, uint32_t tag, float& s0, float& s1, int& budget) {
  uint32_t pause = 0;
  bool again;
#pragma unroll 1
  do {
    __nanosleep(pause);
    pause = POLL0;
    uint32_t bad = 0;
    s0 = s1 = 0.f;
#pragma unroll
    for (int i = 0; i < N; i++) {
      const uint2 w = ld_tagged(p + i * STRIDE);
      bad |= w.y ^ tag;
      if (i < N / 2) s0 += __uint_as_float(w.x); else s1 += __uint_as_float(w.x);
    }
    budget -= 16;
    again = __any_sync(0xffffffffu, bad != 0) && budget > 0;
  } while (again);
}
__device__ __forceinline__ void sts16(uint32_t a, uint32_t v) { asm volatile("st.shared.u16 [%0], %1;" :: "r"(a), "h"((uint16_t)v) : "memory"); }
__device__ __forceinline__ void signal_add(uint32_t* p, uint32_t v) { asm volatile("red.release.gpu.global.add.u32 [%0], %1;" :: "l"(p), "r"(v) : "memory"); }
__device__ __forceinline__ float qmax(float v) { v = fmaxf(v, __shfl_xor_sync(0xffffffffu, v, 1)); return fmaxf(v, __shfl_xor_sync(0xffffffffu, v, 2)); }
__device__ __forceinline__ float qsum(float v) { v += __shfl_xor_sync(0xffffffffu, v, 1); return v + __shfl_xor_sync(0xffffffffu, v, 2); }
__device__ __forceinline__ float fold(float a, float b, bool hi, int m) { return (hi ? b : a) + __shfl_xor_sync(0xffffffffu, hi ? a : b, m); }

__device__ __forceinline__ void yield_slot() { asm volatile("pmevent 0;" ::: "memory"); }
__device__ __forceinline__ float fma_v(float a, float b, float c) { float r; asm volatile("fma.rn.f32 %0, %1, %2, %3;" : "=f"(r) : "f"(a), "f"(b), "f"(c)); return r; }
constexpr float EXP_LIM_F = 36028797018963968.0f;
constexpr uint32_t EXP_TOP = 0x58805880u;
__device__ __forceinline__ void exp_plain(const float (&p)[16], float (&ep)[16], float (&em)[16]) {
#pragma unroll
  for (int i = 0; i < 16; i++) { ep[i] = ex2(p[i]); em[i] = ex2(-p[i]); }
}
__device__ __forceinline__ void exp_shifted(const float (&p)[16], float sgn, float (&e)[16]) {
#pragma unroll
  for (int i = 0; i < 16; i++) e[i] = sgn * p[i];
#pragma unroll
  for (int o = 0; o < 4; o += 2) {
    const float mx = qmax(fmaxf(fmaxf(fmaxf(e[o], e[o + 1]), fmaxf(e[o + 4], e[o + 5])), fmaxf(fmaxf(e[o + 8], e[o + 9]), fmaxf(e[o + 12], e[o + 13]))));
#pragma unroll
    for (int c = 0; c < 4; c++) { e[4 * c + o] = ex2(e[4 * c + o] - mx); e[4 * c + o + 1] = ex2(e[4 * c + o + 1] - mx); }
  }
}
__device__ __forceinline__ void pack_sums(const float (&e)[16], uint32_t (&pk)[2][4], float (&s)[2]) {
#pragma unroll
  for (int i = 0; i < 8; i++) pk[i >> 2][i & 3] = pack2(e[2 * i], e[2 * i + 1]);
#pragma unroll
  for (int o = 0; o < 4; o += 2) s[o >> 1] = ((e[o] + e[o + 1]) + (e[o + 4] + e[o + 5])) + ((e[o + 8] + e[o + 9]) + (e[o + 12] + e[o + 13]));
}
__device__ __forceinline__ uint32_t rcp2(float s) { const float r = rcp(s); return pack2(r, r); }
__device__ __forceinline__ uint32_t mul2(uint32_t a, uint32_t b) { uint32_t r; asm("mul.rn.bf16x2 %0, %1, %2;" : "=r"(r) : "r"(a), "r"(b)); return r; }
__device__ __forceinline__ void store_phi(uint32_t a, const uint32_t (&pk)[2][4], uint32_t r0, uint32_t r1) {
#pragma unroll
  for (int h = 0; h < 2; h++) stmatrix4(a ^ (h * 32), mul2(pk[h][0], r0), mul2(pk[h][1], r1), mul2(pk[h][2], r0), mul2(pk[h][3], r1));
}
__device__ __forceinline__ uint32_t exp_frags(const float (&p)[16], uint32_t (&ef)[4][4], uint32_t top) {
  float ep[16], em[16];
  exp_plain(p, ep, em);
#pragma unroll
  for (int s = 0; s < 2; s++)
#pragma unroll
    for (int r = 0; r < 4; r++) {
      ef[s][r] = pack2(ep[8 * s + 2 * r], ep[8 * s + 2 * r + 1]);
      ef[2 + s][r] = pack2(em[8 * s + 2 * r], em[8 * s + 2 * r + 1]);
    }
#pragma unroll
  for (int s = 0; s < 4; s++) top = __vimax3_u16x2(__vimax3_u16x2(top, ef[s][0], ef[s][1]), ef[s][2], ef[s][3]);
  return top;
}
__device__ __forceinline__ void issue_pq(float (&p)[4][16], const uint32_t (&qf)[4][2][4], uint64_t dw) {
  wg_fence();
#pragma unroll
  for (int h = 0; h < 4; h++) {
    wgmma_m64n32k16_rs<1>(p[h], qf[h][0], dw + h * 128, 0);
    wgmma_m64n32k16_rs<1>(p[h], qf[h][1], dw + h * 128 + 64, 1);
  }
  wg_commit();
}

#define SPLIT_BATCH 2
__device__ __forceinline__ void mainloop128(float (&acc)[2][64], uint64_t da0, uint64_t db0, uint32_t slot, uint32_t ph, int steps, bool lane0, int& budget, int cta, int n0) {
  uint32_t prev = 0;
#pragma unroll 1
  for (int k = 0; k < steps; k++) {
    mbar_wait(bars + B_FX * 8 + slot * 8, ph, budget);
    const uint64_t da = da0 + slot * (STAGE >> 4), db = db0 + slot * (STAGE >> 4);
#pragma unroll
    for (int kk = 0; kk < 4; kk++) {
      if (SPLIT_BATCH == 2 || !(kk & 1)) {
        wg_wait<1>();
        if (kk == 3 - SPLIT_BATCH && k > 0 && lane0) mbar_arrive_n(bars + B_EM * 8 + prev * 8, 2);
        wg_fence();
      }
      wgmma_m64n128k16_ss<0, 1>(acc[0], da + kk * 2, db + kk * 128, kk ? 1 : k);
      wgmma_m64n128k16_ss<0, 1>(acc[1], da + 512 + kk * 2, db + kk * 128, kk ? 1 : k);
      if (SPLIT_BATCH == 2 || (kk & 1)) wg_commit();
    }
    prev = slot;
    if (++slot == NST) { slot = 0; ph ^= 1; }
  }
}
__device__ __forceinline__ void kstep64(float (&acc)[64], uint64_t da, uint64_t db, int accumulate) {
  wg_fence();
#pragma unroll
  for (int kk = 0; kk < 4; kk++) wgmma_m64n128k16_ss<0, 1>(acc, da + kk * 2, db + kk * 128, kk ? 1 : accumulate);
  wg_commit();
}
__device__ __forceinline__ void issue_kv(float (&kv)[20], uint64_t dphi, uint64_t dv, int accumulate) {
  wg_fence();
#pragma unroll
  for (int ks = 0; ks < 4; ks++)
    wgmma_m64n40k16_ss<1, 1>(kv, dphi + ks * 128, dv - (uint64_t)ks * ((64ull << 16) - 64ull), ks ? 1 : accumulate);
  wg_commit();
}
__device__ __forceinline__ void load_x(uint32_t sx, uint32_t (&xf)[8][4]) {
#pragma unroll
  for (int u = 0; u < 8; u++) ldmatrix4((sx ^ ((u & 3) * 32)) + (u >> 2) * 16384, xf[u]);
}
__device__ __forceinline__ uint32_t moe_buf(uint32_t b) { return b == 2 ? SM_V + 8192 : SM_MOE + b * 8192; }
template <bool DOWN>
__device__ __forceinline__ void moe_chunks(float (&a)[4], int n, uint32_t& buf, uint32_t& ph, uint64_t da0, uint64_t db, bool lane0) {
  int budget = BUDGET;
  zero(a);
#pragma unroll 1
  for (int c = 0; c < n; c++) {
    mbar_wait(bars + B_MF * 8 + buf * 8, ph, budget);
    const uint64_t da = da0 + (moe_buf(buf) >> 4);
    wg_fence();
#pragma unroll
    for (int j = 0; j < 4; j++) wgmma_m64n8k16_ss<1, 0>(a, da + j * 128, DOWN ? db - j : db + j * 2, 1);
    wg_commit();
    wg_wait<0>();
    if (lane0) mbar_arrive(bars + B_ME * 8 + buf * 8);
    db += DOWN ? 16 : 8;
    if (++buf >= (DOWN ? 2 : 3)) { buf = 0; ph ^= 1; }
  }
  pin(a);
}
constexpr uint64_t DV_TILE = 4 * ((64ull << 16) - 64ull);

template <bool BY_SM>
__global__ void __launch_bounds__(512, 1)
fused_kernel(const __grid_constant__ CUtensorMap mx, const __grid_constant__ CUtensorMap mw, const __grid_constant__ CUtensorMap mwo,
             const __grid_constant__ CUtensorMap mo, const __grid_constant__ CUtensorMap mout, const __grid_constant__ CUtensorMap mxr,
             const __grid_constant__ CUtensorMap mg, const __grid_constant__ CUtensorMap mu, const __grid_constant__ CUtensorMap md, const Params P) {
  extern __shared__ __align__(1024) uint8_t smem_raw[];
  if (smem_u32(smem_raw) != sb) return;
  const int tid = threadIdx.x, lane = tid & 31;
  if (tid == 256) TS(1);
  const int warp = __shfl_sync(0xffffffffu, tid >> 5, 0), wg = warp >> 2;
  int budget = BUDGET;
  if (warp == 10 && elect_one()) { prefetch_map(&mx); prefetch_map(&mw); }
  int cta;
  {
    uint32_t smid;
    asm volatile("mov.u32 %0, %%smid;" : "=r"(smid));
    if (!BY_SM) cta = blockIdx.x;
    else if (smid < 64) cta = ((smid >> 1) & 7) * 16 + (smid >> 4) * 2 + (smid & 1);
    else if (smid < 120) { const int t = (smid - 64) >> 1, d = (t * 37) >> 8; cta = (1 + t - d * 7) * 16 + 8 + d * 2 + (smid & 1); }
    else cta = smid < 124 ? smid + 8 : smid - 116;
  }
  if (cta >= 128) {
    if (tid == 0) {
      const uint32_t old = atomicAdd(&g_cnt[C_START], 32u);
      wait_count<500>(&g_cnt[C_START], (old & ~255u) + 256u, budget);
    }
    return;
  }
  const int bi = (cta >> 5) * 4 + ((cta >> 2) & 3);
  const int bj = ((cta >> 4) & 1) * 4 + (cta & 3);

  if (wg == 3) {
    asm volatile("setmaxnreg.dec.sync.aligned.u32 64;");
    const int t3 = tid - 384, w3 = warp - 12;
    if (t3 == 0) TSG(0);
    if (t3 < 80) *reinterpret_cast<uint4*>(&g_kvr[cta * 320 + t3 * 4]) = make_uint4(0, 0, 0, 0);
    if (t3 < 17) st_tagged(t3 < 16 ? &g_gate[bi * 128 + bj * 16 + t3] : &g_key[cta], 0, 1);
    bar_sync(0, 512);
#pragma unroll 1
    for (int u = 0; u < 4; u++) {
      const uint4 v = ldg_nc(P.w_phi + bj * 4096 + (u * 128 + t3) * 8);
      sts128(sb + SM_WPHI + u * 2048 + (t3 >> 2) * 64 + (((t3 & 3) ^ ((t3 >> 3) & 3)) << 4),
             pack2(LOG2E * bf_lo(v.x), LOG2E * bf_hi(v.x)), pack2(LOG2E * bf_lo(v.y), LOG2E * bf_hi(v.y)),
             pack2(LOG2E * bf_lo(v.z), LOG2E * bf_hi(v.z)), pack2(LOG2E * bf_lo(v.w), LOG2E * bf_hi(v.w)));
    }
    fence_async_smem();
    warp_arrive(bars + B_WPHI * 8, lane);
    bar_sync(6, 256);
    const uint32_t target = lds32(sb + SM_MISC);
    uint32_t key;
    {
      uint32_t kk[4];
      lds128(sb + SM_MISC + 16, kk);
      if (t3 == 0) st_tagged(&g_key[cta], max(max(kk[0], kk[1]), max(kk[2], kk[3])), target);
      uint2 k, gv;
      __nanosleep(POLLR);
      do {
        __nanosleep(POLL1);
        k = ld_tagged(&g_key[t3]);
        gv = ld_tagged(&g_gate[bi * 128 + t3]);
        budget -= 4;
      } while (!__all_sync(0xffffffffu, k.y == target && gv.y == target) && budget > 0);
      key = __reduce_max_sync(0xffffffffu, k.x);
      if (lane == 0) sts32(sb + SM_MISC + 32 + w3 * 4, key);
      sts32(sb + SM_G + t3 * 4, gv.x);
      bar_sync(5, 128);
      lds128(sb + SM_MISC + 32, kk);
      key = max(max(kk[0], kk[1]), max(kk[2], kk[3]));
    }
    const int idx = (0xFFFF - (key & 0xFFFF)) & (kS - 1);
    if (t3 == 0) { sts32(sb + SM_MISC + 4, idx); TS(8); }
    warp_arrive(bars + B_INFO * 8, lane);
    {
      const uint4 v = ldg_nc(P.x + (size_t)idx * kD + t3 * 8);
      sts128(sb + SM_BAND + t3 * 16, v.x, v.y, v.z, v.w);
    }
    const int t2 = (lane & 3) * 2, row = w3 * 16 + (lane >> 2);
    float a[4];
    uint32_t buf = 0, ph = 0;
    fence_async_smem();
    bar_sync(5, 128);
    {
      const int r = cta >> 4;
#pragma unroll 1
      for (int part = 0; part < 2; part++) {
        const int n = part ? 14 - 2 * r : 2 * r;
        moe_chunks<false>(a, n, buf, ph, P.da, P.dxs + (part ? 0 : (16 - n) * 8), lane == 0);
        uint2* dst = &g_pre[(((cta >> 2) & 2) + 1 - part) * kF + ((r - 1 + part) * 8 + (cta & 7)) * 64 + row];
        if (t2 == 0 && n) { st_tagged(dst, __float_as_uint(a[0]), target); st_tagged(dst + 8, __float_as_uint(a[2]), target); }
      }
    }
    if (t3 == 0) TS(9);
    bar_sync(5, 128);
    sts128(sb + SM_BAND + t3 * 16, 0, 0, 0, 0);
    {
      __nanosleep(POLL0);
      float gs, us;
      gather<kF, 4>(&g_pre[(cta >> 2) * 112 + min(t3, 111)], target, gs, us, budget);
      bar_sync(5, 128);
      if (t3 < 112) sts16(sb + SM_BAND + 112 + (t3 >> 3) * 128 + (t3 & 7) * 2, pack2(gs * sigmoidf(gs) * us, 0.f));
    }
    fence_async_smem();
    bar_sync(5, 128);
    if (t3 == 0) TS(12);
    moe_chunks<true>(a, 7, buf, ph, P.da, P.dband + 7, lane == 0);
    if (t3 == 0) TS(10);
    if (t2 < 4) {
      uint2* dst = &g_yp[(cta >> 2) * kD + (cta & 3) * 256 + t2 * 64 + row];
      st_tagged(dst, __float_as_uint(a[0]), target); st_tagged(dst + 8, __float_as_uint(a[2]), target);
      st_tagged(dst + 64, __float_as_uint(a[1]), target); st_tagged(dst + 72, __float_as_uint(a[3]), target);
    }
    if (lane == 0) mbar_arrive(bars + B_MD * 8);
    if ((idx >> 7) == bi) {
      mbar_wait(bars + (B_PUB + 3) * 8, 0, budget);
      if (w3 == 0) probe(&g_yp[lane * kD + bj * 128], target, budget);
      bar_sync(5, 128);
      float y = 0.f;
#pragma unroll 1
      for (int hf = 0; hf < 2; hf++) {
        float y0, y1;
        gather<kD, 16>(&g_yp[hf * 16 * kD + bj * 128 + t3], target, y0, y1, budget);
        y += y0 + y1;
      }
      const uint32_t ob = key >> 16;
      const float upd = y * sigmoidf(__uint_as_float(((ob & 0x8000u) ? (ob ^ 0x8000u) : (~ob & 0xFFFFu)) << 16));
      const uint32_t a = sb + SM_PHI + (t3 >> 6) * 16384 + (idx & 127) * 128 + ((((t3 >> 3) & 7) ^ (idx & 7)) << 4) + (t3 & 7) * 2;
      mbar_wait(bars + B_XT * 8, 0, budget);
      uint16_t xb;
      asm volatile("ld.shared.u16 %0, [%1];" : "=h"(xb) : "r"(a) : "memory");
      sts16(a, pack2(bf_lo(xb) + upd, 0.f));
      warp_arrive(bars + B_XP * 8, lane);
      if (t3 == 0) TS(11);
    }
  } else if (wg < 2) {
    if ((warp & 3) < EARLY_N && lane < (wg ? 8 : 16)) {
      const int n = warp & 3;
      const __nv_bfloat16* p = wg ? P.w + (size_t)(n * 64 + bi + (lane >> 1) * 16) * (3 * kD) + 1024 + (lane & 1) * 1024 + bj * 128
                                  : P.x + (size_t)(bi * 128 + bj * 16 + lane) * kD + n * 64;
      if (n) __nanosleep(n * EARLY_GAP);
      asm volatile("prefetch.global.L2 [%0];" :: "l"(p));
    }
    __syncwarp();
    asm volatile("setmaxnreg.inc.sync.aligned.u32 208;");
    const int tw = tid & 127, w = warp & 3, g = lane >> 2, t = lane & 3;
    const bool lane0 = lane == 0;
    if (wg == 0) sts128(sb + SM_Z + (tw & 63) * 16, 0x3f803f80u, 0x3f803f80u, 0x3f803f80u, 0x3f803f80u);
    bar_sync(0, 512);
    if (wg == 1) {
      float sr[4], sg[4];
      zero(sr); zero(sg);
#pragma unroll 1
      for (int c = 0; c < 4; c++) {
        mbar_wait(bars + (B_RX + c) * 8, 0, budget);
        uint32_t rs[4], gs[4], xs[4][4];
        lds128(sb + SM_V + c * 512 + lane * 16, rs);
        lds128(sb + SM_V + 2048 + c * 512 + lane * 16, gs);
#pragma unroll
        for (int r = 0; r < 4; r++) lds128(sb + SM_PHI + c * 8192 + (w * 4 + r) * 512 + lane * 16, xs[r]);
#pragma unroll
        for (int e = 0; e < 4; e++) {
          const float r0 = bf_lo(rs[e]), r1 = bf_hi(rs[e]), g0 = bf_lo(gs[e]), g1 = bf_hi(gs[e]);
#pragma unroll
          for (int r = 0; r < 4; r++) {
            const float x0 = bf_lo(xs[r][e]), x1 = bf_hi(xs[r][e]);
            sr[r] = fma_v(x0, r0, sr[r]); sg[r] = fma_v(x0, g0, sg[r]);
            sr[r] = fma_v(x1, r1, sr[r]); sg[r] = fma_v(x1, g1, sg[r]);
            if (r != 1) yield_slot();
          }
        }
      }
      fence_async_smem();
      __syncwarp();
      if (lane < 3) mbar_arrive(bars + (B_ME + lane) * 8);
      const bool b4 = lane & 16, b3 = lane & 8, b2 = lane & 4;
      const float v = qsum(fold(fold(fold(sr[0], sg[0], b4, 16), fold(sr[2], sg[2], b4, 16), b3, 8),
                                fold(fold(sr[1], sg[1], b4, 16), fold(sr[3], sg[3], b4, 16), b3, 8), b2, 4));
      const int row = bi * 128 + bj * 16 + w * 4 + (g & 3);
      const uint32_t rb = pack2(v + 0.f, 0.f);
      const uint32_t ob = (rb & 0x8000u) ? (~rb & 0xFFFFu) : (rb | 0x8000u);
      const uint32_t best = __reduce_max_sync(0xffffffffu, b4 ? 0u : (ob << 16) | (0xFFFFu - row));
      mbar_wait(bars + B_EPOCH * 8, 0, budget);
      const uint32_t tag = lds32(sb + SM_MISC);
      if (lane0) sts32(sb + SM_MISC + 16 + w * 4, best);
      if (b4 && t == 0) st_tagged(&g_gate[row], __float_as_uint(sigmoidf(v)), tag);
      if (tw == 0) TS(14);
      bar_arrive(6, 256);
      bar_sync(1, 256);
    }

    {
      float acc[2][64];
      if (tw == 0) TS(16 + wg * 16);
      mainloop128(acc, P.da, P.db, wg, wg, 16, lane0, budget, cta, wg * 16);
      bar_sync(1 + wg, 256);
      wg_wait<0>();
      pin(acc[0]); pin(acc[1]);
      if (lane0) mbar_arrive_n(bars + (B_EM + wg) * 8, 2);
      if (tw == 0) TS(17 + wg * 16);
      float p[4][16];
      uint32_t vp[8][4];
      const uint32_t av = sb + SM_V + (w * 16 + g) * 64 + ((t ^ (g >> 1)) << 4);
      {
        uint32_t kf[4][2][4];
#pragma unroll
        for (int u = 0; u < 4; u++)
#pragma unroll
          for (int s = 0; s < 2; s++)
#pragma unroll
            for (int r = 0; r < 4; r++) kf[u][s][r] = pack2(acc[u & 1][16 * (u >> 1) + 8 * s + 2 * r], acc[u & 1][16 * (u >> 1) + 8 * s + 2 * r + 1]);
        mbar_wait(bars + B_WPHI * 8, 0, budget);
        const uint64_t dw = P.dw + wg * 256;
        wg_fence();
#pragma unroll
        for (int u = 0; u < 4; u++) {
          wgmma_m64n32k16_rs<1>(p[u], kf[u][0], dw + (u >> 1) * 128, 0);
          wgmma_m64n32k16_rs<1>(p[u], kf[u][1], dw + (u >> 1) * 128 + 64, 1);
        }
        wg_commit();
#pragma unroll
        for (int u = 0; u < 8; u++) {
          const float* a = &acc[(u >> 1) & 1][32 + 16 * (u >> 2) + 2 * (u & 1)];
          vp[u][0] = pack2(a[0], a[1]); vp[u][1] = pack2(a[4], a[5]); vp[u][2] = pack2(a[8], a[9]); vp[u][3] = pack2(a[12], a[13]);
          if (u < 4) sts128(av + (u >> 1) * 4096 + (u & 1) * 512, vp[u][0], vp[u][1], vp[u][2], vp[u][3]);
        }
        pinr(vp);
        wg_wait<0>();
#pragma unroll
        for (int u = 0; u < 4; u++) pin(p[u]);
      }
      if (tw == 0) TS(18 + wg * 16);
      float kv[2][20];
      if (wg) mbar_wait(bars + B_RD * 8, 0, budget);
      {
        const uint32_t sphi = sb + SM_PHI + (w * 16 + (lane & 15)) * 128 + (((lane >> 4) ^ (lane & 7)) << 4);
        float top = 0.f;
        uint32_t pk[4][2][4];
        float ps[2], sa[4], sc[4];
        uint32_t redo = 0;
#pragma unroll
        for (int i = 0; i < 11; i++) {
          if (i >= 3) {
            const int j = i - 3;
            const float s0 = sc[0] + sc[2], s1 = sc[1] + sc[3];
            top = fmaxf(top, fmaxf(s0, s1));
            store_phi((sphi ^ ((j & 1) * 64)) + (j & 2) * 4096, pk[j & 3], rcp2(s0), rcp2(s1));
          }
          if (i >= 2 && i <= 9) {
            sc[0] = sa[0] + sa[2]; sc[1] = sa[1] + sa[3];
            sc[2] = __shfl_xor_sync(0xffffffffu, sc[0], 2); sc[3] = __shfl_xor_sync(0xffffffffu, sc[1], 2);
          }
          if (i >= 1 && i <= 8) {
            sa[0] = ps[0]; sa[1] = ps[1];
            sa[2] = __shfl_xor_sync(0xffffffffu, sa[0], 1); sa[3] = __shfl_xor_sync(0xffffffffu, sa[1], 1);
          }
          if (i < 8) {
            pin(p[i >> 1]);
            float e[16];
#pragma unroll
            for (int c = 0; c < 16; c++) e[c] = ex2((i & 1) ? -p[i >> 1][c] : p[i >> 1][c]);
            pack_sums(e, pk[i & 3], ps);
            pinr(pk[i & 3]); pin(ps);
          }
          if (i < 10) yield_slot();
          if (i >= 2 && i <= 9) pin(sc);
          if (i >= 1 && i <= 8) pin(sa);
          if (i >= 4 && !(i & 1)) {
            const int u = (i - 4) >> 1;
            fence_async_smem();
            wg_wait<0>();
            if (u < 3) bar_sync(7 + wg, 128);
            else asm volatile("{\n.reg .pred p, q;\nsetp.ne.b32 p, %2, 0;\nbar.red.or.pred q, %1, 128, p;\nselp.u32 %0, 1, 0, q;\n}"
                              : "=r"(redo) : "r"(7 + wg), "r"((uint32_t)!(top < EXP_LIM_F)) : "memory");
            issue_kv(kv[u >> 1], P.dphi + (u & 1) * 512, P.dv - (u & 1) * DV_TILE, u & 1);
            if (u == 1 || u == 2) {
#pragma unroll
              for (int r = 0; r < 2; r++) sts128(av + ((u + 1) & 1) * 4096 + r * 512, vp[2 * u + 2 + r][0], vp[2 * u + 2 + r][1], vp[2 * u + 2 + r][2], vp[2 * u + 2 + r][3]);
            }
            if (u < 3) yield_slot();
          }
        }
        if (tw == 0) TS(19 + wg * 16);
        wg_wait<0>();
        pin(kv[0]); pin(kv[1]);
        if (__builtin_expect(__any_sync(0xffffffffu, redo), 0)) {
#pragma unroll 1
          for (int u = 0; u < 4; u++) {
            bar_sync(7 + wg, 128);
#pragma unroll 1
            for (int sg = 0; sg < 2; sg++) {
              float e[16];
              exp_shifted(p[0], sg ? -1.f : 1.f, e);
              pack_sums(e, pk[0], ps);
              store_phi(sphi ^ (sg * 64), pk[0], rcp2(qsum(ps[0])), rcp2(qsum(ps[1])));
            }
            sts128(av, vp[0][0], vp[0][1], vp[0][2], vp[0][3]);
            sts128(av + 512, vp[1][0], vp[1][1], vp[1][2], vp[1][3]);
            fence_async_smem();
            bar_sync(7 + wg, 128);
            issue_kv(kv[1], P.dphi, P.dv, u & 1);
            wg_wait<0>();
            pin(kv[1]);
#pragma unroll
            for (int c = 0; c < 16; c++) { p[0][c] = p[1][c]; p[1][c] = p[2][c]; p[2][c] = p[3][c]; }
#pragma unroll
            for (int c = 0; c < 24; c++) vp[c >> 2][c & 3] = vp[(c >> 2) + 2][c & 3];
            if (u == 1) {
#pragma unroll
              for (int c = 0; c < 20; c++) kv[0][c] = kv[1][c];
            }
          }
        }
      }
      if (tw == 0) TS(20 + wg * 16);
      bar_sync(7 + wg, 128);
      {
        const int srow = w * 16 + (lane & 15);
        const uint32_t a0 = sb + SM_PHI + srow * 64 + (((lane >> 4) ^ ((srow >> 1) & 3)) << 4);
#pragma unroll
        for (int q = 0; q < 4; q++) {
          const float* a = &kv[q >> 1][8 * (q & 1)];
          stmatrix4((a0 ^ ((q & 1) * 32)) + (q >> 1) * 4096, pack2(a[0], a[1]), pack2(a[2], a[3]), pack2(a[4], a[5]), pack2(a[6], a[7]));
        }
        const uint32_t z = pack2(t == 0 ? kv[0][16] : t == 1 ? kv[1][16] : t == 2 ? kv[0][18] : kv[1][18], 0.0625f);
        sts128(sb + SM_PHI + 8192 + ((w & 1) * 16 + (t >> 1) * 8 + g) * 64 + ((((w & 2) + (t & 1)) ^ (g >> 1)) << 4), z, z, z, z);
      }
      fence_async_smem();
      warp_arrive(bars + (B_RED + wg) * 8, lane);
      if (tw == 0) TS(51 + wg * 4);
    }

    uint32_t stash = sb + 3 * STAGE + 8192 + w * 2048 + lane * 16;
    const int rowl = wg * 64 + w * 16 + g;
    mbar_wait(bars + B_INFO * 8, 0, budget);
    const float gA = ldsf(sb + SM_G + rowl * 4), gB = ldsf(sb + SM_G + rowl * 4 + 32);
    __nv_bfloat16* og = P.o + (size_t)(bi * 128 + rowl) * kD + bj * 128 + t * 8;
    uint32_t own = sb + 3 * STAGE + rowl * 128 + ((t ^ g) << 4);
    uint32_t sx = sb + SM_PHI + (wg * 64 + w * 16 + (lane & 15)) * 128 + (((lane >> 4) ^ (lane & 7)) << 4);
    uint32_t routed = (lds32(sb + SM_MISC + 4) >> 4) == (uint32_t)(bi * 8 + warp);
    asm volatile("" : "+l"(og), "+r"(own), "+r"(stash), "+r"(sx), "+r"(routed));
    {
      float p[4][16];
      uint32_t ef[2][4][4];
      uint32_t top = EXP_TOP;
      if (wg == 0) {
        float acc[2][64];
        bar_sync(2, 256);
        if (tw == 0) TS(22);
        mainloop128(acc, P.da, P.db, 32 % NST, (32 / NST) & 1, 12, lane0, budget, cta, 32);
#pragma unroll 1
        for (int n = 0; n < 4; n++) {
          const uint32_t slot = n ? n - 1 : 4;
          if (tw == 0) KS(128 + 44 + n);
          mbar_wait(bars + B_FX * 8 + slot * 8, n != 0, budget);
          if (tw == 0) KS(44 + n);
          kstep64(acc[0], P.da + slot * (STAGE >> 4), P.db + slot * (STAGE >> 4), 1);
          wg_wait<1>();
          if (n == 0 && lane0) mbar_arrive_n(bars + (B_EM + 43 % NST) * 8, 2);
        }
        kstep64(acc[1], P.da + 512 + (44 % NST) * (STAGE >> 4), P.db + (44 % NST) * (STAGE >> 4), 1);
        wg_wait<1>();
        pin(acc[0]);
        if (tw == 0) TS(15);
        {
          uint32_t qf[4][2][4];
#pragma unroll
          for (int u = 0; u < 8; u++)
#pragma unroll
            for (int r = 0; r < 4; r++) qf[u >> 1][u & 1][r] = pack2(acc[0][8 * u + 2 * r], acc[0][8 * u + 2 * r + 1]);
          issue_pq(p, qf, P.dw);
          kstep64(acc[1], P.da + 512 + (45 % NST) * (STAGE >> 4), P.db + (45 % NST) * (STAGE >> 4), 1);
          wg_wait<1>();
        }
#pragma unroll
        for (int h = 0; h < 4; h++) pin(p[h]);
        if (tw == 0) TS(24);
#pragma unroll
        for (int h = 0; h < 2; h++) {
          if (lane0) mbar_arrive_n(bars + (B_EM + (44 + h) % NST) * 8, 2);
          kstep64(acc[1], P.da + 512 + ((46 + h) % NST) * (STAGE >> 4), P.db + ((46 + h) % NST) * (STAGE >> 4), 1);
          yield_slot();
          pin(p[h]);
          top = exp_frags(p[h], ef[h], top);
          pinr(ef[h]);
          yield_slot();
          if (h == 0) wg_wait<1>(); else wg_wait<0>();
        }
        pin(acc[1]);
        if (lane0) { mbar_arrive_n(bars + (B_EM + 46 % NST) * 8, 2); mbar_arrive_n(bars + (B_EM + 47 % NST) * 8, 2); }
        if (tw == 0) TS(23);
        RG(0);
#pragma unroll
        for (int u = 0; u < 8; u++) {
          const float* a = &acc[1][8 * u];
          sts128(stash + (u >> 2) * STAGE + (u & 3) * 512, pack2(a[0], a[1]), pack2(a[2], a[3]), pack2(a[4], a[5]), pack2(a[6], a[7]));
        }
        warp_arrive(bars + B_QS * 8, lane);
        RG(1);
      } else {
        uint32_t qf[4][2][4];
        mbar_wait(bars + B_QS * 8, 0, budget);
        RG(1);
#pragma unroll
        for (int u = 0; u < 8; u++) lds128(stash + (u >> 2) * STAGE + (u & 3) * 512, qf[u >> 1][u & 1]);
        __syncwarp();
        issue_pq(p, qf, P.dw);
        wg_wait<0>();
#pragma unroll
        for (int h = 0; h < 4; h++) pin(p[h]);
        if (tw == 0) TS(40);
      }

#pragma unroll 1
      for (int pr = 0; pr < 2; pr++) {
        RG(2 + pr * 8);
        if (YIELD_EXP && pr > wg) bar_sync(11, 256);
        if (pr | wg) top = exp_frags(p[1], ef[1], exp_frags(p[0], ef[0], EXP_TOP));
        if (YIELD_EXP && pr < wg) { pinr(ef[0]); pinr(ef[1]); bar_arrive(11, 256); }
        if (__builtin_expect(__any_sync(0xffffffffu, top != EXP_TOP), 0)) {
#pragma unroll 1
          for (int u = 0; u < 4; u++) {
            float e[16];
            exp_shifted(p[0], (u & 1) ? -1.f : 1.f, e);
#pragma unroll
            for (int r = 0; r < 4; r++) {
#pragma unroll
              for (int s = 0; s < 6; s++) ef[s >> 2][s & 3][r] = ef[(s + 2) >> 2][(s + 2) & 3][r];
              ef[1][2][r] = pack2(e[2 * r], e[2 * r + 1]);
              ef[1][3][r] = pack2(e[8 + 2 * r], e[8 + 2 * r + 1]);
            }
            if (u & 1) {
#pragma unroll
              for (int e2 = 0; e2 < 16; e2++) p[0][e2] = p[1][e2];
            }
          }
        }
        float np[2][20], nm[2][20];
        RG(3 + pr * 8);
        mbar_wait(bars + (B_KV + pr) * 8, 0, budget);
        RG(4 + pr * 8);
        wg_fence();
#pragma unroll
        for (int hh = 0; hh < 2; hh++) {
          const uint64_t dk = P.dv - (uint64_t)pr * ((384ull << 16) - 512ull) - hh * ((255ull << 16) - 256ull);
          wgmma_m64n40k16_rs<1>(np[hh], ef[hh][0], dk, 0);
          wgmma_m64n40k16_rs<1>(np[hh], ef[hh][1], dk + 64, 1);
          wgmma_m64n40k16_rs<1>(nm[hh], ef[hh][2], dk + 128 - (126ull << 16), 0);
          wgmma_m64n40k16_rs<1>(nm[hh], ef[hh][3], dk + 192 - (126ull << 16), 1);
          wg_commit();
        }
#pragma unroll
        for (int e = 0; e < 16; e++) { p[0][e] = p[2][e]; p[1][e] = p[3][e]; }
        pin(p[0]); pin(p[1]);
#pragma unroll
        for (int hh = 0; hh < 2; hh++) {
          if (hh == 0) wg_wait<1>(); else wg_wait<0>();
          pin(np[hh]); pin(nm[hh]);
          RG(5 + hh + pr * 8);
          uint32_t o[2][4];
#pragma unroll
          for (int r = 0; r < 2; r++) {
            const float dp = np[hh][16 + 2 * r], sp = np[hh][17 + 2 * r], dm = nm[hh][16 + 2 * r], sm = nm[hh][17 + 2 * r];
            const float inv = (r == 0 ? gA : gB) * rcp(fmaf(dp, sm, fmaf(1e-6f, sm, dm) * sp));
            const float cp = sm * inv, cm = sp * inv;
#pragma unroll
            for (int c = 0; c < 4; c++)
              o[r][c] = pack2(fmaf(np[hh][4 * c + 2 * r], cp, nm[hh][4 * c + 2 * r] * cm), fmaf(np[hh][4 * c + 2 * r + 1], cp, nm[hh][4 * c + 2 * r + 1] * cm));
            sts128((own ^ (hh * 64)) + r * 1024, o[r][0], o[r][1], o[r][2], o[r][3]);
          }
          if (hh == 1 && pr == 1) fence_async_smem();
#pragma unroll
          for (int r = 0; r < 2; r++) *reinterpret_cast<uint4*>(og + r * 8 * kD + hh * 32) = make_uint4(o[r][0], o[r][1], o[r][2], o[r][3]);
        }
        RG(7 + pr * 8);
        warp_arrive(bars + (B_PUB + wg * 2 + pr) * 8, lane);
        RG(8 + pr * 8);
        if (tw == 0) TS(25 + pr + wg * 16);
        og += 64; own += STAGE;
      }
    }
    bar_sync(7 + wg, 128);

    RG(18);
    float oacc[64];
    uint32_t xf[8][4];
    {
      const uint64_t dam = P.da + wg * 512;
      mbar_wait(bars + (B_FX + 3) * 8, 1, budget);
      kstep64(oacc, dam + 3 * (STAGE >> 4), P.db + 3 * (STAGE >> 4), 0);
      if (tw == 0) TS(27 + wg * 16);
      mbar_wait(bars + (B_FX + 4) * 8, 1, budget);
      kstep64(oacc, dam + 4 * (STAGE >> 4), P.db + 4 * (STAGE >> 4), 1);
      wg_wait<1>();
      if (lane0) mbar_arrive(bars + (B_EM + 3) * 8);
      wg_wait<0>();
      if (lane0) mbar_arrive(bars + (B_EM + 4) * 8);
      mbar_wait(bars + B_XT * 8, 0, budget);
      load_x(sx, xf);
      uint32_t slot = 0, ph = 0, prev = 0;
#pragma unroll 1
      for (int s = 2; s < 16; s++) {
        if (tid == 0) KS(128 + 48 + s);
        mbar_wait(bars + B_FX * 8 + slot * 8, ph, budget);
        mbar_wait(bars + (B_FY + wg * NST) * 8 + slot * 8, ph, budget);
        if (tid == 0) KS(48 + s);
        if (tid == 128) KS(192 + 48 + s);
        if (END_SKEW && s == 16 - END_SKEW && wg) bar_sync(12, 256);
        const uint64_t da = dam + slot * (STAGE >> 4), db = P.db + slot * (STAGE >> 4);
#pragma unroll
        for (int hf = 0; hf < 2; hf++) {
          wg_wait<1>();
          if (hf && s > 2 && lane0) mbar_arrive(bars + B_EM * 8 + prev * 8);
          wg_fence();
          wgmma_m64n128k16_ss<0, 1>(oacc, da + hf * 4, db + hf * 256, 1);
          wgmma_m64n128k16_ss<0, 1>(oacc, da + hf * 4 + 2, db + hf * 256 + 128, 1);
          wg_commit();
        }
        prev = slot;
        if (++slot == NST) { slot = 0; ph ^= 1; }
      }
      if (END_SKEW && !wg) bar_arrive(12, 256);
    }
    if (__any_sync(0xffffffffu, routed)) { mbar_wait(bars + B_XP * 8, 0, budget); load_x(sx, xf); }
    const float hA = 1.0f - gA, hB = 1.0f - gB;
    float xv[64];
#pragma unroll
    for (int i = 0; i < 32; i++) { xv[2 * i] = bf_lo(xf[i >> 2][i & 3]); xv[2 * i + 1] = bf_hi(xf[i >> 2][i & 3]); }
    pin(xv);
    yield_slot();
    wg_wait<0>();
    pin(oacc);
    if (tw == 0) TS(29 + wg * 16);
#pragma unroll
    for (int hf = 0; hf < 2; hf++) {
#pragma unroll
      for (int u = hf * 4; u < hf * 4 + 4; u++) {
        const float* a = &oacc[8 * u];
        const float* b = &xv[8 * u];
        stmatrix4((sx ^ ((u & 3) * 32)) + hf * 16384,
                  pack2(fmaf(hA, b[0], a[0]), fmaf(hA, b[1], a[1])), pack2(fmaf(hB, b[2], a[2]), fmaf(hB, b[3], a[3])),
                  pack2(fmaf(hA, b[4], a[4]), fmaf(hA, b[5], a[5])), pack2(fmaf(hB, b[6], a[6]), fmaf(hB, b[7], a[7])));
        if (FIN_YIELD) yield_slot();
      }
      fence_async_smem();
      __syncwarp();
      if (elect_one()) tma_store(&mout, sb + SM_PHI + hf * 16384 + warp * 2048, bj * 128 + hf * 64, bi * 128 + warp * 16);
    }
    if (elect_one()) {
      asm volatile("cp.async.bulk.commit_group;" ::: "memory");
      asm volatile("cp.async.bulk.wait_group.read 0;" ::: "memory");
    }
  } else {
    asm volatile("setmaxnreg.dec.sync.aligned.u32 32;");
    if (warp == 8) {
      if (elect_one()) {
        TS(7);
#pragma unroll
        for (int s = 0; s < NST; s++) mbar_init(bars + (B_FX + s) * 8, 1);
        asm volatile("fence.mbarrier_init.release.cluster;" ::: "memory");
        fence_async_smem();
      }
      __syncwarp();
      bar_arrive(0, 512);
      if (elect_one()) {
#pragma unroll 1
        for (int n = 0; n < NST; n++) {
          const uint32_t st = sb + n * STAGE, fb = bars + (B_FX + n) * 8;
          KS(64 + n);
          mbar_expect_tx(fb, STAGE);
          tma_load(st, &mx, fb, n * 64, bi * 128);
          tma_load(st + 16384, &mw, fb, 1024 + bj * 128, n * 64);
          tma_load(st + 24576, &mw, fb, 2048 + bj * 128, n * 64);
        }
      }
      __syncwarp();
      bar_sync(10, 64);
    } else {
      if (warp == 9) {
        if (elect_one()) {
#pragma unroll
          for (int s = B_FY; s < B_NUM; s++) mbar_init(bars + s * 8, s < B_WPHI ? 1 : s < B_EM ? 4 : 8);
          asm volatile("fence.mbarrier_init.release.cluster;" ::: "memory");
          fence_async_smem();
        }
        __syncwarp();
        bar_arrive(10, 64);
      }
      bar_sync(0, 512);
    }
    if (!elect_one()) return;
    if (warp == 8) {
      uint32_t slot = 0, ph = 0;
#pragma unroll 1
      for (int n = NST; n < 48; n++) {
        const int t = n >> 4, k = n & 15;
        const int c0 = t == 2 ? bj * 128 : 1024 + bj * 128 + t * 64, c1 = t == 2 ? c0 + 64 : c0 + 1024;
        const uint32_t st = sb + slot * STAGE, fb = bars + (B_FX + slot) * 8;
        if (n <= NST + 3 * RSTEP && (n - NST) % RSTEP == 0) {
          const int c = (n - NST) / RSTEP;
          mbar_expect_tx(bars + (B_RX + c) * 8, c == 0 ? 8192 + 4096 : 8192);
          tma_load(sb + SM_PHI + c * 8192, &mxr, bars + (B_RX + c) * 8, c * 256, bi * 128 + bj * 16);
          if (c == 0) { bulk_load(sb + SM_V, P.w_r, 2048, bars + B_RX * 8); bulk_load(sb + SM_V + 2048, P.gate_w, 2048, bars + B_RX * 8); }
        }
        mbar_wait(bars + (B_EM + slot) * 8, ph, budget);
        KS(64 + n);
        mbar_expect_tx(fb, STAGE);
        tma_load(st, &mx, fb, k * 64, bi * 128);
        tma_load(st + 16384, &mw, fb, c0, k * 64);
        tma_load(st + 24576, &mw, fb, c1, k * 64);
        {
          const int m = n + WLEAD, tm = m >> 4;
          if ((m & 3) == (bi & 3)) {
            const int d0 = tm >= 2 ? bj * 128 : 1024 + bj * 128 + tm * 64, d1 = tm >= 2 ? d0 + 64 : d0 + 1024;
            tma_prefetch(tm == 3 ? &mwo : &mw, d0, (m & 15) * 64); tma_prefetch(tm == 3 ? &mwo : &mw, d1, (m & 15) * 64);
          }
        }
        if (++slot == NST) { slot = 0; ph ^= 1; }
      }
#pragma unroll 1
      for (int m = WLEAD + ((bi - WLEAD) & 3); m < 16; m += 4) { tma_prefetch(&mwo, bj * 128, m * 64); tma_prefetch(&mwo, bj * 128 + 64, m * 64); }
#pragma unroll 1
      for (int s = 0; s < 16; s++) {
        const int p = s < 2 ? s : (s >= 9), q = s < 9 ? s - 2 : s - 9;
        const int k0 = (s < 2 ? bj : q + (q >= bj)) * 128 + p * 64;
        const uint32_t st = sb + slot * STAGE, fb = bars + (B_FX + slot) * 8;
        mbar_wait(bars + (B_EM + slot) * 8, ph, budget);
        KS(64 + 48 + s);
        mbar_expect_tx(fb, 16384);
        tma_load(st + 16384, &mwo, fb, bj * 128, k0);
        tma_load(st + 24576, &mwo, fb, bj * 128 + 64, k0);
        if (++slot == NST) { slot = 0; ph ^= 1; }
      }
    } else if (warp == 9) {
      prefetch_map(&mo); prefetch_map(&mout);
      uint32_t old;
      asm volatile("atom.add.release.gpu.global.u32 %0, [%1], 1;" : "=r"(old) : "l"(&g_cnt[C_START]) : "memory");
      sts32(sb + SM_MISC, (old & ~255u) + 256u);
      mbar_arrive(bars + B_EPOCH * 8);
      const CUtensorMap* m = (cta & 8) ? &mu : &mg;
      const int l0 = (cta >> 4) * 14, a0 = (cta & 7) * 64, d1 = (cta >> 2) * 112 - 14 * 16, d2 = (cta & 3) * 4;
      uint32_t buf = 0, ph = 0, tnext;
      asm volatile("mov.u32 %0, %%clock;" : "=r"(tnext));
#pragma unroll 1
      for (int c = 0; c < 21; c++) {
        const uint32_t dst = sb + moe_buf(buf), fb = bars + (B_MF + buf) * 8;
        mbar_wait(bars + (B_ME + buf) * 8, ph, budget);
        mbar_expect_tx(fb, 8192);
        if (c < 14) tma_load(dst, m, fb, a0 + ((l0 + c) >> 4) * 512, ((l0 + c) & 15) * 64); else tma_load3(dst, &md, fb, d1 + c * 16, d2);
        if (MLEAD && c >= 2 && c + MLEAD < 17) {
          const int f = c + MLEAD;
          if (f < 14) tma_prefetch(m, a0 + ((l0 + f) >> 4) * 512, ((l0 + f) & 15) * 64); else tma_prefetch3(&md, d1 + f * 16, d2);
        }
        if (MPACE) { uint32_t now; do { asm volatile("mov.u32 %0, %%clock;" : "=r"(now)); if ((int32_t)(now - tnext) >= 0) break; __nanosleep(20); } while (true); tnext = now + MPACE; }
        if (c == 16) {
#pragma unroll 1
          for (int f = 17; f < 21; f++) { __nanosleep(MGAP); tma_prefetch3(&md, d1 + f * 16, d2); }
        }
        if (c < 2) __nanosleep(MGAP);
        if (c == 17) mbar_arrive(bars + B_M2 * 8);
        if (++buf >= (c >= 14 ? 2 : 3)) { buf = 0; ph ^= 1; }
      }
      mbar_wait(bars + B_MD * 8, 0, budget);
      mbar_wait(bars + (B_RD + 1) * 8, 0, budget);
      mbar_wait(bars + XT_GATE * 8, 0, budget);
      mbar_expect_tx(bars + B_XT * 8, 32768);
      tma_load(sb + SM_PHI, &mx, bars + B_XT * 8, bj * 128, bi * 128);
      tma_load(sb + SM_PHI + 16384, &mx, bars + B_XT * 8, bj * 128 + 64, bi * 128);
      mbar_wait(bars + (B_PUB + 1) * 8, 0, budget);
      mbar_wait(bars + (B_PUB + 3) * 8, 0, budget);
      signal_add(&g_cnt[(C_O + bi * 4 + 1) * 32], 32u);
      TS(57);
      wait_count<POLLF>(&g_cnt[(C_O + bi * 4 + 1) * 32], (old & ~255u) + 256u, budget);
      mbar_arrive(bars + B_P1 * 8);
      TS(3);
    } else {
      const int u = warp - 10, hp = bj * 2 + u;
      mbar_wait(bars + B_EPOCH * 8, 0, budget);
      const uint32_t target = lds32(sb + SM_MISC);
      mbar_wait(bars + B_INFO * 8, 0, budget);
      wait_count<200>(&g_cnt[C_START], target, budget);
      fence_async_global();
#pragma unroll 1
      for (int e = 0; e < 2; e++) {
        uint32_t* cnt = &g_cnt[(e ? C_O + bi * 4 + u * 2 : C_KV + hp) * 32];
        mbar_wait(bars + (e ? B_PUB + u * 2 : B_RED + u) * 8, 0, budget);
        if (e == 0) {
#pragma unroll 1
          for (int c = 0; c < RED_CH; c++) {
            bulk_reduce(&g_kvr[hp * 2560 + c * (2560 / RED_CH)], sb + SM_PHI + c * (10240 / RED_CH), 10240 / RED_CH);
            if (c + 1 < RED_CH) __nanosleep(u ? RED_GAP1 : RED_GAP0);
          }
          asm volatile("cp.async.bulk.commit_group;" ::: "memory");
          asm volatile("cp.async.bulk.wait_group 0;" ::: "memory");
          TS(21 + u * 16);
          mbar_arrive(bars + (B_RD + u) * 8);
        }
        signal_add(cnt, e ? 32u : 16u);
        TS(e ? 56 + u * 2 : 60 + u);
        if (e == 0) {
          mbar_wait(bars + (u ? B_M2 : B_RED + 1) * 8, 0, budget);
        }
        wait_count<POLLF>(cnt, target, budget);
        fence_async_global();
        if (e == 0) {
          mbar_expect_tx(bars + (B_KV + u) * 8, 10240);
          bulk_load(sb + SM_V + u * 8192, &g_kvr[hp * 2560], 8192, bars + (B_KV + u) * 8);
          bulk_load(sb + SM_Z + u * 2048, &g_kvr[hp * 2560 + 2048], 2048, bars + (B_KV + u) * 8);
          TS(38 + u);
        }
      }
      TS(2 + u * 2);
      if (u == 0) mbar_wait(bars + B_QS * 8, 0, budget);
      uint32_t slot = 0, ph = 1;
#pragma unroll 1
      for (int s = 2; s < 16; s++) {
        const int p = s >= 9, q = s < 9 ? s - 2 : s - 9;
        if (s == 9) { mbar_wait(bars + B_P1 * 8, 0, budget); fence_async_global(); }
        const uint32_t fb = bars + (B_FY + u * NST + slot) * 8;
        mbar_wait(bars + (B_EM + slot) * 8, ph, budget);
        mbar_expect_tx(fb, 8192);
        tma_load(sb + slot * STAGE + u * 8192, &mo, fb, (q + (q >= bj)) * 128 + p * 64, bi * 128 + u * 64);
        if (++slot == NST) { slot = 0; ph ^= 1; }
      }
    }
  }
}

typedef CUresult (*EncodeFn)(CUtensorMap*, CUtensorMapDataType, cuuint32_t, void*, const cuuint64_t*, const cuuint64_t*, const cuuint32_t*,
                             const cuuint32_t*, CUtensorMapInterleave, CUtensorMapSwizzle, CUtensorMapL2promotion, CUtensorMapFloatOOBfill);

void make_map(EncodeFn enc, CUtensorMap* m, const void* ptr, uint64_t cols, uint64_t rows, uint32_t bc, uint32_t br, CUtensorMapSwizzle swz) {
  const cuuint64_t dims[2] = {cols, rows}, strides[1] = {cols * 2};
  const cuuint32_t box[2] = {bc, br}, es[2] = {1, 1};
  enc(m, CU_TENSOR_MAP_DATA_TYPE_BFLOAT16, 2, const_cast<void*>(ptr), dims, strides, box, es, CU_TENSOR_MAP_INTERLEAVE_NONE, swz,
      CU_TENSOR_MAP_L2_PROMOTION_L2_128B, CU_TENSOR_MAP_FLOAT_OOB_FILL_NONE);
}

}

extern "C" void kernel_launch(void* const* d_in, const int* in_sizes, int n_in, void* d_out, int out_size) {
  (void)in_sizes; (void)n_in; (void)out_size;
  void* fn = nullptr;
  cudaDriverEntryPointQueryResult qr;
  cudaGetDriverEntryPoint("cuTensorMapEncodeTiled", &fn, cudaEnableDefault, &qr);
  EncodeFn enc = (EncodeFn)fn;
  void* o_ptr = nullptr;
  cudaGetSymbolAddress(&o_ptr, g_o);
  CUtensorMap mx, mw, mwo, mo, mout, mxr, mg, mu, md;
  make_map(enc, &mx, d_in[0], kD, kS, 64, 128, CU_TENSOR_MAP_SWIZZLE_128B);
  make_map(enc, &mxr, d_in[0], kD, kS, 256, 16, CU_TENSOR_MAP_SWIZZLE_NONE);
  make_map(enc, &mw, d_in[1], 3 * kD, kD, 64, 64, CU_TENSOR_MAP_SWIZZLE_128B);
  make_map(enc, &mwo, d_in[3], kD, kD, 64, 64, CU_TENSOR_MAP_SWIZZLE_128B);
  make_map(enc, &mo, o_ptr, kD, kS, 64, 64, CU_TENSOR_MAP_SWIZZLE_128B);
  make_map(enc, &mout, d_out, kD, kS, 64, 16, CU_TENSOR_MAP_SWIZZLE_128B);
  make_map(enc, &mg, d_in[6], kF, kD, 64, 64, CU_TENSOR_MAP_SWIZZLE_128B);
  make_map(enc, &mu, d_in[7], kF, kD, 64, 64, CU_TENSOR_MAP_SWIZZLE_128B);
  {
    const cuuint64_t dims[3] = {64, kF, 16}, strides[2] = {kD * 2, 128};
    const cuuint32_t box[3] = {64, 16, 4}, es[3] = {1, 1, 1};
    enc(&md, CU_TENSOR_MAP_DATA_TYPE_BFLOAT16, 3, d_in[8], dims, strides, box, es, CU_TENSOR_MAP_INTERLEAVE_NONE, CU_TENSOR_MAP_SWIZZLE_128B,
        CU_TENSOR_MAP_L2_PROMOTION_L2_128B, CU_TENSOR_MAP_FLOAT_OOB_FILL_NONE);
  }
  Params P;
  P.x = (const __nv_bfloat16*)d_in[0];
  P.w = (const __nv_bfloat16*)d_in[1];
  P.o = (__nv_bfloat16*)o_ptr;
  P.w_phi = (const __nv_bfloat16*)d_in[2];
  P.w_r = (const __nv_bfloat16*)d_in[5];
  P.gate_w = (const __nv_bfloat16*)d_in[9];
  P.da = make_desc(sb, 16, 1024, 1);
  P.db = make_desc(sb + 16384, 8192, 1024, 1);
  P.dw = make_desc(sb + SM_WPHI, 16, 512, 2);
  P.dphi = make_desc(sb + SM_PHI, 16, 1024, 1);
  P.dv = make_desc(sb + SM_V, SM_Z - SM_V, 512, 2);
  P.dband = make_desc(sb + SM_BAND, 128, 128, 0);
  P.dxs = make_desc(sb + SM_BAND, 16, 128, 0);
  int dev = 0, sms = 0;
  cudaGetDevice(&dev);
  cudaDeviceGetAttribute(&sms, cudaDevAttrMultiProcessorCount, dev);
  auto kern = sms == 132 ? fused_kernel<true> : fused_kernel<false>;
  cudaFuncSetAttribute(kern, cudaFuncAttributeMaxDynamicSharedMemorySize, SM_ALLOC);
  kern<<<132, 512, SM_ALLOC, cudaStreamPerThread>>>(mx, mw, mwo, mo, mout, mxr, mg, mu, md, P);
}
```

```cpp
#include <cuda_runtime.h>
#include <cuda_bf16.h>
#include <cuda.h>
#include <stdint.h>

namespace {

template<int TA, int TB> __device__ __forceinline__ void wgmma_m64n128k16_ss(float (&d)[64], uint64_t da, uint64_t db, int scale_d) {
  asm volatile("{\n.reg .pred p;\nsetp.ne.b32 p, %66, 0;\n"
    "wgmma.mma_async.sync.aligned.m64n128k16.f32.bf16.bf16 "
    "{%0, %1, %2, %3, %4, %5, %6, %7, %8, %9, %10, %11, %12, %13, %14, %15, "
    "%16, %17, %18, %19, %20, %21, %22, %23, %24, %25, %26, %27, %28, %29, %30, %31, "
    "%32, %33, %34, %35, %36, %37, %38, %39, %40, %41, %42, %43, %44, %45, %46, %47, "
    "%48, %49, %50, %51, %52, %53, %54, %55, %56, %57, %58, %59, %60, %61, %62, %63}, "
    "%64, %65, p, 1, 1, %67, %68;\n}\n"
    : "+f"(d[0]), "+f"(d[1]), "+f"(d[2]), "+f"(d[3]), "+f"(d[4]), "+f"(d[5]), "+f"(d[6]), "+f"(d[7]),
      "+f"(d[8]), "+f"(d[9]), "+f"(d[10]), "+f"(d[11]), "+f"(d[12]), "+f"(d[13]), "+f"(d[14]), "+f"(d[15]),
      "+f"(d[16]), "+f"(d[17]), "+f"(d[18]), "+f"(d[19]), "+f"(d[20]), "+f"(d[21]), "+f"(d[22]), "+f"(d[23]),
      "+f"(d[24]), "+f"(d[25]), "+f"(d[26]), "+f"(d[27]), "+f"(d[28]), "+f"(d[29]), "+f"(d[30]), "+f"(d[31]),
      "+f"(d[32]), "+f"(d[33]), "+f"(d[34]), "+f"(d[35]), "+f"(d[36]), "+f"(d[37]), "+f"(d[38]), "+f"(d[39]),
      "+f"(d[40]), "+f"(d[41]), "+f"(d[42]), "+f"(d[43]), "+f"(d[44]), "+f"(d[45]), "+f"(d[46]), "+f"(d[47]),
      "+f"(d[48]), "+f"(d[49]), "+f"(d[50]), "+f"(d[51]), "+f"(d[52]), "+f"(d[53]), "+f"(d[54]), "+f"(d[55]),
      "+f"(d[56]), "+f"(d[57]), "+f"(d[58]), "+f"(d[59]), "+f"(d[60]), "+f"(d[61]), "+f"(d[62]), "+f"(d[63])
    : "l"(da), "l"(db), "r"(scale_d), "n"(TA), "n"(TB));
}

template<int TB> __device__ __forceinline__ void wgmma_m64n32k16_rs(float (&d)[16], const uint32_t (&a)[4], uint64_t db, int scale_d) {
  asm volatile("{\n.reg .pred p;\nsetp.ne.b32 p, %21, 0;\n"
    "wgmma.mma_async.sync.aligned.m64n32k16.f32.bf16.bf16 "
    "{%0, %1, %2, %3, %4, %5, %6, %7, %8, %9, %10, %11, %12, %13, %14, %15}, "
    "{%16, %17, %18, %19}, %20, p, 1, 1, %22;\n}\n"
    : "+f"(d[0]), "+f"(d[1]), "+f"(d[2]), "+f"(d[3]), "+f"(d[4]), "+f"(d[5]), "+f"(d[6]), "+f"(d[7]),
      "+f"(d[8]), "+f"(d[9]), "+f"(d[10]), "+f"(d[11]), "+f"(d[12]), "+f"(d[13]), "+f"(d[14]), "+f"(d[15])
    : "r"(a[0]), "r"(a[1]), "r"(a[2]), "r"(a[3]), "l"(db), "r"(scale_d), "n"(TB));
}

template<int TA, int TB> __device__ __forceinline__ void wgmma_m64n40k16_ss(float (&d)[20], uint64_t da, uint64_t db, int scale_d) {
  asm volatile("{\n.reg .pred p;\nsetp.ne.b32 p, %22, 0;\n"
    "wgmma.mma_async.sync.aligned.m64n40k16.f32.bf16.bf16 "
    "{%0, %1, %2, %3, %4, %5, %6, %7, %8, %9, %10, %11, %12, %13, %14, %15, "
    "%16, %17, %18, %19}, "
    "%20, %21, p, 1, 1, %23, %24;\n}\n"
    : "+f"(d[0]), "+f"(d[1]), "+f"(d[2]), "+f"(d[3]), "+f"(d[4]), "+f"(d[5]), "+f"(d[6]), "+f"(d[7]),
      "+f"(d[8]), "+f"(d[9]), "+f"(d[10]), "+f"(d[11]), "+f"(d[12]), "+f"(d[13]), "+f"(d[14]), "+f"(d[15]),
      "+f"(d[16]), "+f"(d[17]), "+f"(d[18]), "+f"(d[19])
    : "l"(da), "l"(db), "r"(scale_d), "n"(TA), "n"(TB));
}

template<int TB> __device__ __forceinline__ void wgmma_m64n40k16_rs(float (&d)[20], const uint32_t (&a)[4], uint64_t db, int scale_d) {
  asm volatile("{\n.reg .pred p;\nsetp.ne.b32 p, %25, 0;\n"
    "wgmma.mma_async.sync.aligned.m64n40k16.f32.bf16.bf16 "
    "{%0, %1, %2, %3, %4, %5, %6, %7, %8, %9, %10, %11, %12, %13, %14, %15, "
    "%16, %17, %18, %19}, "
    "{%20, %21, %22, %23}, %24, p, 1, 1, %26;\n}\n"
    : "+f"(d[0]), "+f"(d[1]), "+f"(d[2]), "+f"(d[3]), "+f"(d[4]), "+f"(d[5]), "+f"(d[6]), "+f"(d[7]),
      "+f"(d[8]), "+f"(d[9]), "+f"(d[10]), "+f"(d[11]), "+f"(d[12]), "+f"(d[13]), "+f"(d[14]), "+f"(d[15]),
      "+f"(d[16]), "+f"(d[17]), "+f"(d[18]), "+f"(d[19])
    : "r"(a[0]), "r"(a[1]), "r"(a[2]), "r"(a[3]), "l"(db), "r"(scale_d), "n"(TB));
}

template<int TA, int TB> __device__ __forceinline__ void wgmma_m64n8k16_ss(float (&d)[4], uint64_t da, uint64_t db, int scale_d) {
  asm volatile("{\n.reg .pred p;\nsetp.ne.b32 p, %6, 0;\n"
    "wgmma.mma_async.sync.aligned.m64n8k16.f32.bf16.bf16 "
    "{%0, %1, %2, %3}, "
    "%4, %5, p, 1, 1, %7, %8;\n}\n"
    : "+f"(d[0]), "+f"(d[1]), "+f"(d[2]), "+f"(d[3])
    : "l"(da), "l"(db), "r"(scale_d), "n"(TA), "n"(TB));
}

constexpr int kS = 2048, kD = 1024, kF = 3584;
constexpr int NST = 5, STAGE = 32768;
constexpr uint32_t sb = 1024;
constexpr int SM_V    = NST * STAGE;
constexpr int SM_Z    = SM_V + 16384;
constexpr int SM_PHI  = SM_Z + 4096;
constexpr int SM_MOE  = SM_PHI + 16384;
constexpr int SM_WPHI = SM_MOE + 16384;
constexpr int SM_BAND = SM_WPHI + 8192;
constexpr int SM_G    = SM_BAND + 2176;
constexpr int SM_BAR  = SM_G + 512;
constexpr int SM_MISC = SM_BAR + 448;
constexpr int SM_TOTAL = SM_MISC + 64;
static_assert(SM_TOTAL <= 232448, "smem");
constexpr uint32_t bars = sb + SM_BAR;
constexpr int B_FX = 0  , B_FY = 5  , B_XT = 15, B_EPOCH = 16, B_RX = 17  , B_MF = 21  , B_RD = 24  , B_KV = 26  , B_M2 = 28, B_P1 = 29;
constexpr int B_WPHI = 30, B_INFO = 31, B_QS = 32, B_XP = 33, B_RED = 34  , B_PUB = 36  , B_ME = 40  , B_MD = 43;
constexpr int B_EM = 44  , B_NUM = 49;
constexpr int C_START = 0, C_O = 1, C_KV = C_O + 64;

__device__ uint2 g_gate[kS];
__device__ uint2 g_key[128];
__device__ uint2 g_pre[4 * kF];
__device__ uint2 g_yp[32 * kD];
__device__ __align__(128) uint32_t g_kvr[16 * 2560];
__device__ __align__(128) uint32_t g_cnt[(C_KV + 32) * 32];
__device__ __align__(1024) __nv_bfloat16 g_o[kS * kD];
#define KS(id)
#define RG(id)
#define TS(id)
#define TSG(id)
constexpr int SM_ALLOC = SM_TOTAL;

#define POLL0 500
#define POLL1 150
#define RSTEP 1
#define POLLR 400
#define EARLY_N 2
#define EARLY_GAP 200
#define POLLF 50
#define RED_CH 10
#define RED_GAP0 250
#define RED_GAP1 0
#define YIELD_EXP 1
#define END_SKEW 3
#define XT_GATE B_QS
#define FIN_YIELD 0
#define MLEAD 0
#define MPACE 0
#define REPF 1
#define HOLD_OWN 2
#define XLATE 0
#define XS 1
#define XGAP 250
#define WLEAD 11
#define MGAP 300

struct Params {
  const __nv_bfloat16 *x, *w, *w_phi, *w_r, *gate_w;
  __nv_bfloat16* o;
  uint64_t da, db, dw, dphi, dv, dband, dxs;
};

__device__ __forceinline__ uint32_t smem_u32(const void* p) { return (uint32_t)__cvta_generic_to_shared(p); }
__device__ __forceinline__ void mbar_init(uint32_t bar, uint32_t cnt) { asm volatile("mbarrier.init.shared::cta.b64 [%0], %1;" :: "r"(bar), "r"(cnt) : "memory"); }
__device__ __forceinline__ void mbar_expect_tx(uint32_t bar, uint32_t bytes) { asm volatile("mbarrier.arrive.expect_tx.shared::cta.b64 _, [%0], %1;" :: "r"(bar), "r"(bytes) : "memory"); }
__device__ __forceinline__ void mbar_arrive(uint32_t bar) { asm volatile("mbarrier.arrive.shared::cta.b64 _, [%0];" :: "r"(bar) : "memory"); }
__device__ __forceinline__ void mbar_arrive_n(uint32_t bar, uint32_t n) { asm volatile("mbarrier.arrive.shared::cta.b64 _, [%0], %1;" :: "r"(bar), "r"(n) : "memory"); }
constexpr int BUDGET = 1 << 20;
__device__ __forceinline__ void mbar_wait(uint32_t bar, uint32_t parity, int& budget) {
  asm volatile("{\n.reg .pred p;\n"
               "WAIT_L:\nmbarrier.try_wait.parity.shared::cta.b64 p, [%1], %2;\n@p bra WAIT_D;\n"
               "add.s32 %0, %0, -1;\nsetp.gt.s32 p, %0, 0;\n@p bra WAIT_L;\nWAIT_D:\n}"
               : "+r"(budget) : "r"(bar), "r"(parity) : "memory");
}
template <int SLEEP>
__device__ __forceinline__ void wait_count(const uint32_t* p, uint32_t target, int& budget) {
  asm volatile("{\n.reg .pred p;\n.reg .s32 v;\n"
               "WAIT_L:\nld.acquire.gpu.global.s32 v, [%1];\nsub.s32 v, v, %2;\nsetp.ge.s32 p, v, 0;\n@p bra WAIT_D;\n"
               "nanosleep.u32 %3;\nadd.s32 %0, %0, -4;\nsetp.gt.s32 p, %0, 0;\n@p bra WAIT_L;\nWAIT_D:\n}"
               : "+r"(budget) : "l"(p), "r"(target), "n"(SLEEP) : "memory");
}
__device__ __forceinline__ void tma_load(uint32_t dst, const CUtensorMap* m, uint32_t bar, int c0, int c1) {
  asm volatile("cp.async.bulk.tensor.2d.shared::cluster.global.mbarrier::complete_tx::bytes [%0], [%1, {%3, %4}], [%2];"
    :: "r"(dst), "l"(m), "r"(bar), "r"(c0), "r"(c1) : "memory");
}
__device__ __forceinline__ void tma_load3(uint32_t dst, const CUtensorMap* m, uint32_t bar, int c1, int c2) {
  asm volatile("cp.async.bulk.tensor.3d.shared::cluster.global.mbarrier::complete_tx::bytes [%0], [%1, {%5, %3, %4}], [%2];"
    :: "r"(dst), "l"(m), "r"(bar), "r"(c1), "r"(c2), "r"(0) : "memory");
}
__device__ __forceinline__ void tma_prefetch3(const CUtensorMap* m, int c1, int c2) {
  asm volatile("cp.async.bulk.prefetch.tensor.3d.L2.global [%0, {%3, %1, %2}];" :: "l"(m), "r"(c1), "r"(c2), "r"(0) : "memory");
}
__device__ __forceinline__ void tma_prefetch(const CUtensorMap* m, int c0, int c1) {
  asm volatile("cp.async.bulk.prefetch.tensor.2d.L2.global [%0, {%1, %2}];" :: "l"(m), "r"(c0), "r"(c1) : "memory");
}
__device__ __forceinline__ void tma_store(const CUtensorMap* m, uint32_t src, int c0, int c1) {
  asm volatile("cp.async.bulk.tensor.2d.global.shared::cta.bulk_group [%0, {%2, %3}], [%1];" :: "l"(m), "r"(src), "r"(c0), "r"(c1) : "memory");
}
__device__ __forceinline__ void bulk_load(uint32_t dst, const void* src, uint32_t bytes, uint32_t bar) {
  asm volatile("cp.async.bulk.shared::cluster.global.mbarrier::complete_tx::bytes [%0], [%1], %2, [%3];" :: "r"(dst), "l"(src), "r"(bytes), "r"(bar) : "memory");
}
__device__ __forceinline__ void bulk_reduce(void* dst, uint32_t src, uint32_t bytes) {
  asm volatile("cp.reduce.async.bulk.global.shared::cta.bulk_group.add.noftz.bf16 [%0], [%1], %2;" :: "l"(dst), "r"(src), "r"(bytes) : "memory");
}
__device__ __forceinline__ void prefetch_map(const CUtensorMap* m) { asm volatile("prefetch.tensormap [%0];" :: "l"(m) : "memory"); }
__device__ __forceinline__ bool elect_one() {
  uint32_t p;
  asm volatile("{\n.reg .pred P;\nelect.sync _|P, 0xffffffff;\nselp.u32 %0, 1, 0, P;\n}" : "=r"(p));
  return p;
}
__device__ __forceinline__ void wg_fence() { asm volatile("wgmma.fence.sync.aligned;" ::: "memory"); }
__device__ __forceinline__ void wg_commit() { asm volatile("wgmma.commit_group.sync.aligned;" ::: "memory"); }
template <int N> __device__ __forceinline__ void wg_wait() { asm volatile("wgmma.wait_group.sync.aligned %0;" :: "n"(N) : "memory"); }
template <int N> __device__ __forceinline__ void zero(float (&r)[N]) {
#pragma unroll
  for (int i = 0; i < N; i++) r[i] = 0.f;
}
template <int N> __device__ __forceinline__ void pin(float (&r)[N]) {
#pragma unroll
  for (int i = 0; i < N; i++) asm volatile("" : "+f"(r[i]) :: "memory");
}
template <int N> __device__ __forceinline__ void pinr(uint32_t (&r)[N][4]) {
#pragma unroll
  for (int i = 0; i < N; i++) asm volatile("" : "+r"(r[i][0]), "+r"(r[i][1]), "+r"(r[i][2]), "+r"(r[i][3]) :: "memory");
}
__device__ __forceinline__ void fence_async_smem() { asm volatile("fence.proxy.async.shared::cta;" ::: "memory"); }
__device__ __forceinline__ void fence_async_global() { asm volatile("fence.proxy.async.global;" ::: "memory"); }
__device__ __forceinline__ void bar_sync(int id, int n) { asm volatile("bar.sync %0, %1;" :: "r"(id), "r"(n) : "memory"); }
__device__ __forceinline__ void bar_arrive(int id, int n) { asm volatile("bar.arrive %0, %1;" :: "r"(id), "r"(n) : "memory"); }
__device__ __forceinline__ void warp_arrive(uint32_t bar, int lane) { __syncwarp(); if (lane == 0) mbar_arrive(bar); }
__host__ __device__ constexpr uint64_t make_desc(uint32_t addr, uint32_t lbo, uint32_t sbo, uint32_t swz) {
  return (uint64_t)((addr & 0x3FFFF) >> 4) | ((uint64_t)((lbo & 0x3FFFF) >> 4) << 16) | ((uint64_t)(sbo >> 4) << 32) | ((uint64_t)swz << 62);
}
__device__ __forceinline__ uint32_t pack2(float lo, float hi) {
  uint32_t r; asm("cvt.rn.bf16x2.f32 %0, %1, %2;" : "=r"(r) : "f"(hi), "f"(lo)); return r;
}
__device__ __forceinline__ float bf_lo(uint32_t v) { return __uint_as_float(v << 16); }
__device__ __forceinline__ float bf_hi(uint32_t v) { return __uint_as_float(v & 0xffff0000u); }
__device__ __forceinline__ float ex2(float x) { float r; asm("ex2.approx.ftz.f32 %0, %1;" : "=f"(r) : "f"(x)); return r; }
__device__ __forceinline__ float rcp(float x) { float r; asm("rcp.approx.ftz.f32 %0, %1;" : "=f"(r) : "f"(x)); return r; }
constexpr float LOG2E = 1.4426950408889634f;
__device__ __forceinline__ float sigmoidf(float x) { return rcp(1.0f + ex2(-LOG2E * x)); }
__device__ __forceinline__ void sts128(uint32_t a, uint32_t x, uint32_t y, uint32_t z, uint32_t w) {
  asm volatile("st.shared.v4.u32 [%0], {%1,%2,%3,%4};" :: "r"(a), "r"(x), "r"(y), "r"(z), "r"(w) : "memory");
}
__device__ __forceinline__ void lds128(uint32_t a, uint32_t (&r)[4]) {
  asm volatile("ld.shared.v4.u32 {%0,%1,%2,%3}, [%4];" : "=r"(r[0]), "=r"(r[1]), "=r"(r[2]), "=r"(r[3]) : "r"(a) : "memory");
}
__device__ __forceinline__ void sts32(uint32_t a, uint32_t v) { asm volatile("st.shared.u32 [%0], %1;" :: "r"(a), "r"(v) : "memory"); }
__device__ __forceinline__ uint32_t lds32(uint32_t a) { uint32_t v; asm volatile("ld.shared.u32 %0, [%1];" : "=r"(v) : "r"(a) : "memory"); return v; }
__device__ __forceinline__ float ldsf(uint32_t a) { return __uint_as_float(lds32(a)); }
__device__ __forceinline__ void stmatrix4(uint32_t a, uint32_t r0, uint32_t r1, uint32_t r2, uint32_t r3) {
  asm volatile("stmatrix.sync.aligned.m8n8.x4.shared.b16 [%0], {%1,%2,%3,%4};" :: "r"(a), "r"(r0), "r"(r1), "r"(r2), "r"(r3) : "memory");
}
__device__ __forceinline__ void ldmatrix4(uint32_t a, uint32_t (&r)[4]) {
  asm volatile("ldmatrix.sync.aligned.m8n8.x4.shared.b16 {%0,%1,%2,%3}, [%4];" : "=r"(r[0]), "=r"(r[1]), "=r"(r[2]), "=r"(r[3]) : "r"(a) : "memory");
}
__device__ __forceinline__ uint4 ldg_nc(const void* p) {
  uint4 v; asm volatile("ld.global.nc.L1::no_allocate.v4.u32 {%0,%1,%2,%3}, [%4];" : "=r"(v.x), "=r"(v.y), "=r"(v.z), "=r"(v.w) : "l"(p)); return v;
}
__device__ __forceinline__ void st_tagged(uint2* p, uint32_t v, uint32_t tag) {
  asm volatile("{\n.reg .b64 x;\nmov.b64 x, {%1, %2};\nst.relaxed.gpu.global.b64 [%0], x;\n}" :: "l"(p), "r"(v), "r"(tag) : "memory");
}
__device__ __forceinline__ uint2 ld_tagged(const uint2* p) {
  uint2 v; asm volatile("{\n.reg .b64 x;\nld.relaxed.gpu.global.b64 x, [%2];\nmov.b64 {%0, %1}, x;\n}" : "=r"(v.x), "=r"(v.y) : "l"(p) : "memory"); return v;
}
__device__ __forceinline__ void probe(const uint2* p, uint32_t tag, int& budget) {
  do { __nanosleep(POLL0); budget -= 16; } while (!__all_sync(0xffffffffu, ld_tagged(p).y == tag) && budget > 0);
}
template <int STRIDE, int N>
__device__ __forceinline__ void gather(const uint2* p, uint32_t tag, float& s0, float& s1, int& budget) {
  uint32_t pause = 0;
  bool again;
#pragma unroll 1
  do {
    __nanosleep(pause);
    pause = POLL0;
    uint32_t bad = 0;
    s0 = s1 = 0.f;
#pragma unroll
    for (int i = 0; i < N; i++) {
      const uint2 w = ld_tagged(p + i * STRIDE);
      bad |= w.y ^ tag;
      if (i < N / 2) s0 += __uint_as_float(w.x); else s1 += __uint_as_float(w.x);
    }
    budget -= 16;
    again = __any_sync(0xffffffffu, bad != 0) && budget > 0;
  } while (again);
}
__device__ __forceinline__ void sts16(uint32_t a, uint32_t v) { asm volatile("st.shared.u16 [%0], %1;" :: "r"(a), "h"((uint16_t)v) : "memory"); }
__device__ __forceinline__ void signal_add(uint32_t* p, uint32_t v) { asm volatile("red.release.gpu.global.add.u32 [%0], %1;" :: "l"(p), "r"(v) : "memory"); }
__device__ __forceinline__ float qmax(float v) { v = fmaxf(v, __shfl_xor_sync(0xffffffffu, v, 1)); return fmaxf(v, __shfl_xor_sync(0xffffffffu, v, 2)); }
__device__ __forceinline__ float qsum(float v) { v += __shfl_xor_sync(0xffffffffu, v, 1); return v + __shfl_xor_sync(0xffffffffu, v, 2); }
__device__ __forceinline__ float fold(float a, float b, bool hi, int m) { return (hi ? b : a) + __shfl_xor_sync(0xffffffffu, hi ? a : b, m); }

__device__ __forceinline__ void yield_slot() { asm volatile("pmevent 0;" ::: "memory"); }
__device__ __forceinline__ float fma_v(float a, float b, float c) { float r; asm volatile("fma.rn.f32 %0, %1, %2, %3;" : "=f"(r) : "f"(a), "f"(b), "f"(c)); return r; }
constexpr float EXP_LIM_F = 36028797018963968.0f;
constexpr uint32_t EXP_TOP = 0x58805880u;
__device__ __forceinline__ void exp_plain(const float (&p)[16], float (&ep)[16], float (&em)[16]) {
#pragma unroll
  for (int i = 0; i < 16; i++) { ep[i] = ex2(p[i]); em[i] = ex2(-p[i]); }
}
__device__ __forceinline__ void exp_shifted(const float (&p)[16], float sgn, float (&e)[16]) {
#pragma unroll
  for (int i = 0; i < 16; i++) e[i] = sgn * p[i];
#pragma unroll
  for (int o = 0; o < 4; o += 2) {
    const float mx = qmax(fmaxf(fmaxf(fmaxf(e[o], e[o + 1]), fmaxf(e[o + 4], e[o + 5])), fmaxf(fmaxf(e[o + 8], e[o + 9]), fmaxf(e[o + 12], e[o + 13]))));
#pragma unroll
    for (int c = 0; c < 4; c++) { e[4 * c + o] = ex2(e[4 * c + o] - mx); e[4 * c + o + 1] = ex2(e[4 * c + o + 1] - mx); }
  }
}
__device__ __forceinline__ void pack_sums(const float (&e)[16], uint32_t (&pk)[2][4], float (&s)[2]) {
#pragma unroll
  for (int i = 0; i < 8; i++) pk[i >> 2][i & 3] = pack2(e[2 * i], e[2 * i + 1]);
#pragma unroll
  for (int o = 0; o < 4; o += 2) s[o >> 1] = ((e[o] + e[o + 1]) + (e[o + 4] + e[o + 5])) + ((e[o + 8] + e[o + 9]) + (e[o + 12] + e[o + 13]));
}
__device__ __forceinline__ uint32_t rcp2(float s) { const float r = rcp(s); return pack2(r, r); }
__device__ __forceinline__ uint32_t mul2(uint32_t a, uint32_t b) { uint32_t r; asm("mul.rn.bf16x2 %0, %1, %2;" : "=r"(r) : "r"(a), "r"(b)); return r; }
__device__ __forceinline__ void store_phi(uint32_t a, const uint32_t (&pk)[2][4], uint32_t r0, uint32_t r1) {
#pragma unroll
  for (int h = 0; h < 2; h++) stmatrix4(a ^ (h * 32), mul2(pk[h][0], r0), mul2(pk[h][1], r1), mul2(pk[h][2], r0), mul2(pk[h][3], r1));
}
__device__ __forceinline__ uint32_t exp_frags(const float (&p)[16], uint32_t (&ef)[4][4], uint32_t top) {
  float ep[16], em[16];
  exp_plain(p, ep, em);
#pragma unroll
  for (int s = 0; s < 2; s++)
#pragma unroll
    for (int r = 0; r < 4; r++) {
      ef[s][r] = pack2(ep[8 * s + 2 * r], ep[8 * s + 2 * r + 1]);
      ef[2 + s][r] = pack2(em[8 * s + 2 * r], em[8 * s + 2 * r + 1]);
    }
#pragma unroll
  for (int s = 0; s < 4; s++) top = __vimax3_u16x2(__vimax3_u16x2(top, ef[s][0], ef[s][1]), ef[s][2], ef[s][3]);
  return top;
}
__device__ __forceinline__ void issue_pq(float (&p)[4][16], const uint32_t (&qf)[4][2][4], uint64_t dw) {
  wg_fence();
#pragma unroll
  for (int h = 0; h < 4; h++) {
    wgmma_m64n32k16_rs<1>(p[h], qf[h][0], dw + h * 128, 0);
    wgmma_m64n32k16_rs<1>(p[h], qf[h][1], dw + h * 128 + 64, 1);
  }
  wg_commit();
}

#define SPLIT_BATCH 2
__device__ __forceinline__ void mainloop128(float (&acc)[2][64], uint64_t da0, uint64_t db0, uint32_t slot, uint32_t ph, int steps, bool lane0, int& budget, int cta, int n0) {
  uint32_t prev = 0;
#pragma unroll 1
  for (int k = 0; k < steps; k++) {
    mbar_wait(bars + B_FX * 8 + slot * 8, ph, budget);
    const uint64_t da = da0 + slot * (STAGE >> 4), db = db0 + slot * (STAGE >> 4);
#pragma unroll
    for (int kk = 0; kk < 4; kk++) {
      if (SPLIT_BATCH == 2 || !(kk & 1)) {
        wg_wait<1>();
        if (kk == 3 - SPLIT_BATCH && k > 0 && lane0) mbar_arrive_n(bars + B_EM * 8 + prev * 8, 2);
        wg_fence();
      }
      wgmma_m64n128k16_ss<0, 1>(acc[0], da + kk * 2, db + kk * 128, kk ? 1 : k);
      wgmma_m64n128k16_ss<0, 1>(acc[1], da + 512 + kk * 2, db + kk * 128, kk ? 1 : k);
      if (SPLIT_BATCH == 2 || (kk & 1)) wg_commit();
    }
    prev = slot;
    if (++slot == NST) { slot = 0; ph ^= 1; }
  }
}
__device__ __forceinline__ void kstep64(float (&acc)[64], uint64_t da, uint64_t db, int accumulate) {
  wg_fence();
#pragma unroll
  for (int kk = 0; kk < 4; kk++) wgmma_m64n128k16_ss<0, 1>(acc, da + kk * 2, db + kk * 128, kk ? 1 : accumulate);
  wg_commit();
}
__device__ __forceinline__ void issue_kv(float (&kv)[20], uint64_t dphi, uint64_t dv, int accumulate) {
  wg_fence();
#pragma unroll
  for (int ks = 0; ks < 4; ks++)
    wgmma_m64n40k16_ss<1, 1>(kv, dphi + ks * 128, dv - (uint64_t)ks * ((64ull << 16) - 64ull), ks ? 1 : accumulate);
  wg_commit();
}
__device__ __forceinline__ void load_x(uint32_t sx, uint32_t (&xf)[8][4]) {
#pragma unroll
  for (int u = 0; u < 8; u++) ldmatrix4((sx ^ ((u & 3) * 32)) + (u >> 2) * 16384, xf[u]);
}
__device__ __forceinline__ uint32_t moe_buf(uint32_t b) { return b == 2 ? SM_V + 8192 : SM_MOE + b * 8192; }
template <bool DOWN>
__device__ __forceinline__ void moe_chunks(float (&a)[4], int n, uint32_t& buf, uint32_t& ph, uint64_t da0, uint64_t db, bool lane0) {
  int budget = BUDGET;
  zero(a);
#pragma unroll 1
  for (int c = 0; c < n; c++) {
    mbar_wait(bars + B_MF * 8 + buf * 8, ph, budget);
    const uint64_t da = da0 + (moe_buf(buf) >> 4);
    wg_fence();
#pragma unroll
    for (int j = 0; j < 4; j++) wgmma_m64n8k16_ss<1, 0>(a, da + j * 128, DOWN ? db - j : db + j * 2, 1);
    wg_commit();
    wg_wait<0>();
    if (lane0) mbar_arrive(bars + B_ME * 8 + buf * 8);
    db += DOWN ? 16 : 8;
    if (++buf >= (DOWN ? 2 : 3)) { buf = 0; ph ^= 1; }
  }
  pin(a);
}
constexpr uint64_t DV_TILE = 4 * ((64ull << 16) - 64ull);

template <bool BY_SM>
__global__ void __launch_bounds__(512, 1)
fused_kernel(const __grid_constant__ CUtensorMap mx, const __grid_constant__ CUtensorMap mw, const __grid_constant__ CUtensorMap mwo,
             const __grid_constant__ CUtensorMap mo, const __grid_constant__ CUtensorMap mout, const __grid_constant__ CUtensorMap mxr,
             const __grid_constant__ CUtensorMap mg, const __grid_constant__ CUtensorMap mu, const __grid_constant__ CUtensorMap md, const Params P) {
  extern __shared__ __align__(1024) uint8_t smem_raw[];
  if (smem_u32(smem_raw) != sb) return;
  const int tid = threadIdx.x, lane = tid & 31;
  if (tid == 256) TS(1);
  const int warp = __shfl_sync(0xffffffffu, tid >> 5, 0), wg = warp >> 2;
  int budget = BUDGET;
  if (warp == 10 && elect_one()) { prefetch_map(&mx); prefetch_map(&mw); }
  int cta;
  {
    uint32_t smid;
    asm volatile("mov.u32 %0, %%smid;" : "=r"(smid));
    if (!BY_SM) cta = blockIdx.x;
    else if (smid < 64) cta = ((smid >> 1) & 7) * 16 + (smid >> 4) * 2 + (smid & 1);
    else if (smid < 120) { const int t = (smid - 64) >> 1, d = (t * 37) >> 8; cta = (1 + t - d * 7) * 16 + 8 + d * 2 + (smid & 1); }
    else cta = smid < 124 ? smid + 8 : smid - 116;
  }
  if (cta >= 128) {
    if (tid == 0) {
      const uint32_t old = atomicAdd(&g_cnt[C_START], 32u);
      wait_count<500>(&g_cnt[C_START], (old & ~255u) + 256u, budget);
    }
    return;
  }
  const int bi = (cta >> 5) * 4 + ((cta >> 2) & 3);
  const int bj = ((cta >> 4) & 1) * 4 + (cta & 3);

  if (wg == 3) {
    asm volatile("setmaxnreg.dec.sync.aligned.u32 64;");
    const int t3 = tid - 384, w3 = warp - 12;
    if (t3 == 0) TSG(0);
    if (t3 < 80) *reinterpret_cast<uint4*>(&g_kvr[cta * 320 + t3 * 4]) = make_uint4(0, 0, 0, 0);
    if (t3 < 17) st_tagged(t3 < 16 ? &g_gate[bi * 128 + bj * 16 + t3] : &g_key[cta], 0, 1);
    bar_sync(0, 512);
#pragma unroll 1
    for (int u = 0; u < 4; u++) {
      const uint4 v = ldg_nc(P.w_phi + bj * 4096 + (u * 128 + t3) * 8);
      sts128(sb + SM_WPHI + u * 2048 + (t3 >> 2) * 64 + (((t3 & 3) ^ ((t3 >> 3) & 3)) << 4),
             pack2(LOG2E * bf_lo(v.x), LOG2E * bf_hi(v.x)), pack2(LOG2E * bf_lo(v.y), LOG2E * bf_hi(v.y)),
             pack2(LOG2E * bf_lo(v.z), LOG2E * bf_hi(v.z)), pack2(LOG2E * bf_lo(v.w), LOG2E * bf_hi(v.w)));
    }
    fence_async_smem();
    warp_arrive(bars + B_WPHI * 8, lane);
    bar_sync(6, 256);
    const uint32_t target = lds32(sb + SM_MISC);
    uint32_t key;
    {
      uint32_t kk[4];
      lds128(sb + SM_MISC + 16, kk);
      if (t3 == 0) st_tagged(&g_key[cta], max(max(kk[0], kk[1]), max(kk[2], kk[3])), target);
      uint2 k, gv;
      __nanosleep(POLLR);
      do {
        __nanosleep(POLL1);
        k = ld_tagged(&g_key[t3]);
        gv = ld_tagged(&g_gate[bi * 128 + t3]);
        budget -= 4;
      } while (!__all_sync(0xffffffffu, k.y == target && gv.y == target) && budget > 0);
      key = __reduce_max_sync(0xffffffffu, k.x);
      if (lane == 0) sts32(sb + SM_MISC + 32 + w3 * 4, key);
      sts32(sb + SM_G + t3 * 4, gv.x);
      bar_sync(5, 128);
      lds128(sb + SM_MISC + 32, kk);
      key = max(max(kk[0], kk[1]), max(kk[2], kk[3]));
    }
    const int idx = (0xFFFF - (key & 0xFFFF)) & (kS - 1);
    if (t3 == 0) { sts32(sb + SM_MISC + 4, idx); TS(8); }
    warp_arrive(bars + B_INFO * 8, lane);
    {
      const uint4 v = ldg_nc(P.x + (size_t)idx * kD + t3 * 8);
      sts128(sb + SM_BAND + t3 * 16, v.x, v.y, v.z, v.w);
    }
    const int t2 = (lane & 3) * 2, row = w3 * 16 + (lane >> 2);
    float a[4];
    uint32_t buf = 0, ph = 0;
    fence_async_smem();
    bar_sync(5, 128);
    {
      const int r = cta >> 4;
#pragma unroll 1
      for (int part = 0; part < 2; part++) {
        const int n = part ? 14 - 2 * r : 2 * r;
        moe_chunks<false>(a, n, buf, ph, P.da, P.dxs + (part ? 0 : (16 - n) * 8), lane == 0);
        uint2* dst = &g_pre[(((cta >> 2) & 2) + 1 - part) * kF + ((r - 1 + part) * 8 + (cta & 7)) * 64 + row];
        if (t2 == 0 && n) { st_tagged(dst, __float_as_uint(a[0]), target); st_tagged(dst + 8, __float_as_uint(a[2]), target); }
      }
    }
    if (t3 == 0) TS(9);
    bar_sync(5, 128);
    sts128(sb + SM_BAND + t3 * 16, 0, 0, 0, 0);
    {
      __nanosleep(POLL0);
      float gs, us;
      gather<kF, 4>(&g_pre[(cta >> 2) * 112 + min(t3, 111)], target, gs, us, budget);
      bar_sync(5, 128);
      if (t3 < 112) sts16(sb + SM_BAND + 112 + (t3 >> 3) * 128 + (t3 & 7) * 2, pack2(gs * sigmoidf(gs) * us, 0.f));
    }
    fence_async_smem();
    bar_sync(5, 128);
    if (t3 == 0) TS(12);
    moe_chunks<true>(a, 7, buf, ph, P.da, P.dband + 7, lane == 0);
    if (t3 == 0) TS(10);
    if (t2 < 4) {
      uint2* dst = &g_yp[(cta >> 2) * kD + (cta & 3) * 256 + t2 * 64 + row];
      st_tagged(dst, __float_as_uint(a[0]), target); st_tagged(dst + 8, __float_as_uint(a[2]), target);
      st_tagged(dst + 64, __float_as_uint(a[1]), target); st_tagged(dst + 72, __float_as_uint(a[3]), target);
    }
    if (lane == 0) mbar_arrive(bars + B_MD * 8);
    if ((idx >> 7) == bi) {
      mbar_wait(bars + (B_PUB + 3) * 8, 0, budget);
      if (w3 == 0) probe(&g_yp[lane * kD + bj * 128], target, budget);
      bar_sync(5, 128);
      float y = 0.f;
#pragma unroll 1
      for (int hf = 0; hf < 2; hf++) {
        float y0, y1;
        gather<kD, 16>(&g_yp[hf * 16 * kD + bj * 128 + t3], target, y0, y1, budget);
        y += y0 + y1;
      }
      const uint32_t ob = key >> 16;
      const float upd = y * sigmoidf(__uint_as_float(((ob & 0x8000u) ? (ob ^ 0x8000u) : (~ob & 0xFFFFu)) << 16));
      const uint32_t a = sb + SM_PHI + (t3 >> 6) * 16384 + (idx & 127) * 128 + ((((t3 >> 3) & 7) ^ (idx & 7)) << 4) + (t3 & 7) * 2;
      mbar_wait(bars + B_XT * 8, 0, budget);
      uint16_t xb;
      asm volatile("ld.shared.u16 %0, [%1];" : "=h"(xb) : "r"(a) : "memory");
      sts16(a, pack2(bf_lo(xb) + upd, 0.f));
      warp_arrive(bars + B_XP * 8, lane);
      if (t3 == 0) TS(11);
    }
  } else if (wg < 2) {
    if ((warp & 3) < EARLY_N && lane < (wg ? 8 : 16)) {
      const int n = warp & 3;
      const __nv_bfloat16* p = wg ? P.w + (size_t)(n * 64 + bi + (lane >> 1) * 16) * (3 * kD) + 1024 + (lane & 1) * 1024 + bj * 128
                                  : P.x + (size_t)(bi * 128 + bj * 16 + lane) * kD + n * 64;
      if (n) __nanosleep(n * EARLY_GAP);
      asm volatile("prefetch.global.L2 [%0];" :: "l"(p));
    }
    __syncwarp();
    asm volatile("setmaxnreg.inc.sync.aligned.u32 208;");
    const int tw = tid & 127, w = warp & 3, g = lane >> 2, t = lane & 3;
    const bool lane0 = lane == 0;
    if (wg == 0) sts128(sb + SM_Z + (tw & 63) * 16, 0x3f803f80u, 0x3f803f80u, 0x3f803f80u, 0x3f803f80u);
    bar_sync(0, 512);
    if (wg == 1) {
      float sr[4], sg[4];
      zero(sr); zero(sg);
#pragma unroll 1
      for (int c = 0; c < 4; c++) {
        mbar_wait(bars + (B_RX + c) * 8, 0, budget);
        uint32_t rs[4], gs[4], xs[4][4];
        lds128(sb + SM_V + c * 512 + lane * 16, rs);
        lds128(sb + SM_V + 2048 + c * 512 + lane * 16, gs);
#pragma unroll
        for (int r = 0; r < 4; r++) lds128(sb + SM_PHI + c * 8192 + (w * 4 + r) * 512 + lane * 16, xs[r]);
#pragma unroll
        for (int e = 0; e < 4; e++) {
          const float r0 = bf_lo(rs[e]), r1 = bf_hi(rs[e]), g0 = bf_lo(gs[e]), g1 = bf_hi(gs[e]);
#pragma unroll
          for (int r = 0; r < 4; r++) {
            const float x0 = bf_lo(xs[r][e]), x1 = bf_hi(xs[r][e]);
            sr[r] = fma_v(x0, r0, sr[r]); sg[r] = fma_v(x0, g0, sg[r]);
            sr[r] = fma_v(x1, r1, sr[r]); sg[r] = fma_v(x1, g1, sg[r]);
            if (r != 1) yield_slot();
          }
        }
      }
      fence_async_smem();
      __syncwarp();
      if (lane < 3) mbar_arrive(bars + (B_ME + lane) * 8);
      const bool b4 = lane & 16, b3 = lane & 8, b2 = lane & 4;
      const float v = qsum(fold(fold(fold(sr[0], sg[0], b4, 16), fold(sr[2], sg[2], b4, 16), b3, 8),
                                fold(fold(sr[1], sg[1], b4, 16), fold(sr[3], sg[3], b4, 16), b3, 8), b2, 4));
      const int row = bi * 128 + bj * 16 + w * 4 + (g & 3);
      const uint32_t rb = pack2(v + 0.f, 0.f);
      const uint32_t ob = (rb & 0x8000u) ? (~rb & 0xFFFFu) : (rb | 0x8000u);
      const uint32_t best = __reduce_max_sync(0xffffffffu, b4 ? 0u : (ob << 16) | (0xFFFFu - row));
      mbar_wait(bars + B_EPOCH * 8, 0, budget);
      const uint32_t tag = lds32(sb + SM_MISC);
      if (lane0) sts32(sb + SM_MISC + 16 + w * 4, best);
      if (b4 && t == 0) st_tagged(&g_gate[row], __float_as_uint(sigmoidf(v)), tag);
      if (tw == 0) TS(14);
      bar_arrive(6, 256);
      bar_sync(1, 256);
    }

    {
      float acc[2][64];
      if (tw == 0) TS(16 + wg * 16);
      mainloop128(acc, P.da, P.db, wg, wg, 16, lane0, budget, cta, wg * 16);
      bar_sync(1 + wg, 256);
      wg_wait<0>();
      pin(acc[0]); pin(acc[1]);
      if (lane0) mbar_arrive_n(bars + (B_EM + wg) * 8, 2);
      if (tw == 0) TS(17 + wg * 16);
      float p[4][16];
      uint32_t vp[8][4];
      const uint32_t av = sb + SM_V + (w * 16 + g) * 64 + ((t ^ (g >> 1)) << 4);
      {
        uint32_t kf[4][2][4];
#pragma unroll
        for (int u = 0; u < 4; u++)
#pragma unroll
          for (int s = 0; s < 2; s++)
#pragma unroll
            for (int r = 0; r < 4; r++) kf[u][s][r] = pack2(acc[u & 1][16 * (u >> 1) + 8 * s + 2 * r], acc[u & 1][16 * (u >> 1) + 8 * s + 2 * r + 1]);
        mbar_wait(bars + B_WPHI * 8, 0, budget);
        const uint64_t dw = P.dw + wg * 256;
        wg_fence();
#pragma unroll
        for (int u = 0; u < 4; u++) {
          wgmma_m64n32k16_rs<1>(p[u], kf[u][0], dw + (u >> 1) * 128, 0);
          wgmma_m64n32k16_rs<1>(p[u], kf[u][1], dw + (u >> 1) * 128 + 64, 1);
        }
        wg_commit();
#pragma unroll
        for (int u = 0; u < 8; u++) {
          const float* a = &acc[(u >> 1) & 1][32 + 16 * (u >> 2) + 2 * (u & 1)];
          vp[u][0] = pack2(a[0], a[1]); vp[u][1] = pack2(a[4], a[5]); vp[u][2] = pack2(a[8], a[9]); vp[u][3] = pack2(a[12], a[13]);
          if (u < 4) sts128(av + (u >> 1) * 4096 + (u & 1) * 512, vp[u][0], vp[u][1], vp[u][2], vp[u][3]);
        }
        pinr(vp);
        wg_wait<0>();
#pragma unroll
        for (int u = 0; u < 4; u++) pin(p[u]);
      }
      if (tw == 0) TS(18 + wg * 16);
      float kv[2][20];
      {
        const uint32_t sphi = sb + SM_PHI + (w * 16 + (lane & 15)) * 128 + (((lane >> 4) ^ (lane & 7)) << 4);
        float top = 0.f;
        uint32_t pk[4][2][4];
        float ps[2], sa[4], sc[4];
        uint32_t redo = 0;
#pragma unroll
        for (int i = 0; i < 11; i++) {
          if (i >= 3) {
            const int j = i - 3;
            const float s0 = sc[0] + sc[2], s1 = sc[1] + sc[3];
            top = fmaxf(top, fmaxf(s0, s1));
            store_phi((sphi ^ ((j & 1) * 64)) + (j & 2) * 4096, pk[j & 3], rcp2(s0), rcp2(s1));
          }
          if (i >= 2 && i <= 9) {
            sc[0] = sa[0] + sa[2]; sc[1] = sa[1] + sa[3];
            sc[2] = __shfl_xor_sync(0xffffffffu, sc[0], 2); sc[3] = __shfl_xor_sync(0xffffffffu, sc[1], 2);
          }
          if (i >= 1 && i <= 8) {
            sa[0] = ps[0]; sa[1] = ps[1];
            sa[2] = __shfl_xor_sync(0xffffffffu, sa[0], 1); sa[3] = __shfl_xor_sync(0xffffffffu, sa[1], 1);
          }
          if (i < 8) {
            pin(p[i >> 1]);
            float e[16];
#pragma unroll
            for (int c = 0; c < 16; c++) e[c] = ex2((i & 1) ? -p[i >> 1][c] : p[i >> 1][c]);
            pack_sums(e, pk[i & 3], ps);
            pinr(pk[i & 3]); pin(ps);
          }
          if (i < 10) yield_slot();
          if (i >= 2 && i <= 9) pin(sc);
          if (i >= 1 && i <= 8) pin(sa);
          if (i == 2 && wg) mbar_wait(bars + B_RD * 8, 0, budget);
          if (i >= 4 && !(i & 1)) {
            const int u = (i - 4) >> 1;
            fence_async_smem();
            wg_wait<0>();
            if (u < 3) bar_sync(7 + wg, 128);
            else asm volatile("{\n.reg .pred p, q;\nsetp.ne.b32 p, %2, 0;\nbar.red.or.pred q, %1, 128, p;\nselp.u32 %0, 1, 0, q;\n}"
                              : "=r"(redo) : "r"(7 + wg), "r"((uint32_t)!(top < EXP_LIM_F)) : "memory");
            issue_kv(kv[u >> 1], P.dphi + (u & 1) * 512, P.dv - (u & 1) * DV_TILE, u & 1);
            if (u == 1 || u == 2) {
#pragma unroll
              for (int r = 0; r < 2; r++) sts128(av + ((u + 1) & 1) * 4096 + r * 512, vp[2 * u + 2 + r][0], vp[2 * u + 2 + r][1], vp[2 * u + 2 + r][2], vp[2 * u + 2 + r][3]);
            }
            if (u < 3) yield_slot();
          }
        }
        if (tw == 0) TS(19 + wg * 16);
        wg_wait<0>();
        pin(kv[0]); pin(kv[1]);
        if (__builtin_expect(__any_sync(0xffffffffu, redo), 0)) {
#pragma unroll 1
          for (int u = 0; u < 4; u++) {
            bar_sync(7 + wg, 128);
#pragma unroll 1
            for (int sg = 0; sg < 2; sg++) {
              float e[16];
              exp_shifted(p[0], sg ? -1.f : 1.f, e);
              pack_sums(e, pk[0], ps);
              store_phi(sphi ^ (sg * 64), pk[0], rcp2(qsum(ps[0])), rcp2(qsum(ps[1])));
            }
            sts128(av, vp[0][0], vp[0][1], vp[0][2], vp[0][3]);
            sts128(av + 512, vp[1][0], vp[1][1], vp[1][2], vp[1][3]);
            fence_async_smem();
            bar_sync(7 + wg, 128);
            issue_kv(kv[1], P.dphi, P.dv, u & 1);
            wg_wait<0>();
            pin(kv[1]);
#pragma unroll
            for (int c = 0; c < 16; c++) { p[0][c] = p[1][c]; p[1][c] = p[2][c]; p[2][c] = p[3][c]; }
#pragma unroll
            for (int c = 0; c < 24; c++) vp[c >> 2][c & 3] = vp[(c >> 2) + 2][c & 3];
            if (u == 1) {
#pragma unroll
              for (int c = 0; c < 20; c++) kv[0][c] = kv[1][c];
            }
          }
        }
      }
      if (tw == 0) TS(20 + wg * 16);
      bar_sync(7 + wg, 128);
      {
        const int srow = w * 16 + (lane & 15);
        const uint32_t a0 = sb + SM_PHI + srow * 64 + (((lane >> 4) ^ ((srow >> 1) & 3)) << 4);
#pragma unroll
        for (int q = 0; q < 4; q++) {
          const float* a = &kv[q >> 1][8 * (q & 1)];
          stmatrix4((a0 ^ ((q & 1) * 32)) + (q >> 1) * 4096, pack2(a[0], a[1]), pack2(a[2], a[3]), pack2(a[4], a[5]), pack2(a[6], a[7]));
        }
        const uint32_t z = pack2(t == 0 ? kv[0][16] : t == 1 ? kv[1][16] : t == 2 ? kv[0][18] : kv[1][18], 0.0625f);
        sts128(sb + SM_PHI + 8192 + ((w & 1) * 16 + (t >> 1) * 8 + g) * 64 + ((((w & 2) + (t & 1)) ^ (g >> 1)) << 4), z, z, z, z);
      }
      fence_async_smem();
      warp_arrive(bars + (B_RED + wg) * 8, lane);
      if (tw == 0) TS(51 + wg * 4);
    }

    uint32_t stash = sb + 3 * STAGE + 8192 + w * 2048 + lane * 16;
    const int rowl = wg * 64 + w * 16 + g;
    mbar_wait(bars + B_INFO * 8, 0, budget);
    const float gA = ldsf(sb + SM_G + rowl * 4), gB = ldsf(sb + SM_G + rowl * 4 + 32);
    __nv_bfloat16* og = P.o + (size_t)(bi * 128 + rowl) * kD + bj * 128 + t * 8;
    uint32_t own = sb + 3 * STAGE + rowl * 128 + ((t ^ g) << 4);
    uint32_t sx = sb + SM_PHI + (wg * 64 + w * 16 + (lane & 15)) * 128 + (((lane >> 4) ^ (lane & 7)) << 4);
    uint32_t routed = (lds32(sb + SM_MISC + 4) >> 4) == (uint32_t)(bi * 8 + warp);
    asm volatile("" : "+l"(og), "+r"(own), "+r"(stash), "+r"(sx), "+r"(routed));
    {
      float p[4][16];
      uint32_t ef[2][4][4];
      uint32_t top = EXP_TOP;
      if (wg == 0) {
        float acc[2][64];
        bar_sync(2, 256);
        if (tw == 0) TS(22);
        mainloop128(acc, P.da, P.db, 32 % NST, (32 / NST) & 1, 12, lane0, budget, cta, 32);
#pragma unroll 1
        for (int n = 0; n < 4; n++) {
          const uint32_t slot = n ? n - 1 : 4;
          if (tw == 0) KS(128 + 44 + n);
          mbar_wait(bars + B_FX * 8 + slot * 8, n != 0, budget);
          if (tw == 0) KS(44 + n);
          kstep64(acc[0], P.da + slot * (STAGE >> 4), P.db + slot * (STAGE >> 4), 1);
          wg_wait<1>();
          if (n == 0 && lane0) mbar_arrive_n(bars + (B_EM + 43 % NST) * 8, 2);
        }
        kstep64(acc[1], P.da + 512 + (44 % NST) * (STAGE >> 4), P.db + (44 % NST) * (STAGE >> 4), 1);
        wg_wait<1>();
        pin(acc[0]);
        if (tw == 0) TS(15);
        {
          uint32_t qf[4][2][4];
#pragma unroll
          for (int u = 0; u < 8; u++)
#pragma unroll
            for (int r = 0; r < 4; r++) qf[u >> 1][u & 1][r] = pack2(acc[0][8 * u + 2 * r], acc[0][8 * u + 2 * r + 1]);
          issue_pq(p, qf, P.dw);
          kstep64(acc[1], P.da + 512 + (45 % NST) * (STAGE >> 4), P.db + (45 % NST) * (STAGE >> 4), 1);
          wg_wait<1>();
        }
#pragma unroll
        for (int h = 0; h < 4; h++) pin(p[h]);
        if (tw == 0) TS(24);
#pragma unroll
        for (int h = 0; h < 2; h++) {
          if (lane0) mbar_arrive_n(bars + (B_EM + (44 + h) % NST) * 8, 2);
          kstep64(acc[1], P.da + 512 + ((46 + h) % NST) * (STAGE >> 4), P.db + ((46 + h) % NST) * (STAGE >> 4), 1);
          yield_slot();
          pin(p[h]);
          top = exp_frags(p[h], ef[h], top);
          pinr(ef[h]);
          yield_slot();
          if (h == 0) wg_wait<1>(); else wg_wait<0>();
        }
        pin(acc[1]);
        if (lane0) { mbar_arrive_n(bars + (B_EM + 46 % NST) * 8, 2); mbar_arrive_n(bars + (B_EM + 47 % NST) * 8, 2); }
        if (tw == 0) TS(23);
        RG(0);
#pragma unroll
        for (int u = 0; u < 8; u++) {
          const float* a = &acc[1][8 * u];
          sts128(stash + (u >> 2) * STAGE + (u & 3) * 512, pack2(a[0], a[1]), pack2(a[2], a[3]), pack2(a[4], a[5]), pack2(a[6], a[7]));
        }
        warp_arrive(bars + B_QS * 8, lane);
        RG(1);
      } else {
        uint32_t qf[4][2][4];
        mbar_wait(bars + B_QS * 8, 0, budget);
        RG(1);
#pragma unroll
        for (int u = 0; u < 8; u++) lds128(stash + (u >> 2) * STAGE + (u & 3) * 512, qf[u >> 1][u & 1]);
        __syncwarp();
        issue_pq(p, qf, P.dw);
        wg_wait<0>();
#pragma unroll
        for (int h = 0; h < 4; h++) pin(p[h]);
        if (tw == 0) TS(40);
      }

#pragma unroll 1
      for (int pr = 0; pr < 2; pr++) {
        RG(2 + pr * 8);
        if (YIELD_EXP && pr > wg) bar_sync(11, 256);
        if (pr | wg) top = exp_frags(p[1], ef[1], exp_frags(p[0], ef[0], EXP_TOP));
        if (YIELD_EXP && pr < wg) { pinr(ef[0]); pinr(ef[1]); bar_arrive(11, 256); }
        if (__builtin_expect(__any_sync(0xffffffffu, top != EXP_TOP), 0)) {
#pragma unroll 1
          for (int u = 0; u < 4; u++) {
            float e[16];
            exp_shifted(p[0], (u & 1) ? -1.f : 1.f, e);
#pragma unroll
            for (int r = 0; r < 4; r++) {
#pragma unroll
              for (int s = 0; s < 6; s++) ef[s >> 2][s & 3][r] = ef[(s + 2) >> 2][(s + 2) & 3][r];
              ef[1][2][r] = pack2(e[2 * r], e[2 * r + 1]);
              ef[1][3][r] = pack2(e[8 + 2 * r], e[8 + 2 * r + 1]);
            }
            if (u & 1) {
#pragma unroll
              for (int e2 = 0; e2 < 16; e2++) p[0][e2] = p[1][e2];
            }
          }
        }
        float np[2][20], nm[2][20];
        RG(3 + pr * 8);
        mbar_wait(bars + (B_KV + pr) * 8, 0, budget);
        RG(4 + pr * 8);
        wg_fence();
#pragma unroll
        for (int hh = 0; hh < 2; hh++) {
          const uint64_t dk = P.dv - (uint64_t)pr * ((384ull << 16) - 512ull) - hh * ((255ull << 16) - 256ull);
          wgmma_m64n40k16_rs<1>(np[hh], ef[hh][0], dk, 0);
          wgmma_m64n40k16_rs<1>(np[hh], ef[hh][1], dk + 64, 1);
          wgmma_m64n40k16_rs<1>(nm[hh], ef[hh][2], dk + 128 - (126ull << 16), 0);
          wgmma_m64n40k16_rs<1>(nm[hh], ef[hh][3], dk + 192 - (126ull << 16), 1);
          wg_commit();
        }
#pragma unroll
        for (int e = 0; e < 16; e++) { p[0][e] = p[2][e]; p[1][e] = p[3][e]; }
        pin(p[0]); pin(p[1]);
#pragma unroll
        for (int hh = 0; hh < 2; hh++) {
          if (hh == 0) wg_wait<1>(); else wg_wait<0>();
          pin(np[hh]); pin(nm[hh]);
          RG(5 + hh + pr * 8);
          uint32_t o[2][4];
#pragma unroll
          for (int r = 0; r < 2; r++) {
            const float dp = np[hh][16 + 2 * r], sp = np[hh][17 + 2 * r], dm = nm[hh][16 + 2 * r], sm = nm[hh][17 + 2 * r];
            const float inv = (r == 0 ? gA : gB) * rcp(fmaf(dp, sm, fmaf(1e-6f, sm, dm) * sp));
            const float cp = sm * inv, cm = sp * inv;
#pragma unroll
            for (int c = 0; c < 4; c++)
              o[r][c] = pack2(fmaf(np[hh][4 * c + 2 * r], cp, nm[hh][4 * c + 2 * r] * cm), fmaf(np[hh][4 * c + 2 * r + 1], cp, nm[hh][4 * c + 2 * r + 1] * cm));
            sts128((own ^ (hh * 64)) + r * 1024, o[r][0], o[r][1], o[r][2], o[r][3]);
          }
          if (hh == 1 && pr == 1) fence_async_smem();
#pragma unroll
          for (int r = 0; r < 2; r++) asm volatile("st.global.v4.u32 [%0], {%1,%2,%3,%4};" :: "l"(og + r * 8 * kD + hh * 32), "r"(o[r][0]), "r"(o[r][1]), "r"(o[r][2]), "r"(o[r][3]) : "memory");
        }
        RG(7 + pr * 8);
        warp_arrive(bars + (B_PUB + wg * 2 + pr) * 8, lane);
        RG(8 + pr * 8);
        if (tw == 0) TS(25 + pr + wg * 16);
        og += 64; own += STAGE;
      }
    }
    if (HOLD_OWN && !wg) mbar_wait(bars + (B_PUB + 1 + HOLD_OWN) * 8, 0, budget);
    bar_sync(7 + wg, 128);

    RG(18);
    float oacc[64];
    uint32_t xf[8][4];
    {
      const uint64_t dam = P.da + wg * 512;
      mbar_wait(bars + (B_FX + 3) * 8, 1, budget);
      kstep64(oacc, dam + 3 * (STAGE >> 4), P.db + 3 * (STAGE >> 4), 0);
      if (tw == 0) TS(27 + wg * 16);
      mbar_wait(bars + (B_FX + 4) * 8, 1, budget);
      kstep64(oacc, dam + 4 * (STAGE >> 4), P.db + 4 * (STAGE >> 4), 1);
      wg_wait<1>();
      if (lane0) mbar_arrive(bars + (B_EM + 3) * 8);
      wg_wait<0>();
      if (lane0) mbar_arrive(bars + (B_EM + 4) * 8);
      if (XS == 1) { mbar_wait(bars + B_XT * 8, 0, budget); load_x(sx, xf); }
      uint32_t slot = 0, ph = 0, prev = 0;
#pragma unroll 1
      for (int s = 2; s < 16; s++) {
        if (tid == 0) KS(128 + 48 + s);
        mbar_wait(bars + B_FX * 8 + slot * 8, ph, budget);
        mbar_wait(bars + (B_FY + wg * NST) * 8 + slot * 8, ph, budget);
        if (tid == 0) KS(48 + s);
        if (tid == 128) KS(192 + 48 + s);
        if (END_SKEW && s == 16 - END_SKEW && wg) bar_sync(12, 256);
        const uint64_t da = dam + slot * (STAGE >> 4), db = P.db + slot * (STAGE >> 4);
#pragma unroll
        for (int hf = 0; hf < 2; hf++) {
          wg_wait<1>();
          if (hf && s > 2 && lane0) mbar_arrive(bars + B_EM * 8 + prev * 8);
          wg_fence();
          wgmma_m64n128k16_ss<0, 1>(oacc, da + hf * 4, db + hf * 256, 1);
          wgmma_m64n128k16_ss<0, 1>(oacc, da + hf * 4 + 2, db + hf * 256 + 128, 1);
          wg_commit();
        }
        if (XS > 1 && s == XS) { mbar_wait(bars + B_XT * 8, 0, budget); load_x(sx, xf); }
        prev = slot;
        if (++slot == NST) { slot = 0; ph ^= 1; }
      }
      if (END_SKEW && !wg) bar_arrive(12, 256);
    }
    if (__any_sync(0xffffffffu, routed)) { mbar_wait(bars + B_XP * 8, 0, budget); load_x(sx, xf); }
    const float hA = 1.0f - gA, hB = 1.0f - gB;
    float xv[64];
#pragma unroll
    for (int i = 0; i < 32; i++) { xv[2 * i] = bf_lo(xf[i >> 2][i & 3]); xv[2 * i + 1] = bf_hi(xf[i >> 2][i & 3]); }
    pin(xv);
    yield_slot();
    wg_wait<0>();
    pin(oacc);
    if (tw == 0) TS(29 + wg * 16);
#pragma unroll
    for (int hf = 0; hf < 2; hf++) {
#pragma unroll
      for (int u = hf * 4; u < hf * 4 + 4; u++) {
        const float* a = &oacc[8 * u];
        const float* b = &xv[8 * u];
        stmatrix4((sx ^ ((u & 3) * 32)) + hf * 16384,
                  pack2(fmaf(hA, b[0], a[0]), fmaf(hA, b[1], a[1])), pack2(fmaf(hB, b[2], a[2]), fmaf(hB, b[3], a[3])),
                  pack2(fmaf(hA, b[4], a[4]), fmaf(hA, b[5], a[5])), pack2(fmaf(hB, b[6], a[6]), fmaf(hB, b[7], a[7])));
        if (FIN_YIELD) yield_slot();
      }
      fence_async_smem();
      __syncwarp();
      if (elect_one()) tma_store(&mout, sb + SM_PHI + hf * 16384 + warp * 2048, bj * 128 + hf * 64, bi * 128 + warp * 16);
    }
    if (elect_one()) {
      asm volatile("cp.async.bulk.commit_group;" ::: "memory");
      asm volatile("cp.async.bulk.wait_group.read 0;" ::: "memory");
    }
  } else {
    asm volatile("setmaxnreg.dec.sync.aligned.u32 32;");
    if (warp == 8) {
      if (elect_one()) {
        TS(7);
#pragma unroll
        for (int s = 0; s < NST; s++) mbar_init(bars + (B_FX + s) * 8, 1);
        asm volatile("fence.mbarrier_init.release.cluster;" ::: "memory");
        fence_async_smem();
      }
      __syncwarp();
      bar_arrive(0, 512);
      if (elect_one()) {
#pragma unroll 1
        for (int n = 0; n < NST; n++) {
          const uint32_t st = sb + n * STAGE, fb = bars + (B_FX + n) * 8;
          KS(64 + n);
          mbar_expect_tx(fb, STAGE);
          tma_load(st, &mx, fb, n * 64, bi * 128);
          tma_load(st + 16384, &mw, fb, 1024 + bj * 128, n * 64);
          tma_load(st + 24576, &mw, fb, 2048 + bj * 128, n * 64);
        }
      }
      __syncwarp();
      bar_sync(10, 64);
    } else {
      if (warp == 9) {
        if (elect_one()) {
#pragma unroll
          for (int s = B_FY; s < B_NUM; s++) mbar_init(bars + s * 8, s < B_WPHI ? 1 : s < B_EM ? 4 : 8);
          asm volatile("fence.mbarrier_init.release.cluster;" ::: "memory");
          fence_async_smem();
        }
        __syncwarp();
        bar_arrive(10, 64);
      }
      bar_sync(0, 512);
    }
    if (!elect_one()) return;
    if (warp == 8) {
      uint32_t slot = 0, ph = 0;
#pragma unroll 1
      for (int n = NST; n < 48; n++) {
        const int t = n >> 4, k = n & 15;
        const int c0 = t == 2 ? bj * 128 : 1024 + bj * 128 + t * 64, c1 = t == 2 ? c0 + 64 : c0 + 1024;
        const uint32_t st = sb + slot * STAGE, fb = bars + (B_FX + slot) * 8;
        if (n <= NST + 3 * RSTEP && (n - NST) % RSTEP == 0) {
          const int c = (n - NST) / RSTEP;
          mbar_expect_tx(bars + (B_RX + c) * 8, c == 0 ? 8192 + 4096 : 8192);
          tma_load(sb + SM_PHI + c * 8192, &mxr, bars + (B_RX + c) * 8, c * 256, bi * 128 + bj * 16);
          if (c == 0) { bulk_load(sb + SM_V, P.w_r, 2048, bars + B_RX * 8); bulk_load(sb + SM_V + 2048, P.gate_w, 2048, bars + B_RX * 8); }
        }
        mbar_wait(bars + (B_EM + slot) * 8, ph, budget);
        KS(64 + n);
        mbar_expect_tx(fb, STAGE);
        tma_load(st, &mx, fb, k * 64, bi * 128);
        tma_load(st + 16384, &mw, fb, c0, k * 64);
        tma_load(st + 24576, &mw, fb, c1, k * 64);
        {
          const int m = n + WLEAD, tm = m >> 4;
          if ((m & 3) == (bi & 3)) {
            const int d0 = tm >= 2 ? bj * 128 : 1024 + bj * 128 + tm * 64, d1 = tm >= 2 ? d0 + 64 : d0 + 1024;
            tma_prefetch(tm == 3 ? &mwo : &mw, d0, (m & 15) * 64); tma_prefetch(tm == 3 ? &mwo : &mw, d1, (m & 15) * 64);
          }
        }
        if (++slot == NST) { slot = 0; ph ^= 1; }
      }
#pragma unroll 1
      for (int m = WLEAD + ((bi - WLEAD) & 3); m < 16; m += 4) { tma_prefetch(&mwo, bj * 128, m * 64); tma_prefetch(&mwo, bj * 128 + 64, m * 64); }
#pragma unroll 1
      for (int s = 0; s < 16; s++) {
        const int p = s < 2 ? s : (s >= 9), q = s < 9 ? s - 2 : s - 9;
        const int k0 = (s < 2 ? bj : q + (q >= bj)) * 128 + p * 64;
        const uint32_t st = sb + slot * STAGE, fb = bars + (B_FX + slot) * 8;
        mbar_wait(bars + (B_EM + slot) * 8, ph, budget);
        KS(64 + 48 + s);
        mbar_expect_tx(fb, 16384);
        tma_load(st + 16384, &mwo, fb, bj * 128, k0);
        tma_load(st + 24576, &mwo, fb, bj * 128 + 64, k0);
        if (++slot == NST) { slot = 0; ph ^= 1; }
      }
      if (REPF) prefetch_map(&mout);
    } else if (warp == 9) {
      prefetch_map(&mo); prefetch_map(&mout);
      uint32_t old;
      asm volatile("atom.add.release.gpu.global.u32 %0, [%1], 1;" : "=r"(old) : "l"(&g_cnt[C_START]) : "memory");
      sts32(sb + SM_MISC, (old & ~255u) + 256u);
      mbar_arrive(bars + B_EPOCH * 8);
      const CUtensorMap* m = (cta & 8) ? &mu : &mg;
      const int l0 = (cta >> 4) * 14, a0 = (cta & 7) * 64, d1 = (cta >> 2) * 112 - 14 * 16, d2 = (cta & 3) * 4;
      uint32_t buf = 0, ph = 0, tnext;
      asm volatile("mov.u32 %0, %%clock;" : "=r"(tnext));
#pragma unroll 1
      for (int c = 0; c < 21; c++) {
        const uint32_t dst = sb + moe_buf(buf), fb = bars + (B_MF + buf) * 8;
        mbar_wait(bars + (B_ME + buf) * 8, ph, budget);
        mbar_expect_tx(fb, 8192);
        if (c < 14) tma_load(dst, m, fb, a0 + ((l0 + c) >> 4) * 512, ((l0 + c) & 15) * 64); else tma_load3(dst, &md, fb, d1 + c * 16, d2);
        if (MLEAD && c >= 2 && c + MLEAD < 17) {
          const int f = c + MLEAD;
          if (f < 14) tma_prefetch(m, a0 + ((l0 + f) >> 4) * 512, ((l0 + f) & 15) * 64); else tma_prefetch3(&md, d1 + f * 16, d2);
        }
        if (MPACE) { uint32_t now; do { asm volatile("mov.u32 %0, %%clock;" : "=r"(now)); if ((int32_t)(now - tnext) >= 0) break; __nanosleep(20); } while (true); tnext = now + MPACE; }
        if (c == 16) {
#pragma unroll 1
          for (int f = 17; f < 21; f++) { __nanosleep(MGAP); tma_prefetch3(&md, d1 + f * 16, d2); }
        }
        if (c < 2) __nanosleep(MGAP);
        if (c == 17) mbar_arrive(bars + B_M2 * 8);
        if (++buf >= (c >= 14 ? 2 : 3)) { buf = 0; ph ^= 1; }
      }
      mbar_wait(bars + B_MD * 8, 0, budget);
      mbar_wait(bars + (B_RD + 1) * 8, 0, budget);
      if (!XLATE) {
        mbar_wait(bars + XT_GATE * 8, 0, budget);
        mbar_expect_tx(bars + B_XT * 8, 32768);
        tma_load(sb + SM_PHI, &mx, bars + B_XT * 8, bj * 128, bi * 128);
        tma_load(sb + SM_PHI + 16384, &mx, bars + B_XT * 8, bj * 128 + 64, bi * 128);
      }
      mbar_wait(bars + (B_PUB + 1) * 8, 0, budget);
      mbar_wait(bars + (B_PUB + 3) * 8, 0, budget);
      signal_add(&g_cnt[(C_O + bi * 4 + 1) * 32], 32u);
      TS(57);
      wait_count<POLLF>(&g_cnt[(C_O + bi * 4 + 1) * 32], (old & ~255u) + 256u, budget);
      mbar_arrive(bars + B_P1 * 8);
      TS(3);
      if (XLATE) {
        mbar_expect_tx(bars + B_XT * 8, 32768);
        __nanosleep(XGAP);
        tma_load(sb + SM_PHI, &mx, bars + B_XT * 8, bj * 128, bi * 128);
        __nanosleep(XGAP);
        tma_load(sb + SM_PHI + 16384, &mx, bars + B_XT * 8, bj * 128 + 64, bi * 128);
      }
    } else {
      const int u = warp - 10, hp = bj * 2 + u;
      mbar_wait(bars + B_EPOCH * 8, 0, budget);
      const uint32_t target = lds32(sb + SM_MISC);
      mbar_wait(bars + B_INFO * 8, 0, budget);
      wait_count<200>(&g_cnt[C_START], target, budget);
      fence_async_global();
#pragma unroll 1
      for (int e = 0; e < 2; e++) {
        uint32_t* cnt = &g_cnt[(e ? C_O + bi * 4 + u * 2 : C_KV + hp) * 32];
        mbar_wait(bars + (e ? B_PUB + u * 2 : B_RED + u) * 8, 0, budget);
        if (e == 0) {
#pragma unroll 1
          for (int c = 0; c < RED_CH; c++) {
            bulk_reduce(&g_kvr[hp * 2560 + c * (2560 / RED_CH)], sb + SM_PHI + c * (10240 / RED_CH), 10240 / RED_CH);
            if (c + 1 < RED_CH) __nanosleep(u ? RED_GAP1 : RED_GAP0);
          }
          asm volatile("cp.async.bulk.commit_group;" ::: "memory");
          asm volatile("cp.async.bulk.wait_group 0;" ::: "memory");
          TS(21 + u * 16);
          mbar_arrive(bars + (B_RD + u) * 8);
        }
        signal_add(cnt, e ? 32u : 16u);
        TS(e ? 56 + u * 2 : 60 + u);
        if (REPF && e) prefetch_map(&mo);
        if (e == 0) {
          mbar_wait(bars + (u ? B_M2 : B_RED + 1) * 8, 0, budget);
        }
        wait_count<POLLF>(cnt, target, budget);
        fence_async_global();
        if (e == 0) {
          mbar_expect_tx(bars + (B_KV + u) * 8, 10240);
          bulk_load(sb + SM_V + u * 8192, &g_kvr[hp * 2560], 8192, bars + (B_KV + u) * 8);
          bulk_load(sb + SM_Z + u * 2048, &g_kvr[hp * 2560 + 2048], 2048, bars + (B_KV + u) * 8);
          TS(38 + u);
        }
      }
      TS(2 + u * 2);
      if (u == 0) mbar_wait(bars + B_QS * 8, 0, budget);
      uint32_t slot = 0, ph = 1;
#pragma unroll 1
      for (int s = 2; s < 16; s++) {
        const int p = s >= 9, q = s < 9 ? s - 2 : s - 9;
        if (s == 9) { mbar_wait(bars + B_P1 * 8, 0, budget); fence_async_global(); }
        const uint32_t fb = bars + (B_FY + u * NST + slot) * 8;
        mbar_wait(bars + (B_EM + slot) * 8, ph, budget);
        mbar_expect_tx(fb, 8192);
        tma_load(sb + slot * STAGE + u * 8192, &mo, fb, (q + (q >= bj)) * 128 + p * 64, bi * 128 + u * 64);
        if (++slot == NST) { slot = 0; ph ^= 1; }
      }
    }
  }
}

typedef CUresult (*EncodeFn)(CUtensorMap*, CUtensorMapDataType, cuuint32_t, void*, const cuuint64_t*, const cuuint64_t*, const cuuint32_t*,
                             const cuuint32_t*, CUtensorMapInterleave, CUtensorMapSwizzle, CUtensorMapL2promotion, CUtensorMapFloatOOBfill);

void make_map(EncodeFn enc, CUtensorMap* m, const void* ptr, uint64_t cols, uint64_t rows, uint32_t bc, uint32_t br, CUtensorMapSwizzle swz) {
  const cuuint64_t dims[2] = {cols, rows}, strides[1] = {cols * 2};
  const cuuint32_t box[2] = {bc, br}, es[2] = {1, 1};
  enc(m, CU_TENSOR_MAP_DATA_TYPE_BFLOAT16, 2, const_cast<void*>(ptr), dims, strides, box, es, CU_TENSOR_MAP_INTERLEAVE_NONE, swz,
      CU_TENSOR_MAP_L2_PROMOTION_L2_128B, CU_TENSOR_MAP_FLOAT_OOB_FILL_NONE);
}

}

extern "C" void kernel_launch(void* const* d_in, const int* in_sizes, int n_in, void* d_out, int out_size) {
  (void)in_sizes; (void)n_in; (void)out_size;
  void* fn = nullptr;
  cudaDriverEntryPointQueryResult qr;
  cudaGetDriverEntryPoint("cuTensorMapEncodeTiled", &fn, cudaEnableDefault, &qr);
  EncodeFn enc = (EncodeFn)fn;
  void* o_ptr = nullptr;
  cudaGetSymbolAddress(&o_ptr, g_o);
  CUtensorMap mx, mw, mwo, mo, mout, mxr, mg, mu, md;
  make_map(enc, &mx, d_in[0], kD, kS, 64, 128, CU_TENSOR_MAP_SWIZZLE_128B);
  make_map(enc, &mxr, d_in[0], kD, kS, 256, 16, CU_TENSOR_MAP_SWIZZLE_NONE);
  make_map(enc, &mw, d_in[1], 3 * kD, kD, 64, 64, CU_TENSOR_MAP_SWIZZLE_128B);
  make_map(enc, &mwo, d_in[3], kD, kD, 64, 64, CU_TENSOR_MAP_SWIZZLE_128B);
  make_map(enc, &mo, o_ptr, kD, kS, 64, 64, CU_TENSOR_MAP_SWIZZLE_128B);
  make_map(enc, &mout, d_out, kD, kS, 64, 16, CU_TENSOR_MAP_SWIZZLE_128B);
  make_map(enc, &mg, d_in[6], kF, kD, 64, 64, CU_TENSOR_MAP_SWIZZLE_128B);
  make_map(enc, &mu, d_in[7], kF, kD, 64, 64, CU_TENSOR_MAP_SWIZZLE_128B);
  {
    const cuuint64_t dims[3] = {64, kF, 16}, strides[2] = {kD * 2, 128};
    const cuuint32_t box[3] = {64, 16, 4}, es[3] = {1, 1, 1};
    enc(&md, CU_TENSOR_MAP_DATA_TYPE_BFLOAT16, 3, d_in[8], dims, strides, box, es, CU_TENSOR_MAP_INTERLEAVE_NONE, CU_TENSOR_MAP_SWIZZLE_128B,
        CU_TENSOR_MAP_L2_PROMOTION_L2_128B, CU_TENSOR_MAP_FLOAT_OOB_FILL_NONE);
  }
  Params P;
  P.x = (const __nv_bfloat16*)d_in[0];
  P.w = (const __nv_bfloat16*)d_in[1];
  P.o = (__nv_bfloat16*)o_ptr;
  P.w_phi = (const __nv_bfloat16*)d_in[2];
  P.w_r = (const __nv_bfloat16*)d_in[5];
  P.gate_w = (const __nv_bfloat16*)d_in[9];
  P.da = make_desc(sb, 16, 1024, 1);
  P.db = make_desc(sb + 16384, 8192, 1024, 1);
  P.dw = make_desc(sb + SM_WPHI, 16, 512, 2);
  P.dphi = make_desc(sb + SM_PHI, 16, 1024, 1);
  P.dv = make_desc(sb + SM_V, SM_Z - SM_V, 512, 2);
  P.dband = make_desc(sb + SM_BAND, 128, 128, 0);
  P.dxs = make_desc(sb + SM_BAND, 16, 128, 0);
  int dev = 0, sms = 0;
  cudaGetDevice(&dev);
  cudaDeviceGetAttribute(&sms, cudaDevAttrMultiProcessorCount, dev);
  auto kern = sms == 132 ? fused_kernel<true> : fused_kernel<false>;
  cudaFuncSetAttribute(kern, cudaFuncAttributeMaxDynamicSharedMemorySize, SM_ALLOC);
  kern<<<132, 512, SM_ALLOC, cudaStreamPerThread>>>(mx, mw, mwo, mo, mout, mxr, mg, mu, md, P);
}
```

```cpp
#include <cuda_runtime.h>
#include <cuda_bf16.h>
#include <cuda.h>
#include <stdint.h>

namespace {

template<int TA, int TB> __device__ __forceinline__ void wgmma_m64n128k16_ss(float (&d)[64], uint64_t da, uint64_t db, int scale_d) {
  asm volatile("{\n.reg .pred p;\nsetp.ne.b32 p, %66, 0;\n"
    "wgmma.mma_async.sync.aligned.m64n128k16.f32.bf16.bf16 "
    "{%0, %1, %2, %3, %4, %5, %6, %7, %8, %9, %10, %11, %12, %13, %14, %15, "
    "%16, %17, %18, %19, %20, %21, %22, %23, %24, %25, %26, %27, %28, %29, %30, %31, "
    "%32, %33, %34, %35, %36, %37, %38, %39, %40, %41, %42, %43, %44, %45, %46, %47, "
    "%48, %49, %50, %51, %52, %53, %54, %55, %56, %57, %58, %59, %60, %61, %62, %63}, "
    "%64, %65, p, 1, 1, %67, %68;\n}\n"
    : "+f"(d[0]), "+f"(d[1]), "+f"(d[2]), "+f"(d[3]), "+f"(d[4]), "+f"(d[5]), "+f"(d[6]), "+f"(d[7]),
      "+f"(d[8]), "+f"(d[9]), "+f"(d[10]), "+f"(d[11]), "+f"(d[12]), "+f"(d[13]), "+f"(d[14]), "+f"(d[15]),
      "+f"(d[16]), "+f"(d[17]), "+f"(d[18]), "+f"(d[19]), "+f"(d[20]), "+f"(d[21]), "+f"(d[22]), "+f"(d[23]),
      "+f"(d[24]), "+f"(d[25]), "+f"(d[26]), "+f"(d[27]), "+f"(d[28]), "+f"(d[29]), "+f"(d[30]), "+f"(d[31]),
      "+f"(d[32]), "+f"(d[33]), "+f"(d[34]), "+f"(d[35]), "+f"(d[36]), "+f"(d[37]), "+f"(d[38]), "+f"(d[39]),
      "+f"(d[40]), "+f"(d[41]), "+f"(d[42]), "+f"(d[43]), "+f"(d[44]), "+f"(d[45]), "+f"(d[46]), "+f"(d[47]),
      "+f"(d[48]), "+f"(d[49]), "+f"(d[50]), "+f"(d[51]), "+f"(d[52]), "+f"(d[53]), "+f"(d[54]), "+f"(d[55]),
      "+f"(d[56]), "+f"(d[57]), "+f"(d[58]), "+f"(d[59]), "+f"(d[60]), "+f"(d[61]), "+f"(d[62]), "+f"(d[63])
    : "l"(da), "l"(db), "r"(scale_d), "n"(TA), "n"(TB));
}

template<int TB> __device__ __forceinline__ void wgmma_m64n32k16_rs(float (&d)[16], const uint32_t (&a)[4], uint64_t db, int scale_d) {
  asm volatile("{\n.reg .pred p;\nsetp.ne.b32 p, %21, 0;\n"
    "wgmma.mma_async.sync.aligned.m64n32k16.f32.bf16.bf16 "
    "{%0, %1, %2, %3, %4, %5, %6, %7, %8, %9, %10, %11, %12, %13, %14, %15}, "
    "{%16, %17, %18, %19}, %20, p, 1, 1, %22;\n}\n"
    : "+f"(d[0]), "+f"(d[1]), "+f"(d[2]), "+f"(d[3]), "+f"(d[4]), "+f"(d[5]), "+f"(d[6]), "+f"(d[7]),
      "+f"(d[8]), "+f"(d[9]), "+f"(d[10]), "+f"(d[11]), "+f"(d[12]), "+f"(d[13]), "+f"(d[14]), "+f"(d[15])
    : "r"(a[0]), "r"(a[1]), "r"(a[2]), "r"(a[3]), "l"(db), "r"(scale_d), "n"(TB));
}

template<int TA, int TB> __device__ __forceinline__ void wgmma_m64n40k16_ss(float (&d)[20], uint64_t da, uint64_t db, int scale_d) {
  asm volatile("{\n.reg .pred p;\nsetp.ne.b32 p, %22, 0;\n"
    "wgmma.mma_async.sync.aligned.m64n40k16.f32.bf16.bf16 "
    "{%0, %1, %2, %3, %4, %5, %6, %7, %8, %9, %10, %11, %12, %13, %14, %15, "
    "%16, %17, %18, %19}, "
    "%20, %21, p, 1, 1, %23, %24;\n}\n"
    : "+f"(d[0]), "+f"(d[1]), "+f"(d[2]), "+f"(d[3]), "+f"(d[4]), "+f"(d[5]), "+f"(d[6]), "+f"(d[7]),
      "+f"(d[8]), "+f"(d[9]), "+f"(d[10]), "+f"(d[11]), "+f"(d[12]), "+f"(d[13]), "+f"(d[14]), "+f"(d[15]),
      "+f"(d[16]), "+f"(d[17]), "+f"(d[18]), "+f"(d[19])
    : "l"(da), "l"(db), "r"(scale_d), "n"(TA), "n"(TB));
}

template<int TB> __device__ __forceinline__ void wgmma_m64n40k16_rs(float (&d)[20], const uint32_t (&a)[4], uint64_t db, int scale_d) {
  asm volatile("{\n.reg .pred p;\nsetp.ne.b32 p, %25, 0;\n"
    "wgmma.mma_async.sync.aligned.m64n40k16.f32.bf16.bf16 "
    "{%0, %1, %2, %3, %4, %5, %6, %7, %8, %9, %10, %11, %12, %13, %14, %15, "
    "%16, %17, %18, %19}, "
    "{%20, %21, %22, %23}, %24, p, 1, 1, %26;\n}\n"
    : "+f"(d[0]), "+f"(d[1]), "+f"(d[2]), "+f"(d[3]), "+f"(d[4]), "+f"(d[5]), "+f"(d[6]), "+f"(d[7]),
      "+f"(d[8]), "+f"(d[9]), "+f"(d[10]), "+f"(d[11]), "+f"(d[12]), "+f"(d[13]), "+f"(d[14]), "+f"(d[15]),
      "+f"(d[16]), "+f"(d[17]), "+f"(d[18]), "+f"(d[19])
    : "r"(a[0]), "r"(a[1]), "r"(a[2]), "r"(a[3]), "l"(db), "r"(scale_d), "n"(TB));
}

template<int TA, int TB> __device__ __forceinline__ void wgmma_m64n8k16_ss(float (&d)[4], uint64_t da, uint64_t db, int scale_d) {
  asm volatile("{\n.reg .pred p;\nsetp.ne.b32 p, %6, 0;\n"
    "wgmma.mma_async.sync.aligned.m64n8k16.f32.bf16.bf16 "
    "{%0, %1, %2, %3}, "
    "%4, %5, p, 1, 1, %7, %8;\n}\n"
    : "+f"(d[0]), "+f"(d[1]), "+f"(d[2]), "+f"(d[3])
    : "l"(da), "l"(db), "r"(scale_d), "n"(TA), "n"(TB));
}

constexpr int kS = 2048, kD = 1024, kF = 3584;
constexpr int NST = 5, STAGE = 32768;
constexpr uint32_t sb = 1024;
constexpr int SM_V    = NST * STAGE;
constexpr int SM_Z    = SM_V + 16384;
constexpr int SM_PHI  = SM_Z + 4096;
constexpr int SM_MOE  = SM_PHI + 16384;
constexpr int SM_WPHI = SM_MOE + 16384;
constexpr int SM_BAND = SM_WPHI + 8192;
constexpr int SM_G    = SM_BAND + 2176;
constexpr int SM_BAR  = SM_G + 512;
constexpr int SM_MISC = SM_BAR + 448;
constexpr int SM_TOTAL = SM_MISC + 64;
static_assert(SM_TOTAL <= 232448, "smem");
constexpr uint32_t bars = sb + SM_BAR;
constexpr int B_FX = 0  , B_FY = 5  , B_XT = 15, B_EPOCH = 16, B_RX = 17  , B_MF = 21  , B_RD = 24  , B_KV = 26  , B_M2 = 28, B_P1 = 29;
constexpr int B_WPHI = 30, B_INFO = 31, B_QS = 32, B_XP = 33, B_RED = 34  , B_PUB = 36  , B_ME = 40  , B_MD = 43;
constexpr int B_EM = 44  , B_NUM = 49;
constexpr int C_START = 0, C_O = 1, C_KV = C_O + 64;

__device__ uint2 g_gate[kS];
__device__ uint2 g_key[128];
__device__ uint2 g_pre[4 * kF];
__device__ uint2 g_yp[32 * kD];
__device__ __align__(128) uint32_t g_kvr[16 * 2560];
__device__ __align__(128) uint32_t g_cnt[(C_KV + 32) * 32];
__device__ __align__(1024) __nv_bfloat16 g_o[kS * kD];
#define KS(id)
#define RG(id)
#define TS(id)
#define TSG(id)
constexpr int SM_ALLOC = SM_TOTAL;

#define POLL0 500
#define POLL1 150
#define RSTEP 1
#define POLLR 400
#define EARLY_N 2
#define EARLY_GAP 200
#define POLLF 50
#define RED_CH 10
#define RED_GAP0 250
#define RED_GAP1 0
#define YIELD_EXP 1
#define END_SKEW 4
#define XT_GATE B_QS
#define FIN_YIELD 0
#define MLEAD 0
#define MPACE 0
#define REPF 1
#define RED_ROT 0
#define RED_CH1 10
#define WLEAD 11
#define MGAP 300

struct Params {
  const __nv_bfloat16 *x, *w, *w_phi, *w_r, *gate_w;
  __nv_bfloat16* o;
  uint64_t da, db, dw, dphi, dv, dband, dxs;
};

__device__ __forceinline__ uint32_t smem_u32(const void* p) { return (uint32_t)__cvta_generic_to_shared(p); }
__device__ __forceinline__ void mbar_init(uint32_t bar, uint32_t cnt) { asm volatile("mbarrier.init.shared::cta.b64 [%0], %1;" :: "r"(bar), "r"(cnt) : "memory"); }
__device__ __forceinline__ void mbar_expect_tx(uint32_t bar, uint32_t bytes) { asm volatile("mbarrier.arrive.expect_tx.shared::cta.b64 _, [%0], %1;" :: "r"(bar), "r"(bytes) : "memory"); }
__device__ __forceinline__ void mbar_arrive(uint32_t bar) { asm volatile("mbarrier.arrive.shared::cta.b64 _, [%0];" :: "r"(bar) : "memory"); }
__device__ __forceinline__ void mbar_arrive_n(uint32_t bar, uint32_t n) { asm volatile("mbarrier.arrive.shared::cta.b64 _, [%0], %1;" :: "r"(bar), "r"(n) : "memory"); }
constexpr int BUDGET = 1 << 20;
__device__ __forceinline__ void mbar_wait(uint32_t bar, uint32_t parity, int& budget) {
  asm volatile("{\n.reg .pred p;\n"
               "WAIT_L:\nmbarrier.try_wait.parity.shared::cta.b64 p, [%1], %2;\n@p bra WAIT_D;\n"
               "add.s32 %0, %0, -1;\nsetp.gt.s32 p, %0, 0;\n@p bra WAIT_L;\nWAIT_D:\n}"
               : "+r"(budget) : "r"(bar), "r"(parity) : "memory");
}
template <int SLEEP>
__device__ __forceinline__ void wait_count(const uint32_t* p, uint32_t target, int& budget) {
  asm volatile("{\n.reg .pred p;\n.reg .s32 v;\n"
               "WAIT_L:\nld.acquire.gpu.global.s32 v, [%1];\nsub.s32 v, v, %2;\nsetp.ge.s32 p, v, 0;\n@p bra WAIT_D;\n"
               "nanosleep.u32 %3;\nadd.s32 %0, %0, -4;\nsetp.gt.s32 p, %0, 0;\n@p bra WAIT_L;\nWAIT_D:\n}"
               : "+r"(budget) : "l"(p), "r"(target), "n"(SLEEP) : "memory");
}
__device__ __forceinline__ void tma_load(uint32_t dst, const CUtensorMap* m, uint32_t bar, int c0, int c1) {
  asm volatile("cp.async.bulk.tensor.2d.shared::cluster.global.mbarrier::complete_tx::bytes [%0], [%1, {%3, %4}], [%2];"
    :: "r"(dst), "l"(m), "r"(bar), "r"(c0), "r"(c1) : "memory");
}
__device__ __forceinline__ void tma_load3(uint32_t dst, const CUtensorMap* m, uint32_t bar, int c1, int c2) {
  asm volatile("cp.async.bulk.tensor.3d.shared::cluster.global.mbarrier::complete_tx::bytes [%0], [%1, {%5, %3, %4}], [%2];"
    :: "r"(dst), "l"(m), "r"(bar), "r"(c1), "r"(c2), "r"(0) : "memory");
}
__device__ __forceinline__ void tma_prefetch3(const CUtensorMap* m, int c1, int c2) {
  asm volatile("cp.async.bulk.prefetch.tensor.3d.L2.global [%0, {%3, %1, %2}];" :: "l"(m), "r"(c1), "r"(c2), "r"(0) : "memory");
}
__device__ __forceinline__ void tma_prefetch(const CUtensorMap* m, int c0, int c1) {
  asm volatile("cp.async.bulk.prefetch.tensor.2d.L2.global [%0, {%1, %2}];" :: "l"(m), "r"(c0), "r"(c1) : "memory");
}
__device__ __forceinline__ void tma_store(const CUtensorMap* m, uint32_t src, int c0, int c1) {
  asm volatile("cp.async.bulk.tensor.2d.global.shared::cta.bulk_group [%0, {%2, %3}], [%1];" :: "l"(m), "r"(src), "r"(c0), "r"(c1) : "memory");
}
__device__ __forceinline__ void bulk_load(uint32_t dst, const void* src, uint32_t bytes, uint32_t bar) {
  asm volatile("cp.async.bulk.shared::cluster.global.mbarrier::complete_tx::bytes [%0], [%1], %2, [%3];" :: "r"(dst), "l"(src), "r"(bytes), "r"(bar) : "memory");
}
__device__ __forceinline__ void bulk_reduce(void* dst, uint32_t src, uint32_t bytes) {
  asm volatile("cp.reduce.async.bulk.global.shared::cta.bulk_group.add.noftz.bf16 [%0], [%1], %2;" :: "l"(dst), "r"(src), "r"(bytes) : "memory");
}
__device__ __forceinline__ void prefetch_map(const CUtensorMap* m) { asm volatile("prefetch.tensormap [%0];" :: "l"(m) : "memory"); }
__device__ __forceinline__ bool elect_one() {
  uint32_t p;
  asm volatile("{\n.reg .pred P;\nelect.sync _|P, 0xffffffff;\nselp.u32 %0, 1, 0, P;\n}" : "=r"(p));
  return p;
}
__device__ __forceinline__ void wg_fence() { asm volatile("wgmma.fence.sync.aligned;" ::: "memory"); }
__device__ __forceinline__ void wg_commit() { asm volatile("wgmma.commit_group.sync.aligned;" ::: "memory"); }
template <int N> __device__ __forceinline__ void wg_wait() { asm volatile("wgmma.wait_group.sync.aligned %0;" :: "n"(N) : "memory"); }
template <int N> __device__ __forceinline__ void zero(float (&r)[N]) {
#pragma unroll
  for (int i = 0; i < N; i++) r[i] = 0.f;
}
template <int N> __device__ __forceinline__ void pin(float (&r)[N]) {
#pragma unroll
  for (int i = 0; i < N; i++) asm volatile("" : "+f"(r[i]) :: "memory");
}
template <int N> __device__ __forceinline__ void pinr(uint32_t (&r)[N][4]) {
#pragma unroll
  for (int i = 0; i < N; i++) asm volatile("" : "+r"(r[i][0]), "+r"(r[i][1]), "+r"(r[i][2]), "+r"(r[i][3]) :: "memory");
}
__device__ __forceinline__ void fence_async_smem() { asm volatile("fence.proxy.async.shared::cta;" ::: "memory"); }
__device__ __forceinline__ void fence_async_global() { asm volatile("fence.proxy.async.global;" ::: "memory"); }
__device__ __forceinline__ void bar_sync(int id, int n) { asm volatile("bar.sync %0, %1;" :: "r"(id), "r"(n) : "memory"); }
__device__ __forceinline__ void bar_arrive(int id, int n) { asm volatile("bar.arrive %0, %1;" :: "r"(id), "r"(n) : "memory"); }
__device__ __forceinline__ void warp_arrive(uint32_t bar, int lane) { __syncwarp(); if (lane == 0) mbar_arrive(bar); }
__host__ __device__ constexpr uint64_t make_desc(uint32_t addr, uint32_t lbo, uint32_t sbo, uint32_t swz) {
  return (uint64_t)((addr & 0x3FFFF) >> 4) | ((uint64_t)((lbo & 0x3FFFF) >> 4) << 16) | ((uint64_t)(sbo >> 4) << 32) | ((uint64_t)swz << 62);
}
__device__ __forceinline__ uint32_t pack2(float lo, float hi) {
  uint32_t r; asm("cvt.rn.bf16x2.f32 %0, %1, %2;" : "=r"(r) : "f"(hi), "f"(lo)); return r;
}
__device__ __forceinline__ float bf_lo(uint32_t v) { return __uint_as_float(v << 16); }
__device__ __forceinline__ float bf_hi(uint32_t v) { return __uint_as_float(v & 0xffff0000u); }
__device__ __forceinline__ float ex2(float x) { float r; asm("ex2.approx.ftz.f32 %0, %1;" : "=f"(r) : "f"(x)); return r; }
__device__ __forceinline__ float rcp(float x) { float r; asm("rcp.approx.ftz.f32 %0, %1;" : "=f"(r) : "f"(x)); return r; }
constexpr float LOG2E = 1.4426950408889634f;
__device__ __forceinline__ float sigmoidf(float x) { return rcp(1.0f + ex2(-LOG2E * x)); }
__device__ __forceinline__ void sts128(uint32_t a, uint32_t x, uint32_t y, uint32_t z, uint32_t w) {
  asm volatile("st.shared.v4.u32 [%0], {%1,%2,%3,%4};" :: "r"(a), "r"(x), "r"(y), "r"(z), "r"(w) : "memory");
}
__device__ __forceinline__ void lds128(uint32_t a, uint32_t (&r)[4]) {
  asm volatile("ld.shared.v4.u32 {%0,%1,%2,%3}, [%4];" : "=r"(r[0]), "=r"(r[1]), "=r"(r[2]), "=r"(r[3]) : "r"(a) : "memory");
}
__device__ __forceinline__ void sts32(uint32_t a, uint32_t v) { asm volatile("st.shared.u32 [%0], %1;" :: "r"(a), "r"(v) : "memory"); }
__device__ __forceinline__ uint32_t lds32(uint32_t a) { uint32_t v; asm volatile("ld.shared.u32 %0, [%1];" : "=r"(v) : "r"(a) : "memory"); return v; }
__device__ __forceinline__ float ldsf(uint32_t a) { return __uint_as_float(lds32(a)); }
__device__ __forceinline__ void stmatrix4(uint32_t a, uint32_t r0, uint32_t r1, uint32_t r2, uint32_t r3) {
  asm volatile("stmatrix.sync.aligned.m8n8.x4.shared.b16 [%0], {%1,%2,%3,%4};" :: "r"(a), "r"(r0), "r"(r1), "r"(r2), "r"(r3) : "memory");
}
__device__ __forceinline__ void ldmatrix4(uint32_t a, uint32_t (&r)[4]) {
  asm volatile("ldmatrix.sync.aligned.m8n8.x4.shared.b16 {%0,%1,%2,%3}, [%4];" : "=r"(r[0]), "=r"(r[1]), "=r"(r[2]), "=r"(r[3]) : "r"(a) : "memory");
}
__device__ __forceinline__ uint4 ldg_nc(const void* p) {
  uint4 v; asm volatile("ld.global.nc.L1::no_allocate.v4.u32 {%0,%1,%2,%3}, [%4];" : "=r"(v.x), "=r"(v.y), "=r"(v.z), "=r"(v.w) : "l"(p)); return v;
}
__device__ __forceinline__ void st_tagged(uint2* p, uint32_t v, uint32_t tag) {
  asm volatile("{\n.reg .b64 x;\nmov.b64 x, {%1, %2};\nst.relaxed.gpu.global.b64 [%0], x;\n}" :: "l"(p), "r"(v), "r"(tag) : "memory");
}
__device__ __forceinline__ uint2 ld_tagged(const uint2* p) {
  uint2 v; asm volatile("{\n.reg .b64 x;\nld.relaxed.gpu.global.b64 x, [%2];\nmov.b64 {%0, %1}, x;\n}" : "=r"(v.x), "=r"(v.y) : "l"(p) : "memory"); return v;
}
__device__ __forceinline__ void probe(const uint2* p, uint32_t tag, int& budget) {
  do { __nanosleep(POLL0); budget -= 16; } while (!__all_sync(0xffffffffu, ld_tagged(p).y == tag) && budget > 0);
}
template <int STRIDE, int N>
__device__ __forceinline__ void gather(const uint2* p, uint32_t tag, float& s0, float& s1, int& budget) {
  uint32_t pause = 0;
  bool again;
#pragma unroll 1
  do {
    __nanosleep(pause);
    pause = POLL0;
    uint32_t bad = 0;
    s0 = s1 = 0.f;
#pragma unroll
    for (int i = 0; i < N; i++) {
      const uint2 w = ld_tagged(p + i * STRIDE);
      bad |= w.y ^ tag;
      if (i < N / 2) s0 += __uint_as_float(w.x); else s1 += __uint_as_float(w.x);
    }
    budget -= 16;
    again = __any_sync(0xffffffffu, bad != 0) && budget > 0;
  } while (again);
}
__device__ __forceinline__ void sts16(uint32_t a, uint32_t v) { asm volatile("st.shared.u16 [%0], %1;" :: "r"(a), "h"((uint16_t)v) : "memory"); }
__device__ __forceinline__ void signal_add(uint32_t* p, uint32_t v) { asm volatile("red.release.gpu.global.add.u32 [%0], %1;" :: "l"(p), "r"(v) : "memory"); }
__device__ __forceinline__ float qmax(float v) { v = fmaxf(v, __shfl_xor_sync(0xffffffffu, v, 1)); return fmaxf(v, __shfl_xor_sync(0xffffffffu, v, 2)); }
__device__ __forceinline__ float qsum(float v) { v += __shfl_xor_sync(0xffffffffu, v, 1); return v + __shfl_xor_sync(0xffffffffu, v, 2); }
__device__ __forceinline__ float fold(float a, float b, bool hi, int m) { return (hi ? b : a) + __shfl_xor_sync(0xffffffffu, hi ? a : b, m); }

__device__ __forceinline__ void yield_slot() { asm volatile("pmevent 0;" ::: "memory"); }
__device__ __forceinline__ float fma_v(float a, float b, float c) { float r; asm volatile("fma.rn.f32 %0, %1, %2, %3;" : "=f"(r) : "f"(a), "f"(b), "f"(c)); return r; }
constexpr float EXP_LIM_F = 36028797018963968.0f;
constexpr uint32_t EXP_TOP = 0x58805880u;
__device__ __forceinline__ void exp_plain(const float (&p)[16], float (&ep)[16], float (&em)[16]) {
#pragma unroll
  for (int i = 0; i < 16; i++) { ep[i] = ex2(p[i]); em[i] = ex2(-p[i]); }
}
__device__ __forceinline__ void exp_shifted(const float (&p)[16], float sgn, float (&e)[16]) {
#pragma unroll
  for (int i = 0; i < 16; i++) e[i] = sgn * p[i];
#pragma unroll
  for (int o = 0; o < 4; o += 2) {
    const float mx = qmax(fmaxf(fmaxf(fmaxf(e[o], e[o + 1]), fmaxf(e[o + 4], e[o + 5])), fmaxf(fmaxf(e[o + 8], e[o + 9]), fmaxf(e[o + 12], e[o + 13]))));
#pragma unroll
    for (int c = 0; c < 4; c++) { e[4 * c + o] = ex2(e[4 * c + o] - mx); e[4 * c + o + 1] = ex2(e[4 * c + o + 1] - mx); }
  }
}
__device__ __forceinline__ void pack_sums(const float (&e)[16], uint32_t (&pk)[2][4], float (&s)[2]) {
#pragma unroll
  for (int i = 0; i < 8; i++) pk[i >> 2][i & 3] = pack2(e[2 * i], e[2 * i + 1]);
#pragma unroll
  for (int o = 0; o < 4; o += 2) s[o >> 1] = ((e[o] + e[o + 1]) + (e[o + 4] + e[o + 5])) + ((e[o + 8] + e[o + 9]) + (e[o + 12] + e[o + 13]));
}
__device__ __forceinline__ uint32_t rcp2(float s) { const float r = rcp(s); return pack2(r, r); }
__device__ __forceinline__ uint32_t mul2(uint32_t a, uint32_t b) { uint32_t r; asm("mul.rn.bf16x2 %0, %1, %2;" : "=r"(r) : "r"(a), "r"(b)); return r; }
__device__ __forceinline__ void store_phi(uint32_t a, const uint32_t (&pk)[2][4], uint32_t r0, uint32_t r1) {
#pragma unroll
  for (int h = 0; h < 2; h++) stmatrix4(a ^ (h * 32), mul2(pk[h][0], r0), mul2(pk[h][1], r1), mul2(pk[h][2], r0), mul2(pk[h][3], r1));
}
__device__ __forceinline__ uint32_t exp_frags(const float (&p)[16], uint32_t (&ef)[4][4], uint32_t top) {
  float ep[16], em[16];
  exp_plain(p, ep, em);
#pragma unroll
  for (int s = 0; s < 2; s++)
#pragma unroll
    for (int r = 0; r < 4; r++) {
      ef[s][r] = pack2(ep[8 * s + 2 * r], ep[8 * s + 2 * r + 1]);
      ef[2 + s][r] = pack2(em[8 * s + 2 * r], em[8 * s + 2 * r + 1]);
    }
#pragma unroll
  for (int s = 0; s < 4; s++) top = __vimax3_u16x2(__vimax3_u16x2(top, ef[s][0], ef[s][1]), ef[s][2], ef[s][3]);
  return top;
}
__device__ __forceinline__ void issue_pq(float (&p)[4][16], const uint32_t (&qf)[4][2][4], uint64_t dw) {
  wg_fence();
#pragma unroll
  for (int h = 0; h < 4; h++) {
    wgmma_m64n32k16_rs<1>(p[h], qf[h][0], dw + h * 128, 0);
    wgmma_m64n32k16_rs<1>(p[h], qf[h][1], dw + h * 128 + 64, 1);
  }
  wg_commit();
}

#define SPLIT_BATCH 2
__device__ __forceinline__ void mainloop128(float (&acc)[2][64], uint64_t da0, uint64_t db0, uint32_t slot, uint32_t ph, int steps, bool lane0, int& budget, int cta, int n0) {
  uint32_t prev = 0;
#pragma unroll 1
  for (int k = 0; k < steps; k++) {
    mbar_wait(bars + B_FX * 8 + slot * 8, ph, budget);
    const uint64_t da = da0 + slot * (STAGE >> 4), db = db0 + slot * (STAGE >> 4);
#pragma unroll
    for (int kk = 0; kk < 4; kk++) {
      if (SPLIT_BATCH == 2 || !(kk & 1)) {
        wg_wait<1>();
        if (kk == 3 - SPLIT_BATCH && k > 0 && lane0) mbar_arrive_n(bars + B_EM * 8 + prev * 8, 2);
        wg_fence();
      }
      wgmma_m64n128k16_ss<0, 1>(acc[0], da + kk * 2, db + kk * 128, kk ? 1 : k);
      wgmma_m64n128k16_ss<0, 1>(acc[1], da + 512 + kk * 2, db + kk * 128, kk ? 1 : k);
      if (SPLIT_BATCH == 2 || (kk & 1)) wg_commit();
    }
    prev = slot;
    if (++slot == NST) { slot = 0; ph ^= 1; }
  }
}
__device__ __forceinline__ void kstep64(float (&acc)[64], uint64_t da, uint64_t db, int accumulate) {
  wg_fence();
#pragma unroll
  for (int kk = 0; kk < 4; kk++) wgmma_m64n128k16_ss<0, 1>(acc, da + kk * 2, db + kk * 128, kk ? 1 : accumulate);
  wg_commit();
}
__device__ __forceinline__ void issue_kv(float (&kv)[20], uint64_t dphi, uint64_t dv, int accumulate) {
  wg_fence();
#pragma unroll
  for (int ks = 0; ks < 4; ks++)
    wgmma_m64n40k16_ss<1, 1>(kv, dphi + ks * 128, dv - (uint64_t)ks * ((64ull << 16) - 64ull), ks ? 1 : accumulate);
  wg_commit();
}
__device__ __forceinline__ void load_x(uint32_t sx, uint32_t (&xf)[8][4]) {
#pragma unroll
  for (int u = 0; u < 8; u++) ldmatrix4((sx ^ ((u & 3) * 32)) + (u >> 2) * 16384, xf[u]);
}
__device__ __forceinline__ uint32_t moe_buf(uint32_t b) { return b == 2 ? SM_V + 8192 : SM_MOE + b * 8192; }
template <bool DOWN>
__device__ __forceinline__ void moe_chunks(float (&a)[4], int n, uint32_t& buf, uint32_t& ph, uint64_t da0, uint64_t db, bool lane0) {
  int budget = BUDGET;
  zero(a);
#pragma unroll 1
  for (int c = 0; c < n; c++) {
    mbar_wait(bars + B_MF * 8 + buf * 8, ph, budget);
    const uint64_t da = da0 + (moe_buf(buf) >> 4);
    wg_fence();
#pragma unroll
    for (int j = 0; j < 4; j++) wgmma_m64n8k16_ss<1, 0>(a, da + j * 128, DOWN ? db - j : db + j * 2, 1);
    wg_commit();
    wg_wait<0>();
    if (lane0) mbar_arrive(bars + B_ME * 8 + buf * 8);
    db += DOWN ? 16 : 8;
    if (++buf >= (DOWN ? 2 : 3)) { buf = 0; ph ^= 1; }
  }
  pin(a);
}
constexpr uint64_t DV_TILE = 4 * ((64ull << 16) - 64ull);

template <bool BY_SM>
__global__ void __launch_bounds__(512, 1)
fused_kernel(const __grid_constant__ CUtensorMap mx, const __grid_constant__ CUtensorMap mw, const __grid_constant__ CUtensorMap mwo,
             const __grid_constant__ CUtensorMap mo, const __grid_constant__ CUtensorMap mout, const __grid_constant__ CUtensorMap mxr,
             const __grid_constant__ CUtensorMap mg, const __grid_constant__ CUtensorMap mu, const __grid_constant__ CUtensorMap md, const Params P) {
  extern __shared__ __align__(1024) uint8_t smem_raw[];
  if (smem_u32(smem_raw) != sb) return;
  const int tid = threadIdx.x, lane = tid & 31;
  if (tid == 256) TS(1);
  const int warp = __shfl_sync(0xffffffffu, tid >> 5, 0), wg = warp >> 2;
  int budget = BUDGET;
  if (warp == 10 && elect_one()) { prefetch_map(&mx); prefetch_map(&mw); }
  int cta;
  {
    uint32_t smid;
    asm volatile("mov.u32 %0, %%smid;" : "=r"(smid));
    if (!BY_SM) cta = blockIdx.x;
    else if (smid < 64) cta = ((smid >> 1) & 7) * 16 + (smid >> 4) * 2 + (smid & 1);
    else if (smid < 120) { const int t = (smid - 64) >> 1, d = (t * 37) >> 8; cta = (1 + t - d * 7) * 16 + 8 + d * 2 + (smid & 1); }
    else cta = smid < 124 ? smid + 8 : smid - 116;
  }
  if (cta >= 128) {
    if (tid == 0) {
      const uint32_t old = atomicAdd(&g_cnt[C_START], 32u);
      wait_count<500>(&g_cnt[C_START], (old & ~255u) + 256u, budget);
    }
    return;
  }
  const int bi = (cta >> 5) * 4 + ((cta >> 2) & 3);
  const int bj = ((cta >> 4) & 1) * 4 + (cta & 3);

  if (wg == 3) {
    asm volatile("setmaxnreg.dec.sync.aligned.u32 64;");
    const int t3 = tid - 384, w3 = warp - 12;
    if (t3 == 0) TSG(0);
    if (t3 < 80) *reinterpret_cast<uint4*>(&g_kvr[cta * 320 + t3 * 4]) = make_uint4(0, 0, 0, 0);
    if (t3 < 17) st_tagged(t3 < 16 ? &g_gate[bi * 128 + bj * 16 + t3] : &g_key[cta], 0, 1);
    bar_sync(0, 512);
#pragma unroll 1
    for (int u = 0; u < 4; u++) {
      const uint4 v = ldg_nc(P.w_phi + bj * 4096 + (u * 128 + t3) * 8);
      sts128(sb + SM_WPHI + u * 2048 + (t3 >> 2) * 64 + (((t3 & 3) ^ ((t3 >> 3) & 3)) << 4),
             pack2(LOG2E * bf_lo(v.x), LOG2E * bf_hi(v.x)), pack2(LOG2E * bf_lo(v.y), LOG2E * bf_hi(v.y)),
             pack2(LOG2E * bf_lo(v.z), LOG2E * bf_hi(v.z)), pack2(LOG2E * bf_lo(v.w), LOG2E * bf_hi(v.w)));
    }
    fence_async_smem();
    warp_arrive(bars + B_WPHI * 8, lane);
    bar_sync(6, 256);
    const uint32_t target = lds32(sb + SM_MISC);
    uint32_t key;
    {
      uint32_t kk[4];
      lds128(sb + SM_MISC + 16, kk);
      if (t3 == 0) st_tagged(&g_key[cta], max(max(kk[0], kk[1]), max(kk[2], kk[3])), target);
      uint2 k, gv;
      __nanosleep(POLLR);
      do {
        __nanosleep(POLL1);
        k = ld_tagged(&g_key[t3]);
        gv = ld_tagged(&g_gate[bi * 128 + t3]);
        budget -= 4;
      } while (!__all_sync(0xffffffffu, k.y == target && gv.y == target) && budget > 0);
      key = __reduce_max_sync(0xffffffffu, k.x);
      if (lane == 0) sts32(sb + SM_MISC + 32 + w3 * 4, key);
      sts32(sb + SM_G + t3 * 4, gv.x);
      bar_sync(5, 128);
      lds128(sb + SM_MISC + 32, kk);
      key = max(max(kk[0], kk[1]), max(kk[2], kk[3]));
    }
    const int idx = (0xFFFF - (key & 0xFFFF)) & (kS - 1);
    if (t3 == 0) { sts32(sb + SM_MISC + 4, idx); TS(8); }
    warp_arrive(bars + B_INFO * 8, lane);
    {
      const uint4 v = ldg_nc(P.x + (size_t)idx * kD + t3 * 8);
      sts128(sb + SM_BAND + t3 * 16, v.x, v.y, v.z, v.w);
    }
    const int t2 = (lane & 3) * 2, row = w3 * 16 + (lane >> 2);
    float a[4];
    uint32_t buf = 0, ph = 0;
    fence_async_smem();
    bar_sync(5, 128);
    {
      const int r = cta >> 4;
#pragma unroll 1
      for (int part = 0; part < 2; part++) {
        const int n = part ? 14 - 2 * r : 2 * r;
        moe_chunks<false>(a, n, buf, ph, P.da, P.dxs + (part ? 0 : (16 - n) * 8), lane == 0);
        uint2* dst = &g_pre[(((cta >> 2) & 2) + 1 - part) * kF + ((r - 1 + part) * 8 + (cta & 7)) * 64 + row];
        if (t2 == 0 && n) { st_tagged(dst, __float_as_uint(a[0]), target); st_tagged(dst + 8, __float_as_uint(a[2]), target); }
      }
    }
    if (t3 == 0) TS(9);
    bar_sync(5, 128);
    sts128(sb + SM_BAND + t3 * 16, 0, 0, 0, 0);
    {
      __nanosleep(POLL0);
      float gs, us;
      gather<kF, 4>(&g_pre[(cta >> 2) * 112 + min(t3, 111)], target, gs, us, budget);
      bar_sync(5, 128);
      if (t3 < 112) sts16(sb + SM_BAND + 112 + (t3 >> 3) * 128 + (t3 & 7) * 2, pack2(gs * sigmoidf(gs) * us, 0.f));
    }
    fence_async_smem();
    bar_sync(5, 128);
    if (t3 == 0) TS(12);
    moe_chunks<true>(a, 7, buf, ph, P.da, P.dband + 7, lane == 0);
    if (t3 == 0) TS(10);
    if (t2 < 4) {
      uint2* dst = &g_yp[(cta >> 2) * kD + (cta & 3) * 256 + t2 * 64 + row];
      st_tagged(dst, __float_as_uint(a[0]), target); st_tagged(dst + 8, __float_as_uint(a[2]), target);
      st_tagged(dst + 64, __float_as_uint(a[1]), target); st_tagged(dst + 72, __float_as_uint(a[3]), target);
    }
    if (lane == 0) mbar_arrive(bars + B_MD * 8);
    if ((idx >> 7) == bi) {
      mbar_wait(bars + (B_PUB + 3) * 8, 0, budget);
      if (w3 == 0) probe(&g_yp[lane * kD + bj * 128], target, budget);
      bar_sync(5, 128);
      float y = 0.f;
#pragma unroll 1
      for (int hf = 0; hf < 2; hf++) {
        float y0, y1;
        gather<kD, 16>(&g_yp[hf * 16 * kD + bj * 128 + t3], target, y0, y1, budget);
        y += y0 + y1;
      }
      const uint32_t ob = key >> 16;
      const float upd = y * sigmoidf(__uint_as_float(((ob & 0x8000u) ? (ob ^ 0x8000u) : (~ob & 0xFFFFu)) << 16));
      const uint32_t a = sb + SM_PHI + (t3 >> 6) * 16384 + (idx & 127) * 128 + ((((t3 >> 3) & 7) ^ (idx & 7)) << 4) + (t3 & 7) * 2;
      mbar_wait(bars + B_XT * 8, 0, budget);
      uint16_t xb;
      asm volatile("ld.shared.u16 %0, [%1];" : "=h"(xb) : "r"(a) : "memory");
      sts16(a, pack2(bf_lo(xb) + upd, 0.f));
      warp_arrive(bars + B_XP * 8, lane);
      if (t3 == 0) TS(11);
    }
  } else if (wg < 2) {
    if ((warp & 3) < EARLY_N && lane < (wg ? 8 : 16)) {
      const int n = warp & 3;
      const __nv_bfloat16* p = wg ? P.w + (size_t)(n * 64 + bi + (lane >> 1) * 16) * (3 * kD) + 1024 + (lane & 1) * 1024 + bj * 128
                                  : P.x + (size_t)(bi * 128 + bj * 16 + lane) * kD + n * 64;
      if (n) __nanosleep(n * EARLY_GAP);
      asm volatile("prefetch.global.L2 [%0];" :: "l"(p));
    }
    __syncwarp();
    asm volatile("setmaxnreg.inc.sync.aligned.u32 208;");
    const int tw = tid & 127, w = warp & 3, g = lane >> 2, t = lane & 3;
    const bool lane0 = lane == 0;
    if (wg == 0) sts128(sb + SM_Z + (tw & 63) * 16, 0x3f803f80u, 0x3f803f80u, 0x3f803f80u, 0x3f803f80u);
    bar_sync(0, 512);
    if (wg == 1) {
      float sr[4], sg[4];
      zero(sr); zero(sg);
#pragma unroll 1
      for (int c = 0; c < 4; c++) {
        mbar_wait(bars + (B_RX + c) * 8, 0, budget);
        uint32_t rs[4], gs[4], xs[4][4];
        lds128(sb + SM_V + c * 512 + lane * 16, rs);
        lds128(sb + SM_V + 2048 + c * 512 + lane * 16, gs);
#pragma unroll
        for (int r = 0; r < 4; r++) lds128(sb + SM_PHI + c * 8192 + (w * 4 + r) * 512 + lane * 16, xs[r]);
#pragma unroll
        for (int e = 0; e < 4; e++) {
          const float r0 = bf_lo(rs[e]), r1 = bf_hi(rs[e]), g0 = bf_lo(gs[e]), g1 = bf_hi(gs[e]);
#pragma unroll
          for (int r = 0; r < 4; r++) {
            const float x0 = bf_lo(xs[r][e]), x1 = bf_hi(xs[r][e]);
            sr[r] = fma_v(x0, r0, sr[r]); sg[r] = fma_v(x0, g0, sg[r]);
            sr[r] = fma_v(x1, r1, sr[r]); sg[r] = fma_v(x1, g1, sg[r]);
            if (r != 1) yield_slot();
          }
        }
      }
      fence_async_smem();
      __syncwarp();
      if (lane < 3) mbar_arrive(bars + (B_ME + lane) * 8);
      const bool b4 = lane & 16, b3 = lane & 8, b2 = lane & 4;
      const float v = qsum(fold(fold(fold(sr[0], sg[0], b4, 16), fold(sr[2], sg[2], b4, 16), b3, 8),
                                fold(fold(sr[1], sg[1], b4, 16), fold(sr[3], sg[3], b4, 16), b3, 8), b2, 4));
      const int row = bi * 128 + bj * 16 + w * 4 + (g & 3);
      const uint32_t rb = pack2(v + 0.f, 0.f);
      const uint32_t ob = (rb & 0x8000u) ? (~rb & 0xFFFFu) : (rb | 0x8000u);
      const uint32_t best = __reduce_max_sync(0xffffffffu, b4 ? 0u : (ob << 16) | (0xFFFFu - row));
      mbar_wait(bars + B_EPOCH * 8, 0, budget);
      const uint32_t tag = lds32(sb + SM_MISC);
      if (lane0) sts32(sb + SM_MISC + 16 + w * 4, best);
      if (b4 && t == 0) st_tagged(&g_gate[row], __float_as_uint(sigmoidf(v)), tag);
      if (tw == 0) TS(14);
      bar_arrive(6, 256);
      bar_sync(1, 256);
    }

    {
      float acc[2][64];
      if (tw == 0) TS(16 + wg * 16);
      mainloop128(acc, P.da, P.db, wg, wg, 16, lane0, budget, cta, wg * 16);
      bar_sync(1 + wg, 256);
      wg_wait<0>();
      pin(acc[0]); pin(acc[1]);
      if (lane0) mbar_arrive_n(bars + (B_EM + wg) * 8, 2);
      if (tw == 0) TS(17 + wg * 16);
      float p[4][16];
      uint32_t vp[8][4];
      const uint32_t av = sb + SM_V + (w * 16 + g) * 64 + ((t ^ (g >> 1)) << 4);
      {
        uint32_t kf[4][2][4];
#pragma unroll
        for (int u = 0; u < 4; u++)
#pragma unroll
          for (int s = 0; s < 2; s++)
#pragma unroll
            for (int r = 0; r < 4; r++) kf[u][s][r] = pack2(acc[u & 1][16 * (u >> 1) + 8 * s + 2 * r], acc[u & 1][16 * (u >> 1) + 8 * s + 2 * r + 1]);
        mbar_wait(bars + B_WPHI * 8, 0, budget);
        const uint64_t dw = P.dw + wg * 256;
        wg_fence();
#pragma unroll
        for (int u = 0; u < 4; u++) {
          wgmma_m64n32k16_rs<1>(p[u], kf[u][0], dw + (u >> 1) * 128, 0);
          wgmma_m64n32k16_rs<1>(p[u], kf[u][1], dw + (u >> 1) * 128 + 64, 1);
        }
        wg_commit();
#pragma unroll
        for (int u = 0; u < 8; u++) {
          const float* a = &acc[(u >> 1) & 1][32 + 16 * (u >> 2) + 2 * (u & 1)];
          vp[u][0] = pack2(a[0], a[1]); vp[u][1] = pack2(a[4], a[5]); vp[u][2] = pack2(a[8], a[9]); vp[u][3] = pack2(a[12], a[13]);
          if (u < 4) sts128(av + (u >> 1) * 4096 + (u & 1) * 512, vp[u][0], vp[u][1], vp[u][2], vp[u][3]);
        }
        pinr(vp);
        wg_wait<0>();
#pragma unroll
        for (int u = 0; u < 4; u++) pin(p[u]);
      }
      if (tw == 0) TS(18 + wg * 16);
      float kv[2][20];
      {
        const uint32_t sphi = sb + SM_PHI + (w * 16 + (lane & 15)) * 128 + (((lane >> 4) ^ (lane & 7)) << 4);
        float top = 0.f;
        uint32_t pk[4][2][4];
        float ps[2], sa[4], sc[4];
        uint32_t redo = 0;
#pragma unroll
        for (int i = 0; i < 11; i++) {
          if (i >= 3) {
            const int j = i - 3;
            const float s0 = sc[0] + sc[2], s1 = sc[1] + sc[3];
            top = fmaxf(top, fmaxf(s0, s1));
            store_phi((sphi ^ ((j & 1) * 64)) + (j & 2) * 4096, pk[j & 3], rcp2(s0), rcp2(s1));
          }
          if (i >= 2 && i <= 9) {
            sc[0] = sa[0] + sa[2]; sc[1] = sa[1] + sa[3];
            sc[2] = __shfl_xor_sync(0xffffffffu, sc[0], 2); sc[3] = __shfl_xor_sync(0xffffffffu, sc[1], 2);
          }
          if (i >= 1 && i <= 8) {
            sa[0] = ps[0]; sa[1] = ps[1];
            sa[2] = __shfl_xor_sync(0xffffffffu, sa[0], 1); sa[3] = __shfl_xor_sync(0xffffffffu, sa[1], 1);
          }
          if (i < 8) {
            pin(p[i >> 1]);
            float e[16];
#pragma unroll
            for (int c = 0; c < 16; c++) e[c] = ex2((i & 1) ? -p[i >> 1][c] : p[i >> 1][c]);
            pack_sums(e, pk[i & 3], ps);
            pinr(pk[i & 3]); pin(ps);
          }
          if (i < 10) yield_slot();
          if (i >= 2 && i <= 9) pin(sc);
          if (i >= 1 && i <= 8) pin(sa);
          if (i == 2 && wg) mbar_wait(bars + B_RD * 8, 0, budget);
          if (i >= 4 && !(i & 1)) {
            const int u = (i - 4) >> 1;
            fence_async_smem();
            wg_wait<0>();
            if (u < 3) bar_sync(7 + wg, 128);
            else asm volatile("{\n.reg .pred p, q;\nsetp.ne.b32 p, %2, 0;\nbar.red.or.pred q, %1, 128, p;\nselp.u32 %0, 1, 0, q;\n}"
                              : "=r"(redo) : "r"(7 + wg), "r"((uint32_t)!(top < EXP_LIM_F)) : "memory");
            issue_kv(kv[u >> 1], P.dphi + (u & 1) * 512, P.dv - (u & 1) * DV_TILE, u & 1);
            if (u == 1 || u == 2) {
#pragma unroll
              for (int r = 0; r < 2; r++) sts128(av + ((u + 1) & 1) * 4096 + r * 512, vp[2 * u + 2 + r][0], vp[2 * u + 2 + r][1], vp[2 * u + 2 + r][2], vp[2 * u + 2 + r][3]);
            }
            if (u < 3) yield_slot();
          }
        }
        if (tw == 0) TS(19 + wg * 16);
        wg_wait<0>();
        pin(kv[0]); pin(kv[1]);
        if (__builtin_expect(__any_sync(0xffffffffu, redo), 0)) {
#pragma unroll 1
          for (int u = 0; u < 4; u++) {
            bar_sync(7 + wg, 128);
#pragma unroll 1
            for (int sg = 0; sg < 2; sg++) {
              float e[16];
              exp_shifted(p[0], sg ? -1.f : 1.f, e);
              pack_sums(e, pk[0], ps);
              store_phi(sphi ^ (sg * 64), pk[0], rcp2(qsum(ps[0])), rcp2(qsum(ps[1])));
            }
            sts128(av, vp[0][0], vp[0][1], vp[0][2], vp[0][3]);
            sts128(av + 512, vp[1][0], vp[1][1], vp[1][2], vp[1][3]);
            fence_async_smem();
            bar_sync(7 + wg, 128);
            issue_kv(kv[1], P.dphi, P.dv, u & 1);
            wg_wait<0>();
            pin(kv[1]);
#pragma unroll
            for (int c = 0; c < 16; c++) { p[0][c] = p[1][c]; p[1][c] = p[2][c]; p[2][c] = p[3][c]; }
#pragma unroll
            for (int c = 0; c < 24; c++) vp[c >> 2][c & 3] = vp[(c >> 2) + 2][c & 3];
            if (u == 1) {
#pragma unroll
              for (int c = 0; c < 20; c++) kv[0][c] = kv[1][c];
            }
          }
        }
      }
      if (tw == 0) TS(20 + wg * 16);
      bar_sync(7 + wg, 128);
      {
        const int srow = w * 16 + (lane & 15);
        const uint32_t a0 = sb + SM_PHI + srow * 64 + (((lane >> 4) ^ ((srow >> 1) & 3)) << 4);
#pragma unroll
        for (int q = 0; q < 4; q++) {
          const float* a = &kv[q >> 1][8 * (q & 1)];
          stmatrix4((a0 ^ ((q & 1) * 32)) + (q >> 1) * 4096, pack2(a[0], a[1]), pack2(a[2], a[3]), pack2(a[4], a[5]), pack2(a[6], a[7]));
        }
        const uint32_t z = pack2(t == 0 ? kv[0][16] : t == 1 ? kv[1][16] : t == 2 ? kv[0][18] : kv[1][18], 0.0625f);
        sts128(sb + SM_PHI + 8192 + ((w & 1) * 16 + (t >> 1) * 8 + g) * 64 + ((((w & 2) + (t & 1)) ^ (g >> 1)) << 4), z, z, z, z);
      }
      fence_async_smem();
      warp_arrive(bars + (B_RED + wg) * 8, lane);
      if (tw == 0) TS(51 + wg * 4);
    }

    uint32_t stash = sb + 3 * STAGE + 8192 + w * 2048 + lane * 16;
    const int rowl = wg * 64 + w * 16 + g;
    mbar_wait(bars + B_INFO * 8, 0, budget);
    const float gA = ldsf(sb + SM_G + rowl * 4), gB = ldsf(sb + SM_G + rowl * 4 + 32);
    __nv_bfloat16* og = P.o + (size_t)(bi * 128 + rowl) * kD + bj * 128 + t * 8;
    uint32_t own = sb + 3 * STAGE + rowl * 128 + ((t ^ g) << 4);
    uint32_t sx = sb + SM_PHI + (wg * 64 + w * 16 + (lane & 15)) * 128 + (((lane >> 4) ^ (lane & 7)) << 4);
    uint32_t routed = (lds32(sb + SM_MISC + 4) >> 4) == (uint32_t)(bi * 8 + warp);
    asm volatile("" : "+l"(og), "+r"(own), "+r"(stash), "+r"(sx), "+r"(routed));
    {
      float p[4][16];
      uint32_t ef[2][4][4];
      uint32_t top = EXP_TOP;
      if (wg == 0) {
        float acc[2][64];
        bar_sync(2, 256);
        if (tw == 0) TS(22);
        mainloop128(acc, P.da, P.db, 32 % NST, (32 / NST) & 1, 12, lane0, budget, cta, 32);
#pragma unroll 1
        for (int n = 0; n < 4; n++) {
          const uint32_t slot = n ? n - 1 : 4;
          if (tw == 0) KS(128 + 44 + n);
          mbar_wait(bars + B_FX * 8 + slot * 8, n != 0, budget);
          if (tw == 0) KS(44 + n);
          kstep64(acc[0], P.da + slot * (STAGE >> 4), P.db + slot * (STAGE >> 4), 1);
          wg_wait<1>();
          if (n == 0 && lane0) mbar_arrive_n(bars + (B_EM + 43 % NST) * 8, 2);
        }
        kstep64(acc[1], P.da + 512 + (44 % NST) * (STAGE >> 4), P.db + (44 % NST) * (STAGE >> 4), 1);
        wg_wait<1>();
        pin(acc[0]);
        if (tw == 0) TS(15);
        {
          uint32_t qf[4][2][4];
#pragma unroll
          for (int u = 0; u < 8; u++)
#pragma unroll
            for (int r = 0; r < 4; r++) qf[u >> 1][u & 1][r] = pack2(acc[0][8 * u + 2 * r], acc[0][8 * u + 2 * r + 1]);
          issue_pq(p, qf, P.dw);
          kstep64(acc[1], P.da + 512 + (45 % NST) * (STAGE >> 4), P.db + (45 % NST) * (STAGE >> 4), 1);
          wg_wait<1>();
        }
#pragma unroll
        for (int h = 0; h < 4; h++) pin(p[h]);
        if (tw == 0) TS(24);
#pragma unroll
        for (int h = 0; h < 2; h++) {
          if (lane0) mbar_arrive_n(bars + (B_EM + (44 + h) % NST) * 8, 2);
          kstep64(acc[1], P.da + 512 + ((46 + h) % NST) * (STAGE >> 4), P.db + ((46 + h) % NST) * (STAGE >> 4), 1);
          yield_slot();
          pin(p[h]);
          top = exp_frags(p[h], ef[h], top);
          pinr(ef[h]);
          yield_slot();
          if (h == 0) wg_wait<1>(); else wg_wait<0>();
        }
        pin(acc[1]);
        if (lane0) { mbar_arrive_n(bars + (B_EM + 46 % NST) * 8, 2); mbar_arrive_n(bars + (B_EM + 47 % NST) * 8, 2); }
        if (tw == 0) TS(23);
        RG(0);
#pragma unroll
        for (int u = 0; u < 8; u++) {
          const float* a = &acc[1][8 * u];
          sts128(stash + (u >> 2) * STAGE + (u & 3) * 512, pack2(a[0], a[1]), pack2(a[2], a[3]), pack2(a[4], a[5]), pack2(a[6], a[7]));
        }
        warp_arrive(bars + B_QS * 8, lane);
        RG(1);
      } else {
        uint32_t qf[4][2][4];
        mbar_wait(bars + B_QS * 8, 0, budget);
        RG(1);
#pragma unroll
        for (int u = 0; u < 8; u++) lds128(stash + (u >> 2) * STAGE + (u & 3) * 512, qf[u >> 1][u & 1]);
        __syncwarp();
        issue_pq(p, qf, P.dw);
        wg_wait<0>();
#pragma unroll
        for (int h = 0; h < 4; h++) pin(p[h]);
        if (tw == 0) TS(40);
      }

#pragma unroll 1
      for (int pr = 0; pr < 2; pr++) {
        RG(2 + pr * 8);
        if (YIELD_EXP && pr > wg) bar_sync(11, 256);
        if (pr | wg) top = exp_frags(p[1], ef[1], exp_frags(p[0], ef[0], EXP_TOP));
        if (YIELD_EXP && pr < wg) { pinr(ef[0]); pinr(ef[1]); bar_arrive(11, 256); }
        if (__builtin_expect(__any_sync(0xffffffffu, top != EXP_TOP), 0)) {
#pragma unroll 1
          for (int u = 0; u < 4; u++) {
            float e[16];
            exp_shifted(p[0], (u & 1) ? -1.f : 1.f, e);
#pragma unroll
            for (int r = 0; r < 4; r++) {
#pragma unroll
              for (int s = 0; s < 6; s++) ef[s >> 2][s & 3][r] = ef[(s + 2) >> 2][(s + 2) & 3][r];
              ef[1][2][r] = pack2(e[2 * r], e[2 * r + 1]);
              ef[1][3][r] = pack2(e[8 + 2 * r], e[8 + 2 * r + 1]);
            }
            if (u & 1) {
#pragma unroll
              for (int e2 = 0; e2 < 16; e2++) p[0][e2] = p[1][e2];
            }
          }
        }
        float np[2][20], nm[2][20];
        RG(3 + pr * 8);
        mbar_wait(bars + (B_KV + pr) * 8, 0, budget);
        RG(4 + pr * 8);
        wg_fence();
#pragma unroll
        for (int hh = 0; hh < 2; hh++) {
          const uint64_t dk = P.dv - (uint64_t)pr * ((384ull << 16) - 512ull) - hh * ((255ull << 16) - 256ull);
          wgmma_m64n40k16_rs<1>(np[hh], ef[hh][0], dk, 0);
          wgmma_m64n40k16_rs<1>(np[hh], ef[hh][1], dk + 64, 1);
          wgmma_m64n40k16_rs<1>(nm[hh], ef[hh][2], dk + 128 - (126ull << 16), 0);
          wgmma_m64n40k16_rs<1>(nm[hh], ef[hh][3], dk + 192 - (126ull << 16), 1);
          wg_commit();
        }
#pragma unroll
        for (int hh = 0; hh < 2; hh++) {
          if (hh == 0) wg_wait<1>(); else wg_wait<0>();
          pin(np[hh]); pin(nm[hh]);
          RG(5 + hh + pr * 8);
          uint32_t o[2][4];
#pragma unroll
          for (int r = 0; r < 2; r++) {
            const float dp = np[hh][16 + 2 * r], sp = np[hh][17 + 2 * r], dm = nm[hh][16 + 2 * r], sm = nm[hh][17 + 2 * r];
            const float inv = (r == 0 ? gA : gB) * rcp(fmaf(dp, sm, fmaf(1e-6f, sm, dm) * sp));
            const float cp = sm * inv, cm = sp * inv;
#pragma unroll
            for (int c = 0; c < 4; c++)
              o[r][c] = pack2(fmaf(np[hh][4 * c + 2 * r], cp, nm[hh][4 * c + 2 * r] * cm), fmaf(np[hh][4 * c + 2 * r + 1], cp, nm[hh][4 * c + 2 * r + 1] * cm));
            sts128((own ^ (hh * 64)) + r * 1024, o[r][0], o[r][1], o[r][2], o[r][3]);
          }
          if (hh == 1 && pr == 1) fence_async_smem();
#pragma unroll
          for (int r = 0; r < 2; r++) asm volatile("st.global.v4.u32 [%0], {%1,%2,%3,%4};" :: "l"(og + r * 8 * kD + hh * 32), "r"(o[r][0]), "r"(o[r][1]), "r"(o[r][2]), "r"(o[r][3]) : "memory");
        }
        RG(7 + pr * 8);
        warp_arrive(bars + (B_PUB + wg * 2 + pr) * 8, lane);
        RG(8 + pr * 8);
        if (tw == 0) TS(25 + pr + wg * 16);
        if (pr) break;
        og += 64; own += STAGE;
#pragma unroll
        for (int e = 0; e < 16; e++) { p[0][e] = p[2][e]; p[1][e] = p[3][e]; }
      }
    }
    uint32_t xf[8][4];
    if (!wg) {
      mbar_wait(bars + B_XT * 8, 0, budget);
      load_x(sx, xf);
      mbar_wait(bars + (B_PUB + 3) * 8, 0, budget);
    } else {
#pragma unroll
      for (int i = 0; i < 32; i++) xf[i >> 2][i & 3] = 0;
    }
    bar_sync(7 + wg, 128);

    RG(18);
    float oacc[64];
    {
      const uint64_t dam = P.da + wg * 512;
      uint32_t slot = 3, ph = 1, prev = 0;
#pragma unroll 1
      for (int s = 0; s < 16; s++) {
        if (tid == 0) KS(128 + 48 + s);
        if (!wg || s <= 16 - END_SKEW) {
          mbar_wait(bars + B_FX * 8 + slot * 8, ph, budget);
          if (s >= 2) mbar_wait(bars + (B_FY + wg * NST) * 8 + slot * 8, ph, budget);
        }
        if (tid == 0) KS(48 + s);
        if (tid == 128) KS(192 + 48 + s);
        if (wg && s == 16 - END_SKEW) {
          mbar_wait(bars + B_XT * 8, 0, budget);
          load_x(sx, xf);
#pragma unroll
          for (int n = 65 - END_SKEW; n < 64; n++) mbar_wait(bars + (B_FY + NST + n % NST) * 8, (n / NST) & 1, budget);
          bar_sync(12, 256);
        }
        const uint64_t da = dam + slot * (STAGE >> 4), db = P.db + slot * (STAGE >> 4);
#pragma unroll
        for (int hf = 0; hf < 2; hf++) {
          wg_wait<1>();
          if (hf && s > 0 && s < 12 && lane0) mbar_arrive(bars + B_EM * 8 + prev * 8);
          wg_fence();
          wgmma_m64n128k16_ss<0, 1>(oacc, da + hf * 4, db + hf * 256, hf ? 1 : s);
          wgmma_m64n128k16_ss<0, 1>(oacc, da + hf * 4 + 2, db + hf * 256 + 128, 1);
          wg_commit();
        }
        prev = slot;
        if (++slot == NST) { slot = 0; ph ^= 1; }
      }
      if (!wg) bar_arrive(12, 256);
    }
    if (__any_sync(0xffffffffu, routed)) { mbar_wait(bars + B_XP * 8, 0, budget); load_x(sx, xf); }
    const float hA = 1.0f - gA, hB = 1.0f - gB;
    float xv[64];
#pragma unroll
    for (int i = 0; i < 32; i++) { xv[2 * i] = bf_lo(xf[i >> 2][i & 3]); xv[2 * i + 1] = bf_hi(xf[i >> 2][i & 3]); }
    pin(xv);
    yield_slot();
    wg_wait<0>();
    pin(oacc);
    if (tw == 0) TS(29 + wg * 16);
#pragma unroll
    for (int hf = 0; hf < 2; hf++) {
#pragma unroll
      for (int u = hf * 4; u < hf * 4 + 4; u++) {
        const float* a = &oacc[8 * u];
        const float* b = &xv[8 * u];
        stmatrix4((sx ^ ((u & 3) * 32)) + hf * 16384,
                  pack2(fmaf(hA, b[0], a[0]), fmaf(hA, b[1], a[1])), pack2(fmaf(hB, b[2], a[2]), fmaf(hB, b[3], a[3])),
                  pack2(fmaf(hA, b[4], a[4]), fmaf(hA, b[5], a[5])), pack2(fmaf(hB, b[6], a[6]), fmaf(hB, b[7], a[7])));
        if (FIN_YIELD) yield_slot();
      }
      fence_async_smem();
      __syncwarp();
      if (elect_one()) tma_store(&mout, sb + SM_PHI + hf * 16384 + warp * 2048, bj * 128 + hf * 64, bi * 128 + warp * 16);
    }
    if (elect_one()) {
      asm volatile("cp.async.bulk.commit_group;" ::: "memory");
      asm volatile("cp.async.bulk.wait_group.read 0;" ::: "memory");
    }
  } else {
    asm volatile("setmaxnreg.dec.sync.aligned.u32 32;");
    if (warp == 8) {
      if (elect_one()) {
        TS(7);
#pragma unroll
        for (int s = 0; s < NST; s++) mbar_init(bars + (B_FX + s) * 8, 1);
        asm volatile("fence.mbarrier_init.release.cluster;" ::: "memory");
        fence_async_smem();
      }
      __syncwarp();
      bar_arrive(0, 512);
      if (elect_one()) {
#pragma unroll 1
        for (int n = 0; n < NST; n++) {
          const uint32_t st = sb + n * STAGE, fb = bars + (B_FX + n) * 8;
          KS(64 + n);
          mbar_expect_tx(fb, STAGE);
          tma_load(st, &mx, fb, n * 64, bi * 128);
          tma_load(st + 16384, &mw, fb, 1024 + bj * 128, n * 64);
          tma_load(st + 24576, &mw, fb, 2048 + bj * 128, n * 64);
        }
      }
      __syncwarp();
      bar_sync(10, 64);
    } else {
      if (warp == 9) {
        if (elect_one()) {
#pragma unroll
          for (int s = B_FY; s < B_NUM; s++) mbar_init(bars + s * 8, s < B_WPHI ? 1 : s < B_EM ? 4 : 8);
          asm volatile("fence.mbarrier_init.release.cluster;" ::: "memory");
          fence_async_smem();
        }
        __syncwarp();
        bar_arrive(10, 64);
      }
      bar_sync(0, 512);
    }
    if (!elect_one()) return;
    if (warp == 8) {
      uint32_t slot = 0, ph = 0;
#pragma unroll 1
      for (int n = NST; n < 48; n++) {
        const int t = n >> 4, k = n & 15;
        const int c0 = t == 2 ? bj * 128 : 1024 + bj * 128 + t * 64, c1 = t == 2 ? c0 + 64 : c0 + 1024;
        const uint32_t st = sb + slot * STAGE, fb = bars + (B_FX + slot) * 8;
        if (n <= NST + 3 * RSTEP && (n - NST) % RSTEP == 0) {
          const int c = (n - NST) / RSTEP;
          mbar_expect_tx(bars + (B_RX + c) * 8, c == 0 ? 8192 + 4096 : 8192);
          tma_load(sb + SM_PHI + c * 8192, &mxr, bars + (B_RX + c) * 8, c * 256, bi * 128 + bj * 16);
          if (c == 0) { bulk_load(sb + SM_V, P.w_r, 2048, bars + B_RX * 8); bulk_load(sb + SM_V + 2048, P.gate_w, 2048, bars + B_RX * 8); }
        }
        mbar_wait(bars + (B_EM + slot) * 8, ph, budget);
        KS(64 + n);
        mbar_expect_tx(fb, STAGE);
        tma_load(st, &mx, fb, k * 64, bi * 128);
        tma_load(st + 16384, &mw, fb, c0, k * 64);
        tma_load(st + 24576, &mw, fb, c1, k * 64);
        {
          const int m = n + WLEAD, tm = m >> 4;
          if ((m & 3) == (bi & 3)) {
            const int d0 = tm >= 2 ? bj * 128 : 1024 + bj * 128 + tm * 64, d1 = tm >= 2 ? d0 + 64 : d0 + 1024;
            tma_prefetch(tm == 3 ? &mwo : &mw, d0, (m & 15) * 64); tma_prefetch(tm == 3 ? &mwo : &mw, d1, (m & 15) * 64);
          }
        }
        if (++slot == NST) { slot = 0; ph ^= 1; }
      }
#pragma unroll 1
      for (int m = WLEAD + ((bi - WLEAD) & 3); m < 16; m += 4) { tma_prefetch(&mwo, bj * 128, m * 64); tma_prefetch(&mwo, bj * 128 + 64, m * 64); }
#pragma unroll 1
      for (int s = 0; s < 16; s++) {
        const int p = s < 2 ? s : (s >= 9), q = s < 9 ? s - 2 : s - 9;
        const int k0 = (s < 2 ? bj : q + (q >= bj)) * 128 + p * 64;
        const uint32_t st = sb + slot * STAGE, fb = bars + (B_FX + slot) * 8;
        mbar_wait(bars + (B_EM + slot) * 8, ph, budget);
        KS(64 + 48 + s);
        mbar_expect_tx(fb, 16384);
        tma_load(st + 16384, &mwo, fb, bj * 128, k0);
        tma_load(st + 24576, &mwo, fb, bj * 128 + 64, k0);
        if (++slot == NST) { slot = 0; ph ^= 1; }
      }
      if (REPF) prefetch_map(&mout);
    } else if (warp == 9) {
      prefetch_map(&mo); prefetch_map(&mout);
      uint32_t old;
      asm volatile("atom.add.release.gpu.global.u32 %0, [%1], 1;" : "=r"(old) : "l"(&g_cnt[C_START]) : "memory");
      sts32(sb + SM_MISC, (old & ~255u) + 256u);
      mbar_arrive(bars + B_EPOCH * 8);
      const CUtensorMap* m = (cta & 8) ? &mu : &mg;
      const int l0 = (cta >> 4) * 14, a0 = (cta & 7) * 64, d1 = (cta >> 2) * 112 - 14 * 16, d2 = (cta & 3) * 4;
      uint32_t buf = 0, ph = 0, tnext;
      asm volatile("mov.u32 %0, %%clock;" : "=r"(tnext));
#pragma unroll 1
      for (int c = 0; c < 21; c++) {
        const uint32_t dst = sb + moe_buf(buf), fb = bars + (B_MF + buf) * 8;
        mbar_wait(bars + (B_ME + buf) * 8, ph, budget);
        mbar_expect_tx(fb, 8192);
        if (c < 14) tma_load(dst, m, fb, a0 + ((l0 + c) >> 4) * 512, ((l0 + c) & 15) * 64); else tma_load3(dst, &md, fb, d1 + c * 16, d2);
        if (MLEAD && c >= 2 && c + MLEAD < 17) {
          const int f = c + MLEAD;
          if (f < 14) tma_prefetch(m, a0 + ((l0 + f) >> 4) * 512, ((l0 + f) & 15) * 64); else tma_prefetch3(&md, d1 + f * 16, d2);
        }
        if (MPACE) { uint32_t now; do { asm volatile("mov.u32 %0, %%clock;" : "=r"(now)); if ((int32_t)(now - tnext) >= 0) break; __nanosleep(20); } while (true); tnext = now + MPACE; }
        if (c == 16) {
#pragma unroll 1
          for (int f = 17; f < 21; f++) { __nanosleep(MGAP); tma_prefetch3(&md, d1 + f * 16, d2); }
        }
        if (c < 2) __nanosleep(MGAP);
        if (c == 17) mbar_arrive(bars + B_M2 * 8);
        if (++buf >= (c >= 14 ? 2 : 3)) { buf = 0; ph ^= 1; }
      }
      mbar_wait(bars + B_MD * 8, 0, budget);
      mbar_wait(bars + (B_RD + 1) * 8, 0, budget);
      mbar_wait(bars + XT_GATE * 8, 0, budget);
      mbar_expect_tx(bars + B_XT * 8, 32768);
      tma_load(sb + SM_PHI, &mx, bars + B_XT * 8, bj * 128, bi * 128);
      tma_load(sb + SM_PHI + 16384, &mx, bars + B_XT * 8, bj * 128 + 64, bi * 128);
      mbar_wait(bars + (B_PUB + 1) * 8, 0, budget);
      mbar_wait(bars + (B_PUB + 3) * 8, 0, budget);
      signal_add(&g_cnt[(C_O + bi * 4 + 1) * 32], 32u);
      TS(57);
      wait_count<POLLF>(&g_cnt[(C_O + bi * 4 + 1) * 32], (old & ~255u) + 256u, budget);
      mbar_arrive(bars + B_P1 * 8);
      TS(3);
    } else {
      const int u = warp - 10, hp = bj * 2 + u;
      mbar_wait(bars + B_EPOCH * 8, 0, budget);
      const uint32_t target = lds32(sb + SM_MISC);
      mbar_wait(bars + B_INFO * 8, 0, budget);
      wait_count<200>(&g_cnt[C_START], target, budget);
      fence_async_global();
#pragma unroll 1
      for (int e = 0; e < 2; e++) {
        uint32_t* cnt = &g_cnt[(e ? C_O + bi * 4 + u * 2 : C_KV + hp) * 32];
        mbar_wait(bars + (e ? B_PUB + u * 2 : B_RED + u) * 8, 0, budget);
        if (e == 0) {
#pragma unroll 1
          for (uint32_t c = 0, n = u ? RED_CH1 : RED_CH, sz = 10240 / n, cc = RED_ROT ? bi % n : 0; c < n; c++) {
            bulk_reduce(reinterpret_cast<char*>(&g_kvr[hp * 2560]) + cc * sz, sb + SM_PHI + cc * sz, sz);
            if (++cc == n) cc = 0;
            if (c + 1 < n) __nanosleep(u ? RED_GAP1 : RED_GAP0);
          }
          asm volatile("cp.async.bulk.commit_group;" ::: "memory");
          asm volatile("cp.async.bulk.wait_group 0;" ::: "memory");
          TS(21 + u * 16);
          mbar_arrive(bars + (B_RD + u) * 8);
        }
        signal_add(cnt, e ? 32u : 16u);
        TS(e ? 56 + u * 2 : 60 + u);
        if (REPF && e) prefetch_map(&mo);
        if (e == 0) {
          mbar_wait(bars + (u ? B_M2 : B_RED + 1) * 8, 0, budget);
        }
        wait_count<POLLF>(cnt, target, budget);
        fence_async_global();
        if (e == 0) {
          mbar_expect_tx(bars + (B_KV + u) * 8, 10240);
          bulk_load(sb + SM_V + u * 8192, &g_kvr[hp * 2560], 8192, bars + (B_KV + u) * 8);
          bulk_load(sb + SM_Z + u * 2048, &g_kvr[hp * 2560 + 2048], 2048, bars + (B_KV + u) * 8);
          TS(38 + u);
        }
      }
      TS(2 + u * 2);
      if (u == 0) mbar_wait(bars + B_QS * 8, 0, budget);
      uint32_t slot = 0, ph = 1;
#pragma unroll 1
      for (int s = 2; s < 16; s++) {
        const int p = s >= 9, q = s < 9 ? s - 2 : s - 9;
        if (s == 9) { mbar_wait(bars + B_P1 * 8, 0, budget); fence_async_global(); }
        const uint32_t fb = bars + (B_FY + u * NST + slot) * 8;
        mbar_wait(bars + (B_EM + slot) * 8, ph, budget);
        mbar_expect_tx(fb, 8192);
        tma_load(sb + slot * STAGE + u * 8192, &mo, fb, (q + (q >= bj)) * 128 + p * 64, bi * 128 + u * 64);
        if (++slot == NST) { slot = 0; ph ^= 1; }
      }
    }
  }
}

typedef CUresult (*EncodeFn)(CUtensorMap*, CUtensorMapDataType, cuuint32_t, void*, const cuuint64_t*, const cuuint64_t*, const cuuint32_t*,
                             const cuuint32_t*, CUtensorMapInterleave, CUtensorMapSwizzle, CUtensorMapL2promotion, CUtensorMapFloatOOBfill);

void make_map(EncodeFn enc, CUtensorMap* m, const void* ptr, uint64_t cols, uint64_t rows, uint32_t bc, uint32_t br, CUtensorMapSwizzle swz) {
  const cuuint64_t dims[2] = {cols, rows}, strides[1] = {cols * 2};
  const cuuint32_t box[2] = {bc, br}, es[2] = {1, 1};
  enc(m, CU_TENSOR_MAP_DATA_TYPE_BFLOAT16, 2, const_cast<void*>(ptr), dims, strides, box, es, CU_TENSOR_MAP_INTERLEAVE_NONE, swz,
      CU_TENSOR_MAP_L2_PROMOTION_L2_128B, CU_TENSOR_MAP_FLOAT_OOB_FILL_NONE);
}

}

extern "C" void kernel_launch(void* const* d_in, const int* in_sizes, int n_in, void* d_out, int out_size) {
  (void)in_sizes; (void)n_in; (void)out_size;
  void* fn = nullptr;
  cudaDriverEntryPointQueryResult qr;
  cudaGetDriverEntryPoint("cuTensorMapEncodeTiled", &fn, cudaEnableDefault, &qr);
  EncodeFn enc = (EncodeFn)fn;
  void* o_ptr = nullptr;
  cudaGetSymbolAddress(&o_ptr, g_o);
  CUtensorMap mx, mw, mwo, mo, mout, mxr, mg, mu, md;
  make_map(enc, &mx, d_in[0], kD, kS, 64, 128, CU_TENSOR_MAP_SWIZZLE_128B);
  make_map(enc, &mxr, d_in[0], kD, kS, 256, 16, CU_TENSOR_MAP_SWIZZLE_NONE);
  make_map(enc, &mw, d_in[1], 3 * kD, kD, 64, 64, CU_TENSOR_MAP_SWIZZLE_128B);
  make_map(enc, &mwo, d_in[3], kD, kD, 64, 64, CU_TENSOR_MAP_SWIZZLE_128B);
  make_map(enc, &mo, o_ptr, kD, kS, 64, 64, CU_TENSOR_MAP_SWIZZLE_128B);
  make_map(enc, &mout, d_out, kD, kS, 64, 16, CU_TENSOR_MAP_SWIZZLE_128B);
  make_map(enc, &mg, d_in[6], kF, kD, 64, 64, CU_TENSOR_MAP_SWIZZLE_128B);
  make_map(enc, &mu, d_in[7], kF, kD, 64, 64, CU_TENSOR_MAP_SWIZZLE_128B);
  {
    const cuuint64_t dims[3] = {64, kF, 16}, strides[2] = {kD * 2, 128};
    const cuuint32_t box[3] = {64, 16, 4}, es[3] = {1, 1, 1};
    enc(&md, CU_TENSOR_MAP_DATA_TYPE_BFLOAT16, 3, d_in[8], dims, strides, box, es, CU_TENSOR_MAP_INTERLEAVE_NONE, CU_TENSOR_MAP_SWIZZLE_128B,
        CU_TENSOR_MAP_L2_PROMOTION_L2_128B, CU_TENSOR_MAP_FLOAT_OOB_FILL_NONE);
  }
  Params P;
  P.x = (const __nv_bfloat16*)d_in[0];
  P.w = (const __nv_bfloat16*)d_in[1];
  P.o = (__nv_bfloat16*)o_ptr;
  P.w_phi = (const __nv_bfloat16*)d_in[2];
  P.w_r = (const __nv_bfloat16*)d_in[5];
  P.gate_w = (const __nv_bfloat16*)d_in[9];
  P.da = make_desc(sb, 16, 1024, 1);
  P.db = make_desc(sb + 16384, 8192, 1024, 1);
  P.dw = make_desc(sb + SM_WPHI, 16, 512, 2);
  P.dphi = make_desc(sb + SM_PHI, 16, 1024, 1);
  P.dv = make_desc(sb + SM_V, SM_Z - SM_V, 512, 2);
  P.dband = make_desc(sb + SM_BAND, 128, 128, 0);
  P.dxs = make_desc(sb + SM_BAND, 16, 128, 0);
  int dev = 0, sms = 0;
  cudaGetDevice(&dev);
  cudaDeviceGetAttribute(&sms, cudaDevAttrMultiProcessorCount, dev);
  auto kern = sms == 132 ? fused_kernel<true> : fused_kernel<false>;
  cudaFuncSetAttribute(kern, cudaFuncAttributeMaxDynamicSharedMemorySize, SM_ALLOC);
  kern<<<132, 512, SM_ALLOC, cudaStreamPerThread>>>(mx, mw, mwo, mo, mout, mxr, mg, mu, md, P);
}
```

```cpp
#include <cuda_runtime.h>
#include <cuda_bf16.h>
#include <cuda.h>
#include <stdint.h>

namespace {

template<int TA, int TB> __device__ __forceinline__ void wgmma_m64n128k16_ss(float (&d)[64], uint64_t da, uint64_t db, int scale_d) {
  asm volatile("{\n.reg .pred p;\nsetp.ne.b32 p, %66, 0;\n"
    "wgmma.mma_async.sync.aligned.m64n128k16.f32.bf16.bf16 "
    "{%0, %1, %2, %3, %4, %5, %6, %7, %8, %9, %10, %11, %12, %13, %14, %15, "
    "%16, %17, %18, %19, %20, %21, %22, %23, %24, %25, %26, %27, %28, %29, %30, %31, "
    "%32, %33, %34, %35, %36, %37, %38, %39, %40, %41, %42, %43, %44, %45, %46, %47, "
    "%48, %49, %50, %51, %52, %53, %54, %55, %56, %57, %58, %59, %60, %61, %62, %63}, "
    "%64, %65, p, 1, 1, %67, %68;\n}\n"
    : "+f"(d[0]), "+f"(d[1]), "+f"(d[2]), "+f"(d[3]), "+f"(d[4]), "+f"(d[5]), "+f"(d[6]), "+f"(d[7]),
      "+f"(d[8]), "+f"(d[9]), "+f"(d[10]), "+f"(d[11]), "+f"(d[12]), "+f"(d[13]), "+f"(d[14]), "+f"(d[15]),
      "+f"(d[16]), "+f"(d[17]), "+f"(d[18]), "+f"(d[19]), "+f"(d[20]), "+f"(d[21]), "+f"(d[22]), "+f"(d[23]),
      "+f"(d[24]), "+f"(d[25]), "+f"(d[26]), "+f"(d[27]), "+f"(d[28]), "+f"(d[29]), "+f"(d[30]), "+f"(d[31]),
      "+f"(d[32]), "+f"(d[33]), "+f"(d[34]), "+f"(d[35]), "+f"(d[36]), "+f"(d[37]), "+f"(d[38]), "+f"(d[39]),
      "+f"(d[40]), "+f"(d[41]), "+f"(d[42]), "+f"(d[43]), "+f"(d[44]), "+f"(d[45]), "+f"(d[46]), "+f"(d[47]),
      "+f"(d[48]), "+f"(d[49]), "+f"(d[50]), "+f"(d[51]), "+f"(d[52]), "+f"(d[53]), "+f"(d[54]), "+f"(d[55]),
      "+f"(d[56]), "+f"(d[57]), "+f"(d[58]), "+f"(d[59]), "+f"(d[60]), "+f"(d[61]), "+f"(d[62]), "+f"(d[63])
    : "l"(da), "l"(db), "r"(scale_d), "n"(TA), "n"(TB));
}

template<int TB> __device__ __forceinline__ void wgmma_m64n32k16_rs(float (&d)[16], const uint32_t (&a)[4], uint64_t db, int scale_d) {
  asm volatile("{\n.reg .pred p;\nsetp.ne.b32 p, %21, 0;\n"
    "wgmma.mma_async.sync.aligned.m64n32k16.f32.bf16.bf16 "
    "{%0, %1, %2, %3, %4, %5, %6, %7, %8, %9, %10, %11, %12, %13, %14, %15}, "
    "{%16, %17, %18, %19}, %20, p, 1, 1, %22;\n}\n"
    : "+f"(d[0]), "+f"(d[1]), "+f"(d[2]), "+f"(d[3]), "+f"(d[4]), "+f"(d[5]), "+f"(d[6]), "+f"(d[7]),
      "+f"(d[8]), "+f"(d[9]), "+f"(d[10]), "+f"(d[11]), "+f"(d[12]), "+f"(d[13]), "+f"(d[14]), "+f"(d[15])
    : "r"(a[0]), "r"(a[1]), "r"(a[2]), "r"(a[3]), "l"(db), "r"(scale_d), "n"(TB));
}

template<int TA, int TB> __device__ __forceinline__ void wgmma_m64n40k16_ss(float (&d)[20], uint64_t da, uint64_t db, int scale_d) {
  asm volatile("{\n.reg .pred p;\nsetp.ne.b32 p, %22, 0;\n"
    "wgmma.mma_async.sync.aligned.m64n40k16.f32.bf16.bf16 "
    "{%0, %1, %2, %3, %4, %5, %6, %7, %8, %9, %10, %11, %12, %13, %14, %15, "
    "%16, %17, %18, %19}, "
    "%20, %21, p, 1, 1, %23, %24;\n}\n"
    : "+f"(d[0]), "+f"(d[1]), "+f"(d[2]), "+f"(d[3]), "+f"(d[4]), "+f"(d[5]), "+f"(d[6]), "+f"(d[7]),
      "+f"(d[8]), "+f"(d[9]), "+f"(d[10]), "+f"(d[11]), "+f"(d[12]), "+f"(d[13]), "+f"(d[14]), "+f"(d[15]),
      "+f"(d[16]), "+f"(d[17]), "+f"(d[18]), "+f"(d[19])
    : "l"(da), "l"(db), "r"(scale_d), "n"(TA), "n"(TB));
}

template<int TB> __device__ __forceinline__ void wgmma_m64n40k16_rs(float (&d)[20], const uint32_t (&a)[4], uint64_t db, int scale_d) {
  asm volatile("{\n.reg .pred p;\nsetp.ne.b32 p, %25, 0;\n"
    "wgmma.mma_async.sync.aligned.m64n40k16.f32.bf16.bf16 "
    "{%0, %1, %2, %3, %4, %5, %6, %7, %8, %9, %10, %11, %12, %13, %14, %15, "
    "%16, %17, %18, %19}, "
    "{%20, %21, %22, %23}, %24, p, 1, 1, %26;\n}\n"
    : "+f"(d[0]), "+f"(d[1]), "+f"(d[2]), "+f"(d[3]), "+f"(d[4]), "+f"(d[5]), "+f"(d[6]), "+f"(d[7]),
      "+f"(d[8]), "+f"(d[9]), "+f"(d[10]), "+f"(d[11]), "+f"(d[12]), "+f"(d[13]), "+f"(d[14]), "+f"(d[15]),
      "+f"(d[16]), "+f"(d[17]), "+f"(d[18]), "+f"(d[19])
    : "r"(a[0]), "r"(a[1]), "r"(a[2]), "r"(a[3]), "l"(db), "r"(scale_d), "n"(TB));
}

template<int TA, int TB> __device__ __forceinline__ void wgmma_m64n8k16_ss(float (&d)[4], uint64_t da, uint64_t db, int scale_d) {
  asm volatile("{\n.reg .pred p;\nsetp.ne.b32 p, %6, 0;\n"
    "wgmma.mma_async.sync.aligned.m64n8k16.f32.bf16.bf16 "
    "{%0, %1, %2, %3}, "
    "%4, %5, p, 1, 1, %7, %8;\n}\n"
    : "+f"(d[0]), "+f"(d[1]), "+f"(d[2]), "+f"(d[3])
    : "l"(da), "l"(db), "r"(scale_d), "n"(TA), "n"(TB));
}

constexpr int kS = 2048, kD = 1024, kF = 3584;
constexpr int NST = 5, STAGE = 32768;
constexpr uint32_t sb = 1024;
constexpr int SM_V    = NST * STAGE;
constexpr int SM_Z    = SM_V + 16384;
constexpr int SM_PHI  = SM_Z + 4096;
constexpr int SM_MOE  = SM_PHI + 16384;
constexpr int SM_WPHI = SM_MOE + 16384;
constexpr int SM_BAND = SM_WPHI + 8192;
constexpr int SM_G    = SM_BAND + 2176;
constexpr int SM_BAR  = SM_G + 512;
constexpr int SM_MISC = SM_BAR + 448;
constexpr int SM_TOTAL = SM_MISC + 64;
static_assert(SM_TOTAL <= 232448, "smem");
constexpr uint32_t bars = sb + SM_BAR;
constexpr int B_FX = 0  , B_FY = 5  , B_XT = 15, B_EPOCH = 16, B_RX = 17  , B_MF = 21  , B_RD = 24  , B_KV = 26  , B_M2 = 28, B_P1 = 29;
constexpr int B_WPHI = 30, B_INFO = 31, B_QS = 32, B_XP = 33, B_RED = 34  , B_PUB = 36  , B_ME = 40  , B_MD = 43, B_T3 = 44;
constexpr int B_EM = 45  , B_NUM = 50;
constexpr int C_START = 0, C_O = 1, C_KV = C_O + 64;

__device__ uint2 g_gate[kS];
__device__ uint2 g_key[128];
__device__ uint2 g_pre[4 * kF];
__device__ uint2 g_yp[32 * kD];
__device__ __align__(128) uint32_t g_kvr[16 * 2560];
__device__ __align__(128) uint32_t g_cnt[(C_KV + 32) * 32];
__device__ __align__(1024) __nv_bfloat16 g_o[kS * kD];
#define KS(id)
#define RG(id)
#define TS(id)
#define TSG(id)
constexpr int SM_ALLOC = SM_TOTAL;

#define POLL0 500
#define POLL1 150
#define RSTEP 1
#define POLLR 400
#define EARLY_N 2
#define EARLY_GAP 200
#define POLLF 50
#define RED_CH 10
#define RED_GAP0 250
#define RED_GAP1 0
#define YIELD_EXP 1
#define END_SKEW 4
#define XT_GATE B_T3
#define FIN_YIELD 0
#define MLEAD 0
#define MPACE 0
#define REPF 1
#define RED_ROT 0
#define RED_CH1 10
#define WLEAD 11
#define MGAP 300

struct Params {
  const __nv_bfloat16 *x, *w, *w_phi, *w_r, *gate_w;
  __nv_bfloat16* o;
  uint64_t da, db, dw, dphi, dv, dband, dxs;
};

__device__ __forceinline__ uint32_t smem_u32(const void* p) { return (uint32_t)__cvta_generic_to_shared(p); }
__device__ __forceinline__ void mbar_init(uint32_t bar, uint32_t cnt) { asm volatile("mbarrier.init.shared::cta.b64 [%0], %1;" :: "r"(bar), "r"(cnt) : "memory"); }
__device__ __forceinline__ void mbar_expect_tx(uint32_t bar, uint32_t bytes) { asm volatile("mbarrier.arrive.expect_tx.shared::cta.b64 _, [%0], %1;" :: "r"(bar), "r"(bytes) : "memory"); }
__device__ __forceinline__ void mbar_arrive(uint32_t bar) { asm volatile("mbarrier.arrive.shared::cta.b64 _, [%0];" :: "r"(bar) : "memory"); }
__device__ __forceinline__ void mbar_arrive_n(uint32_t bar, uint32_t n) { asm volatile("mbarrier.arrive.shared::cta.b64 _, [%0], %1;" :: "r"(bar), "r"(n) : "memory"); }
constexpr int BUDGET = 1 << 20;
__device__ __forceinline__ void mbar_wait(uint32_t bar, uint32_t parity, int& budget) {
  asm volatile("{\n.reg .pred p;\n"
               "WAIT_L:\nmbarrier.try_wait.parity.shared::cta.b64 p, [%1], %2;\n@p bra WAIT_D;\n"
               "add.s32 %0, %0, -1;\nsetp.gt.s32 p, %0, 0;\n@p bra WAIT_L;\nWAIT_D:\n}"
               : "+r"(budget) : "r"(bar), "r"(parity) : "memory");
}
template <int SLEEP>
__device__ __forceinline__ void wait_count(const uint32_t* p, uint32_t target, int& budget) {
  asm volatile("{\n.reg .pred p;\n.reg .s32 v;\n"
               "WAIT_L:\nld.acquire.gpu.global.s32 v, [%1];\nsub.s32 v, v, %2;\nsetp.ge.s32 p, v, 0;\n@p bra WAIT_D;\n"
               "nanosleep.u32 %3;\nadd.s32 %0, %0, -4;\nsetp.gt.s32 p, %0, 0;\n@p bra WAIT_L;\nWAIT_D:\n}"
               : "+r"(budget) : "l"(p), "r"(target), "n"(SLEEP) : "memory");
}
__device__ __forceinline__ void tma_load(uint32_t dst, const CUtensorMap* m, uint32_t bar, int c0, int c1) {
  asm volatile("cp.async.bulk.tensor.2d.shared::cluster.global.mbarrier::complete_tx::bytes [%0], [%1, {%3, %4}], [%2];"
    :: "r"(dst), "l"(m), "r"(bar), "r"(c0), "r"(c1) : "memory");
}
__device__ __forceinline__ void tma_load3(uint32_t dst, const CUtensorMap* m, uint32_t bar, int c1, int c2) {
  asm volatile("cp.async.bulk.tensor.3d.shared::cluster.global.mbarrier::complete_tx::bytes [%0], [%1, {%5, %3, %4}], [%2];"
    :: "r"(dst), "l"(m), "r"(bar), "r"(c1), "r"(c2), "r"(0) : "memory");
}
__device__ __forceinline__ void tma_prefetch3(const CUtensorMap* m, int c1, int c2) {
  asm volatile("cp.async.bulk.prefetch.tensor.3d.L2.global [%0, {%3, %1, %2}];" :: "l"(m), "r"(c1), "r"(c2), "r"(0) : "memory");
}
__device__ __forceinline__ void tma_prefetch(const CUtensorMap* m, int c0, int c1) {
  asm volatile("cp.async.bulk.prefetch.tensor.2d.L2.global [%0, {%1, %2}];" :: "l"(m), "r"(c0), "r"(c1) : "memory");
}
__device__ __forceinline__ void tma_store(const CUtensorMap* m, uint32_t src, int c0, int c1) {
  asm volatile("cp.async.bulk.tensor.2d.global.shared::cta.bulk_group [%0, {%2, %3}], [%1];" :: "l"(m), "r"(src), "r"(c0), "r"(c1) : "memory");
}
__device__ __forceinline__ void bulk_load(uint32_t dst, const void* src, uint32_t bytes, uint32_t bar) {
  asm volatile("cp.async.bulk.shared::cluster.global.mbarrier::complete_tx::bytes [%0], [%1], %2, [%3];" :: "r"(dst), "l"(src), "r"(bytes), "r"(bar) : "memory");
}
__device__ __forceinline__ void bulk_reduce(void* dst, uint32_t src, uint32_t bytes) {
  asm volatile("cp.reduce.async.bulk.global.shared::cta.bulk_group.add.noftz.bf16 [%0], [%1], %2;" :: "l"(dst), "r"(src), "r"(bytes) : "memory");
}
__device__ __forceinline__ void prefetch_map(const CUtensorMap* m) { asm volatile("prefetch.tensormap [%0];" :: "l"(m) : "memory"); }
__device__ __forceinline__ bool elect_one() {
  uint32_t p;
  asm volatile("{\n.reg .pred P;\nelect.sync _|P, 0xffffffff;\nselp.u32 %0, 1, 0, P;\n}" : "=r"(p));
  return p;
}
__device__ __forceinline__ void wg_fence() { asm volatile("wgmma.fence.sync.aligned;" ::: "memory"); }
__device__ __forceinline__ void wg_commit() { asm volatile("wgmma.commit_group.sync.aligned;" ::: "memory"); }
template <int N> __device__ __forceinline__ void wg_wait() { asm volatile("wgmma.wait_group.sync.aligned %0;" :: "n"(N) : "memory"); }
template <int N> __device__ __forceinline__ void zero(float (&r)[N]) {
#pragma unroll
  for (int i = 0; i < N; i++) r[i] = 0.f;
}
template <int N> __device__ __forceinline__ void pin(float (&r)[N]) {
#pragma unroll
  for (int i = 0; i < N; i++) asm volatile("" : "+f"(r[i]) :: "memory");
}
template <int N> __device__ __forceinline__ void pinr(uint32_t (&r)[N][4]) {
#pragma unroll
  for (int i = 0; i < N; i++) asm volatile("" : "+r"(r[i][0]), "+r"(r[i][1]), "+r"(r[i][2]), "+r"(r[i][3]) :: "memory");
}
__device__ __forceinline__ void fence_async_smem() { asm volatile("fence.proxy.async.shared::cta;" ::: "memory"); }
__device__ __forceinline__ void fence_async_global() { asm volatile("fence.proxy.async.global;" ::: "memory"); }
__device__ __forceinline__ void bar_sync(int id, int n) { asm volatile("bar.sync %0, %1;" :: "r"(id), "r"(n) : "memory"); }
__device__ __forceinline__ void bar_arrive(int id, int n) { asm volatile("bar.arrive %0, %1;" :: "r"(id), "r"(n) : "memory"); }
__device__ __forceinline__ void warp_arrive(uint32_t bar, int lane) { __syncwarp(); if (lane == 0) mbar_arrive(bar); }
__host__ __device__ constexpr uint64_t make_desc(uint32_t addr, uint32_t lbo, uint32_t sbo, uint32_t swz) {
  return (uint64_t)((addr & 0x3FFFF) >> 4) | ((uint64_t)((lbo & 0x3FFFF) >> 4) << 16) | ((uint64_t)(sbo >> 4) << 32) | ((uint64_t)swz << 62);
}
__device__ __forceinline__ uint32_t pack2(float lo, float hi) {
  uint32_t r; asm("cvt.rn.bf16x2.f32 %0, %1, %2;" : "=r"(r) : "f"(hi), "f"(lo)); return r;
}
__device__ __forceinline__ float bf_lo(uint32_t v) { return __uint_as_float(v << 16); }
__device__ __forceinline__ float bf_hi(uint32_t v) { return __uint_as_float(v & 0xffff0000u); }
__device__ __forceinline__ float ex2(float x) { float r; asm("ex2.approx.ftz.f32 %0, %1;" : "=f"(r) : "f"(x)); return r; }
__device__ __forceinline__ float rcp(float x) { float r; asm("rcp.approx.ftz.f32 %0, %1;" : "=f"(r) : "f"(x)); return r; }
constexpr float LOG2E = 1.4426950408889634f;
__device__ __forceinline__ float sigmoidf(float x) { return rcp(1.0f + ex2(-LOG2E * x)); }
__device__ __forceinline__ void sts128(uint32_t a, uint32_t x, uint32_t y, uint32_t z, uint32_t w) {
  asm volatile("st.shared.v4.u32 [%0], {%1,%2,%3,%4};" :: "r"(a), "r"(x), "r"(y), "r"(z), "r"(w) : "memory");
}
__device__ __forceinline__ void lds128(uint32_t a, uint32_t (&r)[4]) {
  asm volatile("ld.shared.v4.u32 {%0,%1,%2,%3}, [%4];" : "=r"(r[0]), "=r"(r[1]), "=r"(r[2]), "=r"(r[3]) : "r"(a) : "memory");
}
__device__ __forceinline__ void sts32(uint32_t a, uint32_t v) { asm volatile("st.shared.u32 [%0], %1;" :: "r"(a), "r"(v) : "memory"); }
__device__ __forceinline__ uint32_t lds32(uint32_t a) { uint32_t v; asm volatile("ld.shared.u32 %0, [%1];" : "=r"(v) : "r"(a) : "memory"); return v; }
__device__ __forceinline__ float ldsf(uint32_t a) { return __uint_as_float(lds32(a)); }
__device__ __forceinline__ void stmatrix4(uint32_t a, uint32_t r0, uint32_t r1, uint32_t r2, uint32_t r3) {
  asm volatile("stmatrix.sync.aligned.m8n8.x4.shared.b16 [%0], {%1,%2,%3,%4};" :: "r"(a), "r"(r0), "r"(r1), "r"(r2), "r"(r3) : "memory");
}
__device__ __forceinline__ void ldmatrix4(uint32_t a, uint32_t (&r)[4]) {
  asm volatile("ldmatrix.sync.aligned.m8n8.x4.shared.b16 {%0,%1,%2,%3}, [%4];" : "=r"(r[0]), "=r"(r[1]), "=r"(r[2]), "=r"(r[3]) : "r"(a) : "memory");
}
__device__ __forceinline__ uint4 ldg_nc(const void* p) {
  uint4 v; asm volatile("ld.global.nc.L1::no_allocate.v4.u32 {%0,%1,%2,%3}, [%4];" : "=r"(v.x), "=r"(v.y), "=r"(v.z), "=r"(v.w) : "l"(p)); return v;
}
__device__ __forceinline__ void st_tagged(uint2* p, uint32_t v, uint32_t tag) {
  asm volatile("{\n.reg .b64 x;\nmov.b64 x, {%1, %2};\nst.relaxed.gpu.global.b64 [%0], x;\n}" :: "l"(p), "r"(v), "r"(tag) : "memory");
}
__device__ __forceinline__ uint2 ld_tagged(const uint2* p) {
  uint2 v; asm volatile("{\n.reg .b64 x;\nld.relaxed.gpu.global.b64 x, [%2];\nmov.b64 {%0, %1}, x;\n}" : "=r"(v.x), "=r"(v.y) : "l"(p) : "memory"); return v;
}
__device__ __forceinline__ void probe(const uint2* p, uint32_t tag, int& budget) {
  do { __nanosleep(POLL0); budget -= 16; } while (!__all_sync(0xffffffffu, ld_tagged(p).y == tag) && budget > 0);
}
template <int STRIDE, int N>
__device__ __forceinline__ void gather(const uint2* p, uint32_t tag, float& s0, float& s1, int& budget) {
  uint32_t pause = 0;
  bool again;
#pragma unroll 1
  do {
    __nanosleep(pause);
    pause = POLL0;
    uint32_t bad = 0;
    s0 = s1 = 0.f;
#pragma unroll
    for (int i = 0; i < N; i++) {
      const uint2 w = ld_tagged(p + i * STRIDE);
      bad |= w.y ^ tag;
      if (i < N / 2) s0 += __uint_as_float(w.x); else s1 += __uint_as_float(w.x);
    }
    budget -= 16;
    again = __any_sync(0xffffffffu, bad != 0) && budget > 0;
  } while (again);
}
__device__ __forceinline__ void sts16(uint32_t a, uint32_t v) { asm volatile("st.shared.u16 [%0], %1;" :: "r"(a), "h"((uint16_t)v) : "memory"); }
__device__ __forceinline__ void signal_add(uint32_t* p, uint32_t v) { asm volatile("red.release.gpu.global.add.u32 [%0], %1;" :: "l"(p), "r"(v) : "memory"); }
__device__ __forceinline__ float qmax(float v) { v = fmaxf(v, __shfl_xor_sync(0xffffffffu, v, 1)); return fmaxf(v, __shfl_xor_sync(0xffffffffu, v, 2)); }
__device__ __forceinline__ float qsum(float v) { v += __shfl_xor_sync(0xffffffffu, v, 1); return v + __shfl_xor_sync(0xffffffffu, v, 2); }
__device__ __forceinline__ float fold(float a, float b, bool hi, int m) { return (hi ? b : a) + __shfl_xor_sync(0xffffffffu, hi ? a : b, m); }

__device__ __forceinline__ void yield_slot() { asm volatile("pmevent 0;" ::: "memory"); }
__device__ __forceinline__ float fma_v(float a, float b, float c) { float r; asm volatile("fma.rn.f32 %0, %1, %2, %3;" : "=f"(r) : "f"(a), "f"(b), "f"(c)); return r; }
constexpr float EXP_LIM_F = 36028797018963968.0f;
constexpr uint32_t EXP_TOP = 0x58805880u;
__device__ __forceinline__ void exp_plain(const float (&p)[16], float (&ep)[16], float (&em)[16]) {
#pragma unroll
  for (int i = 0; i < 16; i++) { ep[i] = ex2(p[i]); em[i] = ex2(-p[i]); }
}
__device__ __forceinline__ void exp_shifted(const float (&p)[16], float sgn, float (&e)[16]) {
#pragma unroll
  for (int i = 0; i < 16; i++) e[i] = sgn * p[i];
#pragma unroll
  for (int o = 0; o < 4; o += 2) {
    const float mx = qmax(fmaxf(fmaxf(fmaxf(e[o], e[o + 1]), fmaxf(e[o + 4], e[o + 5])), fmaxf(fmaxf(e[o + 8], e[o + 9]), fmaxf(e[o + 12], e[o + 13]))));
#pragma unroll
    for (int c = 0; c < 4; c++) { e[4 * c + o] = ex2(e[4 * c + o] - mx); e[4 * c + o + 1] = ex2(e[4 * c + o + 1] - mx); }
  }
}
__device__ __forceinline__ void pack_sums(const float (&e)[16], uint32_t (&pk)[2][4], float (&s)[2]) {
#pragma unroll
  for (int i = 0; i < 8; i++) pk[i >> 2][i & 3] = pack2(e[2 * i], e[2 * i + 1]);
#pragma unroll
  for (int o = 0; o < 4; o += 2) s[o >> 1] = ((e[o] + e[o + 1]) + (e[o + 4] + e[o + 5])) + ((e[o + 8] + e[o + 9]) + (e[o + 12] + e[o + 13]));
}
__device__ __forceinline__ uint32_t rcp2(float s) { const float r = rcp(s); return pack2(r, r); }
__device__ __forceinline__ uint32_t mul2(uint32_t a, uint32_t b) { uint32_t r; asm("mul.rn.bf16x2 %0, %1, %2;" : "=r"(r) : "r"(a), "r"(b)); return r; }
__device__ __forceinline__ void store_phi(uint32_t a, const uint32_t (&pk)[2][4], uint32_t r0, uint32_t r1) {
#pragma unroll
  for (int h = 0; h < 2; h++) stmatrix4(a ^ (h * 32), mul2(pk[h][0], r0), mul2(pk[h][1], r1), mul2(pk[h][2], r0), mul2(pk[h][3], r1));
}
__device__ __forceinline__ uint32_t exp_frags(const float (&p)[16], uint32_t (&ef)[4][4], uint32_t top) {
  float ep[16], em[16];
  exp_plain(p, ep, em);
#pragma unroll
  for (int s = 0; s < 2; s++)
#pragma unroll
    for (int r = 0; r < 4; r++) {
      ef[s][r] = pack2(ep[8 * s + 2 * r], ep[8 * s + 2 * r + 1]);
      ef[2 + s][r] = pack2(em[8 * s + 2 * r], em[8 * s + 2 * r + 1]);
    }
#pragma unroll
  for (int s = 0; s < 4; s++) top = __vimax3_u16x2(__vimax3_u16x2(top, ef[s][0], ef[s][1]), ef[s][2], ef[s][3]);
  return top;
}
__device__ __forceinline__ void issue_pq(float (&p)[4][16], const uint32_t (&qf)[4][2][4], uint64_t dw, int accumulate) {
  wg_fence();
#pragma unroll
  for (int h = 0; h < 4; h++) {
    wgmma_m64n32k16_rs<1>(p[h], qf[h][0], dw + h * 128, accumulate);
    wgmma_m64n32k16_rs<1>(p[h], qf[h][1], dw + h * 128 + 64, 1);
  }
  wg_commit();
}

#define SPLIT_BATCH 2
__device__ __forceinline__ void mainloop128(float (&acc)[2][64], uint64_t da0, uint64_t db0, uint32_t slot, uint32_t ph, int steps, bool lane0, int& budget, int cta, int n0) {
  uint32_t prev = 0;
#pragma unroll 1
  for (int k = 0; k < steps; k++) {
    mbar_wait(bars + B_FX * 8 + slot * 8, ph, budget);
    const uint64_t da = da0 + slot * (STAGE >> 4), db = db0 + slot * (STAGE >> 4);
#pragma unroll
    for (int kk = 0; kk < 4; kk++) {
      if (SPLIT_BATCH == 2 || !(kk & 1)) {
        wg_wait<1>();
        if (kk == 3 - SPLIT_BATCH && k > 0 && lane0) mbar_arrive_n(bars + B_EM * 8 + prev * 8, 2);
        wg_fence();
      }
      wgmma_m64n128k16_ss<0, 1>(acc[0], da + kk * 2, db + kk * 128, kk ? 1 : k);
      wgmma_m64n128k16_ss<0, 1>(acc[1], da + 512 + kk * 2, db + kk * 128, kk ? 1 : k);
      if (SPLIT_BATCH == 2 || (kk & 1)) wg_commit();
    }
    prev = slot;
    if (++slot == NST) { slot = 0; ph ^= 1; }
  }
}
__device__ __forceinline__ void kstep64(float (&acc)[64], uint64_t da, uint64_t db, int accumulate) {
  wg_fence();
#pragma unroll
  for (int kk = 0; kk < 4; kk++) wgmma_m64n128k16_ss<0, 1>(acc, da + kk * 2, db + kk * 128, kk ? 1 : accumulate);
  wg_commit();
}
__device__ __forceinline__ void issue_kv(float (&kv)[20], uint64_t dphi, uint64_t dv, int accumulate) {
  wg_fence();
#pragma unroll
  for (int ks = 0; ks < 4; ks++)
    wgmma_m64n40k16_ss<1, 1>(kv, dphi + ks * 128, dv - (uint64_t)ks * ((64ull << 16) - 64ull), ks ? 1 : accumulate);
  wg_commit();
}
__device__ __forceinline__ void load_x(uint32_t sx, uint32_t (&xf)[8][4]) {
#pragma unroll
  for (int u = 0; u < 8; u++) ldmatrix4((sx ^ ((u & 3) * 32)) + (u >> 2) * 16384, xf[u]);
}
__device__ __forceinline__ uint32_t moe_buf(uint32_t b) { return b == 2 ? SM_V + 8192 : SM_MOE + b * 8192; }
template <bool DOWN>
__device__ __forceinline__ void moe_chunks(float (&a)[4], int n, uint32_t& buf, uint32_t& ph, uint64_t da0, uint64_t db, bool lane0) {
  int budget = BUDGET;
  zero(a);
#pragma unroll 1
  for (int c = 0; c < n; c++) {
    mbar_wait(bars + B_MF * 8 + buf * 8, ph, budget);
    const uint64_t da = da0 + (moe_buf(buf) >> 4);
    wg_fence();
#pragma unroll
    for (int j = 0; j < 4; j++) wgmma_m64n8k16_ss<1, 0>(a, da + j * 128, DOWN ? db - j : db + j * 2, 1);
    wg_commit();
    wg_wait<0>();
    if (lane0) mbar_arrive(bars + B_ME * 8 + buf * 8);
    db += DOWN ? 16 : 8;
    if (++buf >= (DOWN ? 2 : 3)) { buf = 0; ph ^= 1; }
  }
  pin(a);
}
constexpr uint64_t DV_TILE = 4 * ((64ull << 16) - 64ull);

template <bool BY_SM>
__global__ void __launch_bounds__(512, 1)
fused_kernel(const __grid_constant__ CUtensorMap mx, const __grid_constant__ CUtensorMap mw, const __grid_constant__ CUtensorMap mwo,
             const __grid_constant__ CUtensorMap mo, const __grid_constant__ CUtensorMap mout, const __grid_constant__ CUtensorMap mxr,
             const __grid_constant__ CUtensorMap mg, const __grid_constant__ CUtensorMap mu, const __grid_constant__ CUtensorMap md, const Params P) {
  extern __shared__ __align__(1024) uint8_t smem_raw[];
  if (smem_u32(smem_raw) != sb) return;
  const int tid = threadIdx.x, lane = tid & 31;
  if (tid == 256) TS(1);
  const int warp = __shfl_sync(0xffffffffu, tid >> 5, 0), wg = warp >> 2;
  int budget = BUDGET;
  if (warp == 10 && elect_one()) { prefetch_map(&mx); prefetch_map(&mw); }
  int cta;
  {
    uint32_t smid;
    asm volatile("mov.u32 %0, %%smid;" : "=r"(smid));
    if (!BY_SM) cta = blockIdx.x;
    else if (smid < 64) cta = ((smid >> 1) & 7) * 16 + (smid >> 4) * 2 + (smid & 1);
    else if (smid < 120) { const int t = (smid - 64) >> 1, d = (t * 37) >> 8; cta = (1 + t - d * 7) * 16 + 8 + d * 2 + (smid & 1); }
    else cta = smid < 124 ? smid + 8 : smid - 116;
  }
  if (cta >= 128) {
    if (tid == 0) {
      const uint32_t old = atomicAdd(&g_cnt[C_START], 32u);
      wait_count<500>(&g_cnt[C_START], (old & ~255u) + 256u, budget);
    }
    return;
  }
  const int bi = (cta >> 5) * 4 + ((cta >> 2) & 3);
  const int bj = ((cta >> 4) & 1) * 4 + (cta & 3);

  if (wg == 3) {
    asm volatile("setmaxnreg.dec.sync.aligned.u32 64;");
    const int t3 = tid - 384, w3 = warp - 12;
    if (t3 == 0) TSG(0);
    if (t3 < 80) *reinterpret_cast<uint4*>(&g_kvr[cta * 320 + t3 * 4]) = make_uint4(0, 0, 0, 0);
    if (t3 < 17) st_tagged(t3 < 16 ? &g_gate[bi * 128 + bj * 16 + t3] : &g_key[cta], 0, 1);
    bar_sync(0, 512);
#pragma unroll 1
    for (int u = 0; u < 4; u++) {
      const uint4 v = ldg_nc(P.w_phi + bj * 4096 + (u * 128 + t3) * 8);
      sts128(sb + SM_WPHI + u * 2048 + (t3 >> 2) * 64 + (((t3 & 3) ^ ((t3 >> 3) & 3)) << 4),
             pack2(LOG2E * bf_lo(v.x), LOG2E * bf_hi(v.x)), pack2(LOG2E * bf_lo(v.y), LOG2E * bf_hi(v.y)),
             pack2(LOG2E * bf_lo(v.z), LOG2E * bf_hi(v.z)), pack2(LOG2E * bf_lo(v.w), LOG2E * bf_hi(v.w)));
    }
    fence_async_smem();
    warp_arrive(bars + B_WPHI * 8, lane);
    bar_sync(6, 256);
    const uint32_t target = lds32(sb + SM_MISC);
    uint32_t key;
    {
      uint32_t kk[4];
      lds128(sb + SM_MISC + 16, kk);
      if (t3 == 0) st_tagged(&g_key[cta], max(max(kk[0], kk[1]), max(kk[2], kk[3])), target);
      uint2 k, gv;
      __nanosleep(POLLR);
      do {
        __nanosleep(POLL1);
        k = ld_tagged(&g_key[t3]);
        gv = ld_tagged(&g_gate[bi * 128 + t3]);
        budget -= 4;
      } while (!__all_sync(0xffffffffu, k.y == target && gv.y == target) && budget > 0);
      key = __reduce_max_sync(0xffffffffu, k.x);
      if (lane == 0) sts32(sb + SM_MISC + 32 + w3 * 4, key);
      sts32(sb + SM_G + t3 * 4, gv.x);
      bar_sync(5, 128);
      lds128(sb + SM_MISC + 32, kk);
      key = max(max(kk[0], kk[1]), max(kk[2], kk[3]));
    }
    const int idx = (0xFFFF - (key & 0xFFFF)) & (kS - 1);
    if (t3 == 0) { sts32(sb + SM_MISC + 4, idx); TS(8); }
    warp_arrive(bars + B_INFO * 8, lane);
    {
      const uint4 v = ldg_nc(P.x + (size_t)idx * kD + t3 * 8);
      sts128(sb + SM_BAND + t3 * 16, v.x, v.y, v.z, v.w);
    }
    const int t2 = (lane & 3) * 2, row = w3 * 16 + (lane >> 2);
    float a[4];
    uint32_t buf = 0, ph = 0;
    fence_async_smem();
    bar_sync(5, 128);
    {
      const int r = cta >> 4;
#pragma unroll 1
      for (int part = 0; part < 2; part++) {
        const int n = part ? 14 - 2 * r : 2 * r;
        moe_chunks<false>(a, n, buf, ph, P.da, P.dxs + (part ? 0 : (16 - n) * 8), lane == 0);
        uint2* dst = &g_pre[(((cta >> 2) & 2) + 1 - part) * kF + ((r - 1 + part) * 8 + (cta & 7)) * 64 + row];
        if (t2 == 0 && n) { st_tagged(dst, __float_as_uint(a[0]), target); st_tagged(dst + 8, __float_as_uint(a[2]), target); }
      }
    }
    if (t3 == 0) TS(9);
    bar_sync(5, 128);
    sts128(sb + SM_BAND + t3 * 16, 0, 0, 0, 0);
    {
      __nanosleep(POLL0);
      float gs, us;
      gather<kF, 4>(&g_pre[(cta >> 2) * 112 + min(t3, 111)], target, gs, us, budget);
      bar_sync(5, 128);
      if (t3 < 112) sts16(sb + SM_BAND + 112 + (t3 >> 3) * 128 + (t3 & 7) * 2, pack2(gs * sigmoidf(gs) * us, 0.f));
    }
    fence_async_smem();
    bar_sync(5, 128);
    if (t3 == 0) TS(12);
    moe_chunks<true>(a, 7, buf, ph, P.da, P.dband + 7, lane == 0);
    if (t3 == 0) TS(10);
    if (t2 < 4) {
      uint2* dst = &g_yp[(cta >> 2) * kD + (cta & 3) * 256 + t2 * 64 + row];
      st_tagged(dst, __float_as_uint(a[0]), target); st_tagged(dst + 8, __float_as_uint(a[2]), target);
      st_tagged(dst + 64, __float_as_uint(a[1]), target); st_tagged(dst + 72, __float_as_uint(a[3]), target);
    }
    if (lane == 0) mbar_arrive(bars + B_MD * 8);
    if ((idx >> 7) == bi) {
      mbar_wait(bars + (B_PUB + 3) * 8, 0, budget);
      if (w3 == 0) probe(&g_yp[lane * kD + bj * 128], target, budget);
      bar_sync(5, 128);
      float y = 0.f;
#pragma unroll 1
      for (int hf = 0; hf < 2; hf++) {
        float y0, y1;
        gather<kD, 16>(&g_yp[hf * 16 * kD + bj * 128 + t3], target, y0, y1, budget);
        y += y0 + y1;
      }
      const uint32_t ob = key >> 16;
      const float upd = y * sigmoidf(__uint_as_float(((ob & 0x8000u) ? (ob ^ 0x8000u) : (~ob & 0xFFFFu)) << 16));
      const uint32_t a = sb + SM_PHI + (t3 >> 6) * 16384 + (idx & 127) * 128 + ((((t3 >> 3) & 7) ^ (idx & 7)) << 4) + (t3 & 7) * 2;
      mbar_wait(bars + B_XT * 8, 0, budget);
      uint16_t xb;
      asm volatile("ld.shared.u16 %0, [%1];" : "=h"(xb) : "r"(a) : "memory");
      sts16(a, pack2(bf_lo(xb) + upd, 0.f));
      warp_arrive(bars + B_XP * 8, lane);
      if (t3 == 0) TS(11);
    }
  } else if (wg < 2) {
    if ((warp & 3) < EARLY_N && lane < (wg ? 8 : 16)) {
      const int n = warp & 3;
      const __nv_bfloat16* p = wg ? P.w + (size_t)(n * 64 + bi + (lane >> 1) * 16) * (3 * kD) + 1024 + (lane & 1) * 1024 + bj * 128
                                  : P.x + (size_t)(bi * 128 + bj * 16 + lane) * kD + n * 64;
      if (n) __nanosleep(n * EARLY_GAP);
      asm volatile("prefetch.global.L2 [%0];" :: "l"(p));
    }
    __syncwarp();
    asm volatile("setmaxnreg.inc.sync.aligned.u32 208;");
    const int tw = tid & 127, w = warp & 3, g = lane >> 2, t = lane & 3;
    const bool lane0 = lane == 0;
    if (wg == 0) sts128(sb + SM_Z + (tw & 63) * 16, 0x3f803f80u, 0x3f803f80u, 0x3f803f80u, 0x3f803f80u);
    bar_sync(0, 512);
    if (wg == 1) {
      float sr[4], sg[4];
      zero(sr); zero(sg);
#pragma unroll 1
      for (int c = 0; c < 4; c++) {
        mbar_wait(bars + (B_RX + c) * 8, 0, budget);
        uint32_t rs[4], gs[4], xs[4][4];
        lds128(sb + SM_V + c * 512 + lane * 16, rs);
        lds128(sb + SM_V + 2048 + c * 512 + lane * 16, gs);
#pragma unroll
        for (int r = 0; r < 4; r++) lds128(sb + SM_PHI + c * 8192 + (w * 4 + r) * 512 + lane * 16, xs[r]);
#pragma unroll
        for (int e = 0; e < 4; e++) {
          const float r0 = bf_lo(rs[e]), r1 = bf_hi(rs[e]), g0 = bf_lo(gs[e]), g1 = bf_hi(gs[e]);
#pragma unroll
          for (int r = 0; r < 4; r++) {
            const float x0 = bf_lo(xs[r][e]), x1 = bf_hi(xs[r][e]);
            sr[r] = fma_v(x0, r0, sr[r]); sg[r] = fma_v(x0, g0, sg[r]);
            sr[r] = fma_v(x1, r1, sr[r]); sg[r] = fma_v(x1, g1, sg[r]);
            if (r != 1) yield_slot();
          }
        }
      }
      fence_async_smem();
      __syncwarp();
      if (lane < 3) mbar_arrive(bars + (B_ME + lane) * 8);
      const bool b4 = lane & 16, b3 = lane & 8, b2 = lane & 4;
      const float v = qsum(fold(fold(fold(sr[0], sg[0], b4, 16), fold(sr[2], sg[2], b4, 16), b3, 8),
                                fold(fold(sr[1], sg[1], b4, 16), fold(sr[3], sg[3], b4, 16), b3, 8), b2, 4));
      const int row = bi * 128 + bj * 16 + w * 4 + (g & 3);
      const uint32_t rb = pack2(v + 0.f, 0.f);
      const uint32_t ob = (rb & 0x8000u) ? (~rb & 0xFFFFu) : (rb | 0x8000u);
      const uint32_t best = __reduce_max_sync(0xffffffffu, b4 ? 0u : (ob << 16) | (0xFFFFu - row));
      mbar_wait(bars + B_EPOCH * 8, 0, budget);
      const uint32_t tag = lds32(sb + SM_MISC);
      if (lane0) sts32(sb + SM_MISC + 16 + w * 4, best);
      if (b4 && t == 0) st_tagged(&g_gate[row], __float_as_uint(sigmoidf(v)), tag);
      if (tw == 0) TS(14);
      bar_arrive(6, 256);
      bar_sync(1, 256);
    }

    {
      float acc[2][64];
      if (tw == 0) TS(16 + wg * 16);
      mainloop128(acc, P.da, P.db, wg, wg, 16, lane0, budget, cta, wg * 16);
      bar_sync(1 + wg, 256);
      wg_wait<0>();
      pin(acc[0]); pin(acc[1]);
      if (lane0) mbar_arrive_n(bars + (B_EM + wg) * 8, 2);
      if (tw == 0) TS(17 + wg * 16);
      float p[4][16];
      uint32_t vp[8][4];
      const uint32_t av = sb + SM_V + (w * 16 + g) * 64 + ((t ^ (g >> 1)) << 4);
      {
        uint32_t kf[4][2][4];
#pragma unroll
        for (int u = 0; u < 4; u++)
#pragma unroll
          for (int s = 0; s < 2; s++)
#pragma unroll
            for (int r = 0; r < 4; r++) kf[u][s][r] = pack2(acc[u & 1][16 * (u >> 1) + 8 * s + 2 * r], acc[u & 1][16 * (u >> 1) + 8 * s + 2 * r + 1]);
        mbar_wait(bars + B_WPHI * 8, 0, budget);
        const uint64_t dw = P.dw + wg * 256;
        wg_fence();
#pragma unroll
        for (int u = 0; u < 4; u++) {
          wgmma_m64n32k16_rs<1>(p[u], kf[u][0], dw + (u >> 1) * 128, 0);
          wgmma_m64n32k16_rs<1>(p[u], kf[u][1], dw + (u >> 1) * 128 + 64, 1);
        }
        wg_commit();
#pragma unroll
        for (int u = 0; u < 8; u++) {
          const float* a = &acc[(u >> 1) & 1][32 + 16 * (u >> 2) + 2 * (u & 1)];
          vp[u][0] = pack2(a[0], a[1]); vp[u][1] = pack2(a[4], a[5]); vp[u][2] = pack2(a[8], a[9]); vp[u][3] = pack2(a[12], a[13]);
          if (u < 4) sts128(av + (u >> 1) * 4096 + (u & 1) * 512, vp[u][0], vp[u][1], vp[u][2], vp[u][3]);
        }
        pinr(vp);
        wg_wait<0>();
#pragma unroll
        for (int u = 0; u < 4; u++) pin(p[u]);
      }
      if (tw == 0) TS(18 + wg * 16);
      float kv[2][20];
      {
        const uint32_t sphi = sb + SM_PHI + (w * 16 + (lane & 15)) * 128 + (((lane >> 4) ^ (lane & 7)) << 4);
        float top = 0.f;
        uint32_t pk[4][2][4];
        float ps[2], sa[4], sc[4];
        uint32_t redo = 0;
#pragma unroll
        for (int i = 0; i < 11; i++) {
          if (i >= 3) {
            const int j = i - 3;
            const float s0 = sc[0] + sc[2], s1 = sc[1] + sc[3];
            top = fmaxf(top, fmaxf(s0, s1));
            store_phi((sphi ^ ((j & 1) * 64)) + (j & 2) * 4096, pk[j & 3], rcp2(s0), rcp2(s1));
          }
          if (i >= 2 && i <= 9) {
            sc[0] = sa[0] + sa[2]; sc[1] = sa[1] + sa[3];
            sc[2] = __shfl_xor_sync(0xffffffffu, sc[0], 2); sc[3] = __shfl_xor_sync(0xffffffffu, sc[1], 2);
          }
          if (i >= 1 && i <= 8) {
            sa[0] = ps[0]; sa[1] = ps[1];
            sa[2] = __shfl_xor_sync(0xffffffffu, sa[0], 1); sa[3] = __shfl_xor_sync(0xffffffffu, sa[1], 1);
          }
          if (i < 8) {
            pin(p[i >> 1]);
            float e[16];
#pragma unroll
            for (int c = 0; c < 16; c++) e[c] = ex2((i & 1) ? -p[i >> 1][c] : p[i >> 1][c]);
            pack_sums(e, pk[i & 3], ps);
            pinr(pk[i & 3]); pin(ps);
          }
          if (i < 10) yield_slot();
          if (i >= 2 && i <= 9) pin(sc);
          if (i >= 1 && i <= 8) pin(sa);
          if (i == 2 && wg) mbar_wait(bars + B_RD * 8, 0, budget);
          if (i >= 4 && !(i & 1)) {
            const int u = (i - 4) >> 1;
            fence_async_smem();
            wg_wait<0>();
            if (u < 3) bar_sync(7 + wg, 128);
            else asm volatile("{\n.reg .pred p, q;\nsetp.ne.b32 p, %2, 0;\nbar.red.or.pred q, %1, 128, p;\nselp.u32 %0, 1, 0, q;\n}"
                              : "=r"(redo) : "r"(7 + wg), "r"((uint32_t)!(top < EXP_LIM_F)) : "memory");
            issue_kv(kv[u >> 1], P.dphi + (u & 1) * 512, P.dv - (u & 1) * DV_TILE, u & 1);
            if (u == 1 || u == 2) {
#pragma unroll
              for (int r = 0; r < 2; r++) sts128(av + ((u + 1) & 1) * 4096 + r * 512, vp[2 * u + 2 + r][0], vp[2 * u + 2 + r][1], vp[2 * u + 2 + r][2], vp[2 * u + 2 + r][3]);
            }
            if (u < 3) yield_slot();
          }
        }
        if (tw == 0) TS(19 + wg * 16);
        wg_wait<0>();
        pin(kv[0]); pin(kv[1]);
        if (__builtin_expect(__any_sync(0xffffffffu, redo), 0)) {
#pragma unroll 1
          for (int u = 0; u < 4; u++) {
            bar_sync(7 + wg, 128);
#pragma unroll 1
            for (int sg = 0; sg < 2; sg++) {
              float e[16];
              exp_shifted(p[0], sg ? -1.f : 1.f, e);
              pack_sums(e, pk[0], ps);
              store_phi(sphi ^ (sg * 64), pk[0], rcp2(qsum(ps[0])), rcp2(qsum(ps[1])));
            }
            sts128(av, vp[0][0], vp[0][1], vp[0][2], vp[0][3]);
            sts128(av + 512, vp[1][0], vp[1][1], vp[1][2], vp[1][3]);
            fence_async_smem();
            bar_sync(7 + wg, 128);
            issue_kv(kv[1], P.dphi, P.dv, u & 1);
            wg_wait<0>();
            pin(kv[1]);
#pragma unroll
            for (int c = 0; c < 16; c++) { p[0][c] = p[1][c]; p[1][c] = p[2][c]; p[2][c] = p[3][c]; }
#pragma unroll
            for (int c = 0; c < 24; c++) vp[c >> 2][c & 3] = vp[(c >> 2) + 2][c & 3];
            if (u == 1) {
#pragma unroll
              for (int c = 0; c < 20; c++) kv[0][c] = kv[1][c];
            }
          }
        }
      }
      if (tw == 0) TS(20 + wg * 16);
      bar_sync(7 + wg, 128);
      {
        const int srow = w * 16 + (lane & 15);
        const uint32_t a0 = sb + SM_PHI + srow * 64 + (((lane >> 4) ^ ((srow >> 1) & 3)) << 4);
#pragma unroll
        for (int q = 0; q < 4; q++) {
          const float* a = &kv[q >> 1][8 * (q & 1)];
          stmatrix4((a0 ^ ((q & 1) * 32)) + (q >> 1) * 4096, pack2(a[0], a[1]), pack2(a[2], a[3]), pack2(a[4], a[5]), pack2(a[6], a[7]));
        }
        const uint32_t z = pack2(t == 0 ? kv[0][16] : t == 1 ? kv[1][16] : t == 2 ? kv[0][18] : kv[1][18], 0.0625f);
        sts128(sb + SM_PHI + 8192 + ((w & 1) * 16 + (t >> 1) * 8 + g) * 64 + ((((w & 2) + (t & 1)) ^ (g >> 1)) << 4), z, z, z, z);
      }
      fence_async_smem();
      warp_arrive(bars + (B_RED + wg) * 8, lane);
      if (tw == 0) TS(51 + wg * 4);
    }

    uint32_t stash = sb + 3 * STAGE + w * 4096 + lane * 16;
    const int rowl = wg * 64 + w * 16 + g;
    mbar_wait(bars + B_INFO * 8, 0, budget);
    const float gA = ldsf(sb + SM_G + rowl * 4), gB = ldsf(sb + SM_G + rowl * 4 + 32);
    __nv_bfloat16* og = P.o + (size_t)(bi * 128 + rowl) * kD + bj * 128 + t * 8;
    uint32_t own = sb + 3 * STAGE + rowl * 128 + ((t ^ g) << 4);
    uint32_t sx = sb + SM_PHI + (wg * 64 + w * 16 + (lane & 15)) * 128 + (((lane >> 4) ^ (lane & 7)) << 4);
    uint32_t routed = (lds32(sb + SM_MISC + 4) >> 4) == (uint32_t)(bi * 8 + warp);
    asm volatile("" : "+l"(og), "+r"(own), "+r"(stash), "+r"(sx), "+r"(routed));
    {
      float p[4][16];
      uint32_t ef[2][4][4];
      uint32_t qf[4][2][4];
      auto pack_q = [&](const float (&a)[64]) {
#pragma unroll
        for (int i = 0; i < 32; i++) qf[i >> 3][(i >> 2) & 1][i & 3] = pack2(a[2 * i], a[2 * i + 1]);
      };
      if (wg == 0) {
        float acc[2][64];
        bar_sync(2, 256);
        if (tw == 0) TS(22);
        mainloop128(acc, P.da, P.db, 32 % NST, (32 / NST) & 1, 12, lane0, budget, cta, 32);
#pragma unroll
        for (int n = 44; n < 48; n++) {
          mbar_wait(bars + (B_FX + n % NST) * 8, (n / NST) & 1, budget);
          kstep64(acc[0], P.da + (n % NST) * (STAGE >> 4), P.db + (n % NST) * (STAGE >> 4), 1);
          if (n == 47) break;
          wg_wait<1>();
          if (n == 44) {
            if (lane0) mbar_arrive_n(bars + (B_EM + 43 % NST) * 8, 2);
            pin(acc[1]);
            bar_sync(7, 128);
          }
          if (n <= 45) {
#pragma unroll
            for (int u = (n - 44) * 4; u < (n - 43) * 4; u++) {
              const float* a = &acc[1][8 * u];
              sts128(stash + u * 512, pack2(a[0], a[1]), pack2(a[2], a[3]), pack2(a[4], a[5]), pack2(a[6], a[7]));
            }
          }
          if (n == 45) warp_arrive(bars + B_QS * 8, lane);
        }
        bar_sync(13, 256);
        wg_wait<0>();
        pin(acc[0]);
        if (tw == 0) TS(15);
        pack_q(acc[0]);
        issue_pq(p, qf, P.dw, 0);
        wg_wait<0>();
      } else {
        float acc[64];
        mbar_wait(bars + B_QS * 8, 0, budget);
#pragma unroll
        for (int u = 0; u < 8; u++) lds128(stash + u * 512, qf[u >> 1][u & 1]);
        pinr(qf[3]);
        bar_sync(13, 256);
#pragma unroll
        for (int n = 44; n < 48; n++) {
#pragma unroll
          for (int hf = 0; hf < 2; hf++) {
            const uint64_t da = P.da + 512 + (n % NST) * (STAGE >> 4) + hf * 4, db = P.db + (n % NST) * (STAGE >> 4) + hf * 256;
            wg_wait<1>();
            if (hf && n > 44 && lane0) mbar_arrive_n(bars + (B_EM + (n - 1) % NST) * 8, 2);
            wg_fence();
            wgmma_m64n128k16_ss<0, 1>(acc, da, db, n > 44 || hf);
            wgmma_m64n128k16_ss<0, 1>(acc, da + 2, db + 128, 1);
            wg_commit();
          }
          if (n == 46) issue_pq(p, qf, P.dw, 0);
        }
        wg_wait<0>();
        pin(acc);
        if (lane0) { mbar_arrive_n(bars + (B_EM + 47 % NST) * 8, 2); mbar_arrive(bars + B_T3 * 8); }
        if (tw == 0) TS(23);
        pack_q(acc);
        issue_pq(p, qf, P.dw, 1);
        wg_wait<0>();
      }
#pragma unroll
      for (int h = 0; h < 4; h++) pin(p[h]);
      if (tw == 0) TS(24 + wg * 16);

#pragma unroll 1
      for (int pr = 0; pr < 2; pr++) {
        if (YIELD_EXP && pr > wg) bar_sync(11, 256);
        const uint32_t top = exp_frags(p[1], ef[1], exp_frags(p[0], ef[0], EXP_TOP));
        if (YIELD_EXP && pr < wg) { pinr(ef[0]); pinr(ef[1]); bar_arrive(11, 256); }
        if (__builtin_expect(__any_sync(0xffffffffu, top != EXP_TOP), 0)) {
#pragma unroll 1
          for (int u = 0; u < 4; u++) {
            float e[16];
            exp_shifted(p[0], (u & 1) ? -1.f : 1.f, e);
#pragma unroll
            for (int r = 0; r < 4; r++) {
#pragma unroll
              for (int s = 0; s < 6; s++) ef[s >> 2][s & 3][r] = ef[(s + 2) >> 2][(s + 2) & 3][r];
              ef[1][2][r] = pack2(e[2 * r], e[2 * r + 1]);
              ef[1][3][r] = pack2(e[8 + 2 * r], e[8 + 2 * r + 1]);
            }
            if (u & 1) {
#pragma unroll
              for (int e2 = 0; e2 < 16; e2++) p[0][e2] = p[1][e2];
            }
          }
        }
        float np[2][20], nm[2][20];
        mbar_wait(bars + (B_KV + pr) * 8, 0, budget);
        wg_fence();
#pragma unroll
        for (int hh = 0; hh < 2; hh++) {
          const uint64_t dk = P.dv - (uint64_t)pr * ((384ull << 16) - 512ull) - hh * ((255ull << 16) - 256ull);
          wgmma_m64n40k16_rs<1>(np[hh], ef[hh][0], dk, 0);
          wgmma_m64n40k16_rs<1>(np[hh], ef[hh][1], dk + 64, 1);
          wgmma_m64n40k16_rs<1>(nm[hh], ef[hh][2], dk + 128 - (126ull << 16), 0);
          wgmma_m64n40k16_rs<1>(nm[hh], ef[hh][3], dk + 192 - (126ull << 16), 1);
          wg_commit();
        }
#pragma unroll
        for (int hh = 0; hh < 2; hh++) {
          if (hh == 0) wg_wait<1>(); else wg_wait<0>();
          pin(np[hh]); pin(nm[hh]);
          uint32_t o[2][4];
#pragma unroll
          for (int r = 0; r < 2; r++) {
            const float dp = np[hh][16 + 2 * r], sp = np[hh][17 + 2 * r], dm = nm[hh][16 + 2 * r], sm = nm[hh][17 + 2 * r];
            const float inv = (r == 0 ? gA : gB) * rcp(fmaf(dp, sm, fmaf(1e-6f, sm, dm) * sp));
            const float cp = sm * inv, cm = sp * inv;
#pragma unroll
            for (int c = 0; c < 4; c++)
              o[r][c] = pack2(fmaf(np[hh][4 * c + 2 * r], cp, nm[hh][4 * c + 2 * r] * cm), fmaf(np[hh][4 * c + 2 * r + 1], cp, nm[hh][4 * c + 2 * r + 1] * cm));
            sts128((own ^ (hh * 64)) + r * 1024, o[r][0], o[r][1], o[r][2], o[r][3]);
          }
          if (hh == 1 && pr == 1) fence_async_smem();
#pragma unroll
          for (int r = 0; r < 2; r++) asm volatile("st.global.v4.u32 [%0], {%1,%2,%3,%4};" :: "l"(og + r * 8 * kD + hh * 32), "r"(o[r][0]), "r"(o[r][1]), "r"(o[r][2]), "r"(o[r][3]) : "memory");
        }
        warp_arrive(bars + (B_PUB + wg * 2 + pr) * 8, lane);
        if (tw == 0) TS(25 + pr + wg * 16);
        if (pr) break;
        og += 64; own += STAGE;
#pragma unroll
        for (int e = 0; e < 16; e++) { p[0][e] = p[2][e]; p[1][e] = p[3][e]; }
      }
    }
    uint32_t xf[8][4];
    if (!wg) {
      mbar_wait(bars + B_XT * 8, 0, budget);
      load_x(sx, xf);
      mbar_wait(bars + (B_PUB + 3) * 8, 0, budget);
    } else {
#pragma unroll
      for (int i = 0; i < 32; i++) xf[i >> 2][i & 3] = 0;
    }
    bar_sync(7 + wg, 128);

    float oacc[64];
    {
      const uint64_t dam = P.da + wg * 512;
      uint32_t slot = 3, ph = 1, prev = 0;
#pragma unroll 1
      for (int s = 0; s < 16; s++) {
        if (tid == 0) KS(128 + 48 + s);
        if (!wg || s <= 16 - END_SKEW) {
          mbar_wait(bars + B_FX * 8 + slot * 8, ph, budget);
          if (s >= 2) mbar_wait(bars + (B_FY + wg * NST) * 8 + slot * 8, ph, budget);
        }
        if (tid == 0) KS(48 + s);
        if (tid == 128) KS(192 + 48 + s);
        if (wg && s == 16 - END_SKEW) {
          mbar_wait(bars + B_XT * 8, 0, budget);
          load_x(sx, xf);
#pragma unroll
          for (int n = 65 - END_SKEW; n < 64; n++) mbar_wait(bars + (B_FY + NST + n % NST) * 8, (n / NST) & 1, budget);
          bar_sync(12, 256);
        }
        const uint64_t da = dam + slot * (STAGE >> 4), db = P.db + slot * (STAGE >> 4);
#pragma unroll
        for (int hf = 0; hf < 2; hf++) {
          wg_wait<1>();
          if (hf && s > 0 && s < 12 && lane0) mbar_arrive(bars + B_EM * 8 + prev * 8);
          wg_fence();
          wgmma_m64n128k16_ss<0, 1>(oacc, da + hf * 4, db + hf * 256, hf ? 1 : s);
          wgmma_m64n128k16_ss<0, 1>(oacc, da + hf * 4 + 2, db + hf * 256 + 128, 1);
          wg_commit();
        }
        prev = slot;
        if (++slot == NST) { slot = 0; ph ^= 1; }
      }
      if (!wg) bar_arrive(12, 256);
    }
    if (__any_sync(0xffffffffu, routed)) { mbar_wait(bars + B_XP * 8, 0, budget); load_x(sx, xf); }
    const float hA = 1.0f - gA, hB = 1.0f - gB;
    float xv[64];
#pragma unroll
    for (int i = 0; i < 32; i++) { xv[2 * i] = bf_lo(xf[i >> 2][i & 3]); xv[2 * i + 1] = bf_hi(xf[i >> 2][i & 3]); }
    pin(xv);
    yield_slot();
    wg_wait<0>();
    pin(oacc);
    if (tw == 0) TS(29 + wg * 16);
#pragma unroll
    for (int hf = 0; hf < 2; hf++) {
#pragma unroll
      for (int u = hf * 4; u < hf * 4 + 4; u++) {
        const float* a = &oacc[8 * u];
        const float* b = &xv[8 * u];
        stmatrix4((sx ^ ((u & 3) * 32)) + hf * 16384,
                  pack2(fmaf(hA, b[0], a[0]), fmaf(hA, b[1], a[1])), pack2(fmaf(hB, b[2], a[2]), fmaf(hB, b[3], a[3])),
                  pack2(fmaf(hA, b[4], a[4]), fmaf(hA, b[5], a[5])), pack2(fmaf(hB, b[6], a[6]), fmaf(hB, b[7], a[7])));
        if (FIN_YIELD) yield_slot();
      }
      fence_async_smem();
      __syncwarp();
      if (elect_one()) tma_store(&mout, sb + SM_PHI + hf * 16384 + warp * 2048, bj * 128 + hf * 64, bi * 128 + warp * 16);
    }
    if (elect_one()) {
      asm volatile("cp.async.bulk.commit_group;" ::: "memory");
      asm volatile("cp.async.bulk.wait_group.read 0;" ::: "memory");
    }
  } else {
    asm volatile("setmaxnreg.dec.sync.aligned.u32 32;");
    if (warp == 8) {
      if (elect_one()) {
        TS(7);
#pragma unroll
        for (int s = 0; s < NST; s++) mbar_init(bars + (B_FX + s) * 8, 1);
        asm volatile("fence.mbarrier_init.release.cluster;" ::: "memory");
        fence_async_smem();
      }
      __syncwarp();
      bar_arrive(0, 512);
      if (elect_one()) {
#pragma unroll 1
        for (int n = 0; n < NST; n++) {
          const uint32_t st = sb + n * STAGE, fb = bars + (B_FX + n) * 8;
          KS(64 + n);
          mbar_expect_tx(fb, STAGE);
          tma_load(st, &mx, fb, n * 64, bi * 128);
          tma_load(st + 16384, &mw, fb, 1024 + bj * 128, n * 64);
          tma_load(st + 24576, &mw, fb, 2048 + bj * 128, n * 64);
        }
      }
      __syncwarp();
      bar_sync(10, 64);
    } else {
      if (warp == 9) {
        if (elect_one()) {
#pragma unroll
          for (int s = B_FY; s < B_NUM; s++) mbar_init(bars + s * 8, s < B_WPHI ? 1 : s < B_EM ? 4 : 8);
          asm volatile("fence.mbarrier_init.release.cluster;" ::: "memory");
          fence_async_smem();
        }
        __syncwarp();
        bar_arrive(10, 64);
      }
      bar_sync(0, 512);
    }
    if (!elect_one()) return;
    if (warp == 8) {
      uint32_t slot = 0, ph = 0;
#pragma unroll 1
      for (int n = NST; n < 48; n++) {
        const int t = n >> 4, k = n & 15;
        const int c0 = t == 2 ? bj * 128 : 1024 + bj * 128 + t * 64, c1 = t == 2 ? c0 + 64 : c0 + 1024;
        const uint32_t st = sb + slot * STAGE, fb = bars + (B_FX + slot) * 8;
        if (n <= NST + 3 * RSTEP && (n - NST) % RSTEP == 0) {
          const int c = (n - NST) / RSTEP;
          mbar_expect_tx(bars + (B_RX + c) * 8, c == 0 ? 8192 + 4096 : 8192);
          tma_load(sb + SM_PHI + c * 8192, &mxr, bars + (B_RX + c) * 8, c * 256, bi * 128 + bj * 16);
          if (c == 0) { bulk_load(sb + SM_V, P.w_r, 2048, bars + B_RX * 8); bulk_load(sb + SM_V + 2048, P.gate_w, 2048, bars + B_RX * 8); }
        }
        mbar_wait(bars + (B_EM + slot) * 8, ph, budget);
        KS(64 + n);
        mbar_expect_tx(fb, STAGE);
        tma_load(st, &mx, fb, k * 64, bi * 128);
        tma_load(st + 16384, &mw, fb, c0, k * 64);
        tma_load(st + 24576, &mw, fb, c1, k * 64);
        {
          const int m = n + WLEAD, tm = m >> 4;
          if ((m & 3) == (bi & 3)) {
            const int d0 = tm >= 2 ? bj * 128 : 1024 + bj * 128 + tm * 64, d1 = tm >= 2 ? d0 + 64 : d0 + 1024;
            tma_prefetch(tm == 3 ? &mwo : &mw, d0, (m & 15) * 64); tma_prefetch(tm == 3 ? &mwo : &mw, d1, (m & 15) * 64);
          }
        }
        if (++slot == NST) { slot = 0; ph ^= 1; }
      }
#pragma unroll 1
      for (int m = WLEAD + ((bi - WLEAD) & 3); m < 16; m += 4) { tma_prefetch(&mwo, bj * 128, m * 64); tma_prefetch(&mwo, bj * 128 + 64, m * 64); }
#pragma unroll 1
      for (int s = 0; s < 16; s++) {
        const int p = s < 2 ? s : (s >= 9), q = s < 9 ? s - 2 : s - 9;
        const int k0 = (s < 2 ? bj : q + (q >= bj)) * 128 + p * 64;
        const uint32_t st = sb + slot * STAGE, fb = bars + (B_FX + slot) * 8;
        mbar_wait(bars + (B_EM + slot) * 8, ph, budget);
        KS(64 + 48 + s);
        mbar_expect_tx(fb, 16384);
        tma_load(st + 16384, &mwo, fb, bj * 128, k0);
        tma_load(st + 24576, &mwo, fb, bj * 128 + 64, k0);
        if (++slot == NST) { slot = 0; ph ^= 1; }
      }
      if (REPF) prefetch_map(&mout);
    } else if (warp == 9) {
      prefetch_map(&mo); prefetch_map(&mout);
      uint32_t old;
      asm volatile("atom.add.release.gpu.global.u32 %0, [%1], 1;" : "=r"(old) : "l"(&g_cnt[C_START]) : "memory");
      sts32(sb + SM_MISC, (old & ~255u) + 256u);
      mbar_arrive(bars + B_EPOCH * 8);
      const CUtensorMap* m = (cta & 8) ? &mu : &mg;
      const int l0 = (cta >> 4) * 14, a0 = (cta & 7) * 64, d1 = (cta >> 2) * 112 - 14 * 16, d2 = (cta & 3) * 4;
      uint32_t buf = 0, ph = 0, tnext;
      asm volatile("mov.u32 %0, %%clock;" : "=r"(tnext));
#pragma unroll 1
      for (int c = 0; c < 21; c++) {
        const uint32_t dst = sb + moe_buf(buf), fb = bars + (B_MF + buf) * 8;
        mbar_wait(bars + (B_ME + buf) * 8, ph, budget);
        mbar_expect_tx(fb, 8192);
        if (c < 14) tma_load(dst, m, fb, a0 + ((l0 + c) >> 4) * 512, ((l0 + c) & 15) * 64); else tma_load3(dst, &md, fb, d1 + c * 16, d2);
        if (MLEAD && c >= 2 && c + MLEAD < 17) {
          const int f = c + MLEAD;
          if (f < 14) tma_prefetch(m, a0 + ((l0 + f) >> 4) * 512, ((l0 + f) & 15) * 64); else tma_prefetch3(&md, d1 + f * 16, d2);
        }
        if (MPACE) { uint32_t now; do { asm volatile("mov.u32 %0, %%clock;" : "=r"(now)); if ((int32_t)(now - tnext) >= 0) break; __nanosleep(20); } while (true); tnext = now + MPACE; }
        if (c == 16) {
#pragma unroll 1
          for (int f = 17; f < 21; f++) { __nanosleep(MGAP); tma_prefetch3(&md, d1 + f * 16, d2); }
        }
        if (c < 2) __nanosleep(MGAP);
        if (c == 17) mbar_arrive(bars + B_M2 * 8);
        if (++buf >= (c >= 14 ? 2 : 3)) { buf = 0; ph ^= 1; }
      }
      mbar_wait(bars + B_MD * 8, 0, budget);
      mbar_wait(bars + (B_RD + 1) * 8, 0, budget);
      mbar_wait(bars + XT_GATE * 8, 0, budget);
      mbar_expect_tx(bars + B_XT * 8, 32768);
      tma_load(sb + SM_PHI, &mx, bars + B_XT * 8, bj * 128, bi * 128);
      tma_load(sb + SM_PHI + 16384, &mx, bars + B_XT * 8, bj * 128 + 64, bi * 128);
      mbar_wait(bars + (B_PUB + 1) * 8, 0, budget);
      mbar_wait(bars + (B_PUB + 3) * 8, 0, budget);
      signal_add(&g_cnt[(C_O + bi * 4 + 1) * 32], 32u);
      TS(57);
      wait_count<POLLF>(&g_cnt[(C_O + bi * 4 + 1) * 32], (old & ~255u) + 256u, budget);
      mbar_arrive(bars + B_P1 * 8);
      TS(3);
    } else {
      const int u = warp - 10, hp = bj * 2 + u;
      mbar_wait(bars + B_EPOCH * 8, 0, budget);
      const uint32_t target = lds32(sb + SM_MISC);
      mbar_wait(bars + B_INFO * 8, 0, budget);
      wait_count<200>(&g_cnt[C_START], target, budget);
      fence_async_global();
#pragma unroll 1
      for (int e = 0; e < 2; e++) {
        uint32_t* cnt = &g_cnt[(e ? C_O + bi * 4 + u * 2 : C_KV + hp) * 32];
        mbar_wait(bars + (e ? B_PUB + u * 2 : B_RED + u) * 8, 0, budget);
        if (e == 0) {
#pragma unroll 1
          for (uint32_t c = 0, n = u ? RED_CH1 : RED_CH, sz = 10240 / n, cc = RED_ROT ? bi % n : 0; c < n; c++) {
            bulk_reduce(reinterpret_cast<char*>(&g_kvr[hp * 2560]) + cc * sz, sb + SM_PHI + cc * sz, sz);
            if (++cc == n) cc = 0;
            if (c + 1 < n) __nanosleep(u ? RED_GAP1 : RED_GAP0);
          }
          asm volatile("cp.async.bulk.commit_group;" ::: "memory");
          asm volatile("cp.async.bulk.wait_group 0;" ::: "memory");
          TS(21 + u * 16);
          mbar_arrive(bars + (B_RD + u) * 8);
        }
        signal_add(cnt, e ? 32u : 16u);
        TS(e ? 56 + u * 2 : 60 + u);
        if (REPF && e) prefetch_map(&mo);
        if (e == 0) {
          mbar_wait(bars + (u ? B_M2 : B_RED + 1) * 8, 0, budget);
        }
        wait_count<POLLF>(cnt, target, budget);
        fence_async_global();
        if (e == 0) {
          mbar_expect_tx(bars + (B_KV + u) * 8, 10240);
          bulk_load(sb + SM_V + u * 8192, &g_kvr[hp * 2560], 8192, bars + (B_KV + u) * 8);
          bulk_load(sb + SM_Z + u * 2048, &g_kvr[hp * 2560 + 2048], 2048, bars + (B_KV + u) * 8);
          TS(38 + u);
        }
      }
      TS(2 + u * 2);
      if (u == 0) mbar_wait(bars + B_T3 * 8, 0, budget);
      uint32_t slot = 0, ph = 1;
#pragma unroll 1
      for (int s = 2; s < 16; s++) {
        const int p = s >= 9, q = s < 9 ? s - 2 : s - 9;
        if (s == 9) { mbar_wait(bars + B_P1 * 8, 0, budget); fence_async_global(); }
        const uint32_t fb = bars + (B_FY + u * NST + slot) * 8;
        mbar_wait(bars + (B_EM + slot) * 8, ph, budget);
        mbar_expect_tx(fb, 8192);
        tma_load(sb + slot * STAGE + u * 8192, &mo, fb, (q + (q >= bj)) * 128 + p * 64, bi * 128 + u * 64);
        if (++slot == NST) { slot = 0; ph ^= 1; }
      }
    }
  }
}

typedef CUresult (*EncodeFn)(CUtensorMap*, CUtensorMapDataType, cuuint32_t, void*, const cuuint64_t*, const cuuint64_t*, const cuuint32_t*,
                             const cuuint32_t*, CUtensorMapInterleave, CUtensorMapSwizzle, CUtensorMapL2promotion, CUtensorMapFloatOOBfill);

void make_map(EncodeFn enc, CUtensorMap* m, const void* ptr, uint64_t cols, uint64_t rows, uint32_t bc, uint32_t br, CUtensorMapSwizzle swz) {
  const cuuint64_t dims[2] = {cols, rows}, strides[1] = {cols * 2};
  const cuuint32_t box[2] = {bc, br}, es[2] = {1, 1};
  enc(m, CU_TENSOR_MAP_DATA_TYPE_BFLOAT16, 2, const_cast<void*>(ptr), dims, strides, box, es, CU_TENSOR_MAP_INTERLEAVE_NONE, swz,
      CU_TENSOR_MAP_L2_PROMOTION_L2_128B, CU_TENSOR_MAP_FLOAT_OOB_FILL_NONE);
}

}

extern "C" void kernel_launch(void* const* d_in, const int* in_sizes, int n_in, void* d_out, int out_size) {
  (void)in_sizes; (void)n_in; (void)out_size;
  void* fn = nullptr;
  cudaDriverEntryPointQueryResult qr;
  cudaGetDriverEntryPoint("cuTensorMapEncodeTiled", &fn, cudaEnableDefault, &qr);
  EncodeFn enc = (EncodeFn)fn;
  void* o_ptr = nullptr;
  cudaGetSymbolAddress(&o_ptr, g_o);
  CUtensorMap mx, mw, mwo, mo, mout, mxr, mg, mu, md;
  make_map(enc, &mx, d_in[0], kD, kS, 64, 128, CU_TENSOR_MAP_SWIZZLE_128B);
  make_map(enc, &mxr, d_in[0], kD, kS, 256, 16, CU_TENSOR_MAP_SWIZZLE_NONE);
  make_map(enc, &mw, d_in[1], 3 * kD, kD, 64, 64, CU_TENSOR_MAP_SWIZZLE_128B);
  make_map(enc, &mwo, d_in[3], kD, kD, 64, 64, CU_TENSOR_MAP_SWIZZLE_128B);
  make_map(enc, &mo, o_ptr, kD, kS, 64, 64, CU_TENSOR_MAP_SWIZZLE_128B);
  make_map(enc, &mout, d_out, kD, kS, 64, 16, CU_TENSOR_MAP_SWIZZLE_128B);
  make_map(enc, &mg, d_in[6], kF, kD, 64, 64, CU_TENSOR_MAP_SWIZZLE_128B);
  make_map(enc, &mu, d_in[7], kF, kD, 64, 64, CU_TENSOR_MAP_SWIZZLE_128B);
  {
    const cuuint64_t dims[3] = {64, kF, 16}, strides[2] = {kD * 2, 128};
    const cuuint32_t box[3] = {64, 16, 4}, es[3] = {1, 1, 1};
    enc(&md, CU_TENSOR_MAP_DATA_TYPE_BFLOAT16, 3, d_in[8], dims, strides, box, es, CU_TENSOR_MAP_INTERLEAVE_NONE, CU_TENSOR_MAP_SWIZZLE_128B,
        CU_TENSOR_MAP_L2_PROMOTION_L2_128B, CU_TENSOR_MAP_FLOAT_OOB_FILL_NONE);
  }
  Params P;
  P.x = (const __nv_bfloat16*)d_in[0];
  P.w = (const __nv_bfloat16*)d_in[1];
  P.o = (__nv_bfloat16*)o_ptr;
  P.w_phi = (const __nv_bfloat16*)d_in[2];
  P.w_r = (const __nv_bfloat16*)d_in[5];
  P.gate_w = (const __nv_bfloat16*)d_in[9];
  P.da = make_desc(sb, 16, 1024, 1);
  P.db = make_desc(sb + 16384, 8192, 1024, 1);
  P.dw = make_desc(sb + SM_WPHI, 16, 512, 2);
  P.dphi = make_desc(sb + SM_PHI, 16, 1024, 1);
  P.dv = make_desc(sb + SM_V, SM_Z - SM_V, 512, 2);
  P.dband = make_desc(sb + SM_BAND, 128, 128, 0);
  P.dxs = make_desc(sb + SM_BAND, 16, 128, 0);
  int dev = 0, sms = 0;
  cudaGetDevice(&dev);
  cudaDeviceGetAttribute(&sms, cudaDevAttrMultiProcessorCount, dev);
  auto kern = sms == 132 ? fused_kernel<true> : fused_kernel<false>;
  cudaFuncSetAttribute(kern, cudaFuncAttributeMaxDynamicSharedMemorySize, SM_ALLOC);
  kern<<<132, 512, SM_ALLOC, cudaStreamPerThread>>>(mx, mw, mwo, mo, mout, mxr, mg, mu, md, P);
}
```

```cpp
#include <cuda_runtime.h>
#include <cuda_bf16.h>
#include <cuda.h>
#include <stdint.h>

namespace {

template<int TA, int TB> __device__ __forceinline__ void wgmma_m64n128k16_ss(float (&d)[64], uint64_t da, uint64_t db, int scale_d) {
  asm volatile("{\n.reg .pred p;\nsetp.ne.b32 p, %66, 0;\n"
    "wgmma.mma_async.sync.aligned.m64n128k16.f32.bf16.bf16 "
    "{%0, %1, %2, %3, %4, %5, %6, %7, %8, %9, %10, %11, %12, %13, %14, %15, "
    "%16, %17, %18, %19, %20, %21, %22, %23, %24, %25, %26, %27, %28, %29, %30, %31, "
    "%32, %33, %34, %35, %36, %37, %38, %39, %40, %41, %42, %43, %44, %45, %46, %47, "
    "%48, %49, %50, %51, %52, %53, %54, %55, %56, %57, %58, %59, %60, %61, %62, %63}, "
    "%64, %65, p, 1, 1, %67, %68;\n}\n"
    : "+f"(d[0]), "+f"(d[1]), "+f"(d[2]), "+f"(d[3]), "+f"(d[4]), "+f"(d[5]), "+f"(d[6]), "+f"(d[7]),
      "+f"(d[8]), "+f"(d[9]), "+f"(d[10]), "+f"(d[11]), "+f"(d[12]), "+f"(d[13]), "+f"(d[14]), "+f"(d[15]),
      "+f"(d[16]), "+f"(d[17]), "+f"(d[18]), "+f"(d[19]), "+f"(d[20]), "+f"(d[21]), "+f"(d[22]), "+f"(d[23]),
      "+f"(d[24]), "+f"(d[25]), "+f"(d[26]), "+f"(d[27]), "+f"(d[28]), "+f"(d[29]), "+f"(d[30]), "+f"(d[31]),
      "+f"(d[32]), "+f"(d[33]), "+f"(d[34]), "+f"(d[35]), "+f"(d[36]), "+f"(d[37]), "+f"(d[38]), "+f"(d[39]),
      "+f"(d[40]), "+f"(d[41]), "+f"(d[42]), "+f"(d[43]), "+f"(d[44]), "+f"(d[45]), "+f"(d[46]), "+f"(d[47]),
      "+f"(d[48]), "+f"(d[49]), "+f"(d[50]), "+f"(d[51]), "+f"(d[52]), "+f"(d[53]), "+f"(d[54]), "+f"(d[55]),
      "+f"(d[56]), "+f"(d[57]), "+f"(d[58]), "+f"(d[59]), "+f"(d[60]), "+f"(d[61]), "+f"(d[62]), "+f"(d[63])
    : "l"(da), "l"(db), "r"(scale_d), "n"(TA), "n"(TB));
}

template<int TB> __device__ __forceinline__ void wgmma_m64n32k16_rs(float (&d)[16], const uint32_t (&a)[4], uint64_t db, int scale_d) {
  asm volatile("{\n.reg .pred p;\nsetp.ne.b32 p, %21, 0;\n"
    "wgmma.mma_async.sync.aligned.m64n32k16.f32.bf16.bf16 "
    "{%0, %1, %2, %3, %4, %5, %6, %7, %8, %9, %10, %11, %12, %13, %14, %15}, "
    "{%16, %17, %18, %19}, %20, p, 1, 1, %22;\n}\n"
    : "+f"(d[0]), "+f"(d[1]), "+f"(d[2]), "+f"(d[3]), "+f"(d[4]), "+f"(d[5]), "+f"(d[6]), "+f"(d[7]),
      "+f"(d[8]), "+f"(d[9]), "+f"(d[10]), "+f"(d[11]), "+f"(d[12]), "+f"(d[13]), "+f"(d[14]), "+f"(d[15])
    : "r"(a[0]), "r"(a[1]), "r"(a[2]), "r"(a[3]), "l"(db), "r"(scale_d), "n"(TB));
}

template<int TA, int TB> __device__ __forceinline__ void wgmma_m64n40k16_ss(float (&d)[20], uint64_t da, uint64_t db, int scale_d) {
  asm volatile("{\n.reg .pred p;\nsetp.ne.b32 p, %22, 0;\n"
    "wgmma.mma_async.sync.aligned.m64n40k16.f32.bf16.bf16 "
    "{%0, %1, %2, %3, %4, %5, %6, %7, %8, %9, %10, %11, %12, %13, %14, %15, "
    "%16, %17, %18, %19}, "
    "%20, %21, p, 1, 1, %23, %24;\n}\n"
    : "+f"(d[0]), "+f"(d[1]), "+f"(d[2]), "+f"(d[3]), "+f"(d[4]), "+f"(d[5]), "+f"(d[6]), "+f"(d[7]),
      "+f"(d[8]), "+f"(d[9]), "+f"(d[10]), "+f"(d[11]), "+f"(d[12]), "+f"(d[13]), "+f"(d[14]), "+f"(d[15]),
      "+f"(d[16]), "+f"(d[17]), "+f"(d[18]), "+f"(d[19])
    : "l"(da), "l"(db), "r"(scale_d), "n"(TA), "n"(TB));
}

template<int TB> __device__ __forceinline__ void wgmma_m64n40k16_rs(float (&d)[20], const uint32_t (&a)[4], uint64_t db, int scale_d) {
  asm volatile("{\n.reg .pred p;\nsetp.ne.b32 p, %25, 0;\n"
    "wgmma.mma_async.sync.aligned.m64n40k16.f32.bf16.bf16 "
    "{%0, %1, %2, %3, %4, %5, %6, %7, %8, %9, %10, %11, %12, %13, %14, %15, "
    "%16, %17, %18, %19}, "
    "{%20, %21, %22, %23}, %24, p, 1, 1, %26;\n}\n"
    : "+f"(d[0]), "+f"(d[1]), "+f"(d[2]), "+f"(d[3]), "+f"(d[4]), "+f"(d[5]), "+f"(d[6]), "+f"(d[7]),
      "+f"(d[8]), "+f"(d[9]), "+f"(d[10]), "+f"(d[11]), "+f"(d[12]), "+f"(d[13]), "+f"(d[14]), "+f"(d[15]),
      "+f"(d[16]), "+f"(d[17]), "+f"(d[18]), "+f"(d[19])
    : "r"(a[0]), "r"(a[1]), "r"(a[2]), "r"(a[3]), "l"(db), "r"(scale_d), "n"(TB));
}

template<int TA, int TB> __device__ __forceinline__ void wgmma_m64n8k16_ss(float (&d)[4], uint64_t da, uint64_t db, int scale_d) {
  asm volatile("{\n.reg .pred p;\nsetp.ne.b32 p, %6, 0;\n"
    "wgmma.mma_async.sync.aligned.m64n8k16.f32.bf16.bf16 "
    "{%0, %1, %2, %3}, "
    "%4, %5, p, 1, 1, %7, %8;\n}\n"
    : "+f"(d[0]), "+f"(d[1]), "+f"(d[2]), "+f"(d[3])
    : "l"(da), "l"(db), "r"(scale_d), "n"(TA), "n"(TB));
}

constexpr int kS = 2048, kD = 1024, kF = 3584;
constexpr int NST = 5, STAGE = 32768;
constexpr uint32_t sb = 1024;
constexpr int SM_V    = NST * STAGE;
constexpr int SM_Z    = SM_V + 16384;
constexpr int SM_PHI  = SM_Z + 4096;
constexpr int SM_MOE  = SM_PHI + 16384;
constexpr int SM_WPHI = SM_MOE + 16384;
constexpr int SM_ONE  = SM_WPHI + 8192;
constexpr int SM_BAND = SM_ONE + 1024;
constexpr int SM_G    = SM_BAND + 2176;
constexpr int SM_BAR  = SM_G + 512;
constexpr int SM_MISC = SM_BAR + 448;
constexpr int SM_TOTAL = SM_MISC + 64;
static_assert(SM_TOTAL <= 232448, "smem");
constexpr uint32_t bars = sb + SM_BAR;
constexpr int B_FX = 0  , B_FY = 5  , B_XT = 15, B_EPOCH = 16, B_RX = 17  , B_MF = 21  , B_RD = 24  , B_KV = 26  , B_M2 = 28, B_P1 = 29;
constexpr int B_WPHI = 30, B_INFO = 31, B_QS = 32, B_XP = 33, B_RED = 34  , B_PUB = 36  , B_ME = 40  , B_MD = 43, B_T3 = 44, B_RH = 45  ;
constexpr int B_EM = 47  , B_NUM = 52;
constexpr int C_START = 0, C_O = 1, C_KV = C_O + 64;

__device__ uint2 g_gate[kS];
__device__ uint2 g_key[128];
__device__ uint2 g_pre[4 * kF];
__device__ uint2 g_yp[32 * kD];
__device__ __align__(128) uint32_t g_kvr[16 * 2560];
__device__ __align__(128) uint32_t g_cnt[(C_KV + 32) * 32];
__device__ __align__(1024) __nv_bfloat16 g_o[kS * kD];
#define KS(id)
#define RG(id)
#define TS(id)
#define TSG(id)
constexpr int SM_ALLOC = SM_TOTAL;

#define POLL0 500
#define POLL1 150
#define RSTEP 1
#define POLLR 400
#define EARLY_N 2
#define EARLY_GAP 200
#define POLLF 50
#define RED_GAP0 250
#define RED_GAP1 0
#define YIELD_EXP 1
#define END_SKEW 4
#define XT_GATE B_T3
#define FIN_YIELD 0
#define MLEAD 0
#define MPACE 0
#define REPF 1
#define WLEAD 11
#define MGAP 300

struct Params {
  const __nv_bfloat16 *x, *w, *w_phi, *w_r, *gate_w;
  __nv_bfloat16* o;
  uint64_t da, db, dw, dphi, dv, dkv, dband, dxs;
};

__device__ __forceinline__ uint32_t smem_u32(const void* p) { return (uint32_t)__cvta_generic_to_shared(p); }
__device__ __forceinline__ void mbar_init(uint32_t bar, uint32_t cnt) { asm volatile("mbarrier.init.shared::cta.b64 [%0], %1;" :: "r"(bar), "r"(cnt) : "memory"); }
__device__ __forceinline__ void mbar_expect_tx(uint32_t bar, uint32_t bytes) { asm volatile("mbarrier.arrive.expect_tx.shared::cta.b64 _, [%0], %1;" :: "r"(bar), "r"(bytes) : "memory"); }
__device__ __forceinline__ void mbar_arrive(uint32_t bar) { asm volatile("mbarrier.arrive.shared::cta.b64 _, [%0];" :: "r"(bar) : "memory"); }
__device__ __forceinline__ void mbar_arrive_n(uint32_t bar, uint32_t n) { asm volatile("mbarrier.arrive.shared::cta.b64 _, [%0], %1;" :: "r"(bar), "r"(n) : "memory"); }
constexpr int BUDGET = 1 << 20;
__device__ __forceinline__ void mbar_wait(uint32_t bar, uint32_t parity, int& budget) {
  asm volatile("{\n.reg .pred p;\n"
               "WAIT_L:\nmbarrier.try_wait.parity.shared::cta.b64 p, [%1], %2;\n@p bra WAIT_D;\n"
               "add.s32 %0, %0, -1;\nsetp.gt.s32 p, %0, 0;\n@p bra WAIT_L;\nWAIT_D:\n}"
               : "+r"(budget) : "r"(bar), "r"(parity) : "memory");
}
template <int SLEEP>
__device__ __forceinline__ void wait_count(const uint32_t* p, uint32_t target, int& budget) {
  asm volatile("{\n.reg .pred p;\n.reg .s32 v;\n"
               "WAIT_L:\nld.acquire.gpu.global.s32 v, [%1];\nsub.s32 v, v, %2;\nsetp.ge.s32 p, v, 0;\n@p bra WAIT_D;\n"
               "nanosleep.u32 %3;\nadd.s32 %0, %0, -4;\nsetp.gt.s32 p, %0, 0;\n@p bra WAIT_L;\nWAIT_D:\n}"
               : "+r"(budget) : "l"(p), "r"(target), "n"(SLEEP) : "memory");
}
__device__ __forceinline__ void tma_load(uint32_t dst, const CUtensorMap* m, uint32_t bar, int c0, int c1) {
  asm volatile("cp.async.bulk.tensor.2d.shared::cluster.global.mbarrier::complete_tx::bytes [%0], [%1, {%3, %4}], [%2];"
    :: "r"(dst), "l"(m), "r"(bar), "r"(c0), "r"(c1) : "memory");
}
__device__ __forceinline__ void tma_load3(uint32_t dst, const CUtensorMap* m, uint32_t bar, int c1, int c2) {
  asm volatile("cp.async.bulk.tensor.3d.shared::cluster.global.mbarrier::complete_tx::bytes [%0], [%1, {%5, %3, %4}], [%2];"
    :: "r"(dst), "l"(m), "r"(bar), "r"(c1), "r"(c2), "r"(0) : "memory");
}
__device__ __forceinline__ void tma_prefetch3(const CUtensorMap* m, int c1, int c2) {
  asm volatile("cp.async.bulk.prefetch.tensor.3d.L2.global [%0, {%3, %1, %2}];" :: "l"(m), "r"(c1), "r"(c2), "r"(0) : "memory");
}
__device__ __forceinline__ void tma_prefetch(const CUtensorMap* m, int c0, int c1) {
  asm volatile("cp.async.bulk.prefetch.tensor.2d.L2.global [%0, {%1, %2}];" :: "l"(m), "r"(c0), "r"(c1) : "memory");
}
__device__ __forceinline__ void tma_store(const CUtensorMap* m, uint32_t src, int c0, int c1) {
  asm volatile("cp.async.bulk.tensor.2d.global.shared::cta.bulk_group [%0, {%2, %3}], [%1];" :: "l"(m), "r"(src), "r"(c0), "r"(c1) : "memory");
}
__device__ __forceinline__ void bulk_load(uint32_t dst, const void* src, uint32_t bytes, uint32_t bar) {
  asm volatile("cp.async.bulk.shared::cluster.global.mbarrier::complete_tx::bytes [%0], [%1], %2, [%3];" :: "r"(dst), "l"(src), "r"(bytes), "r"(bar) : "memory");
}
__device__ __forceinline__ void bulk_reduce(void* dst, uint32_t src, uint32_t bytes) {
  asm volatile("cp.reduce.async.bulk.global.shared::cta.bulk_group.add.noftz.bf16 [%0], [%1], %2;" :: "l"(dst), "r"(src), "r"(bytes) : "memory");
}
__device__ __forceinline__ void prefetch_map(const CUtensorMap* m) { asm volatile("prefetch.tensormap [%0];" :: "l"(m) : "memory"); }
__device__ __forceinline__ bool elect_one() {
  uint32_t p;
  asm volatile("{\n.reg .pred P;\nelect.sync _|P, 0xffffffff;\nselp.u32 %0, 1, 0, P;\n}" : "=r"(p));
  return p;
}
__device__ __forceinline__ void wg_fence() { asm volatile("wgmma.fence.sync.aligned;" ::: "memory"); }
__device__ __forceinline__ void wg_commit() { asm volatile("wgmma.commit_group.sync.aligned;" ::: "memory"); }
template <int N> __device__ __forceinline__ void wg_wait() { asm volatile("wgmma.wait_group.sync.aligned %0;" :: "n"(N) : "memory"); }
template <int N> __device__ __forceinline__ void zero(float (&r)[N]) {
#pragma unroll
  for (int i = 0; i < N; i++) r[i] = 0.f;
}
template <int N> __device__ __forceinline__ void pin(float (&r)[N]) {
#pragma unroll
  for (int i = 0; i < N; i++) asm volatile("" : "+f"(r[i]) :: "memory");
}
template <int N> __device__ __forceinline__ void pinr(uint32_t (&r)[N][4]) {
#pragma unroll
  for (int i = 0; i < N; i++) asm volatile("" : "+r"(r[i][0]), "+r"(r[i][1]), "+r"(r[i][2]), "+r"(r[i][3]) :: "memory");
}
__device__ __forceinline__ void fence_async_smem() { asm volatile("fence.proxy.async.shared::cta;" ::: "memory"); }
__device__ __forceinline__ void fence_async_global() { asm volatile("fence.proxy.async.global;" ::: "memory"); }
__device__ __forceinline__ void bar_sync(int id, int n) { asm volatile("bar.sync %0, %1;" :: "r"(id), "r"(n) : "memory"); }
__device__ __forceinline__ void bar_arrive(int id, int n) { asm volatile("bar.arrive %0, %1;" :: "r"(id), "r"(n) : "memory"); }
__device__ __forceinline__ void warp_arrive(uint32_t bar, int lane) { __syncwarp(); if (lane == 0) mbar_arrive(bar); }
__host__ __device__ constexpr uint64_t make_desc(uint32_t addr, uint32_t lbo, uint32_t sbo, uint32_t swz) {
  return (uint64_t)((addr & 0x3FFFF) >> 4) | ((uint64_t)((lbo & 0x3FFFF) >> 4) << 16) | ((uint64_t)(sbo >> 4) << 32) | ((uint64_t)swz << 62);
}
__device__ __forceinline__ uint32_t pack2(float lo, float hi) {
  uint32_t r; asm("cvt.rn.bf16x2.f32 %0, %1, %2;" : "=r"(r) : "f"(hi), "f"(lo)); return r;
}
__device__ __forceinline__ float bf_lo(uint32_t v) { return __uint_as_float(v << 16); }
__device__ __forceinline__ float bf_hi(uint32_t v) { return __uint_as_float(v & 0xffff0000u); }
__device__ __forceinline__ float ex2(float x) { float r; asm("ex2.approx.ftz.f32 %0, %1;" : "=f"(r) : "f"(x)); return r; }
__device__ __forceinline__ float rcp(float x) { float r; asm("rcp.approx.ftz.f32 %0, %1;" : "=f"(r) : "f"(x)); return r; }
constexpr float LOG2E = 1.4426950408889634f;
__device__ __forceinline__ float sigmoidf(float x) { return rcp(1.0f + ex2(-LOG2E * x)); }
__device__ __forceinline__ void sts128(uint32_t a, uint32_t x, uint32_t y, uint32_t z, uint32_t w) {
  asm volatile("st.shared.v4.u32 [%0], {%1,%2,%3,%4};" :: "r"(a), "r"(x), "r"(y), "r"(z), "r"(w) : "memory");
}
__device__ __forceinline__ void lds128(uint32_t a, uint32_t (&r)[4]) {
  asm volatile("ld.shared.v4.u32 {%0,%1,%2,%3}, [%4];" : "=r"(r[0]), "=r"(r[1]), "=r"(r[2]), "=r"(r[3]) : "r"(a) : "memory");
}
__device__ __forceinline__ void sts32(uint32_t a, uint32_t v) { asm volatile("st.shared.u32 [%0], %1;" :: "r"(a), "r"(v) : "memory"); }
__device__ __forceinline__ uint32_t lds32(uint32_t a) { uint32_t v; asm volatile("ld.shared.u32 %0, [%1];" : "=r"(v) : "r"(a) : "memory"); return v; }
__device__ __forceinline__ float ldsf(uint32_t a) { return __uint_as_float(lds32(a)); }
__device__ __forceinline__ void stmatrix4(uint32_t a, uint32_t r0, uint32_t r1, uint32_t r2, uint32_t r3) {
  asm volatile("stmatrix.sync.aligned.m8n8.x4.shared.b16 [%0], {%1,%2,%3,%4};" :: "r"(a), "r"(r0), "r"(r1), "r"(r2), "r"(r3) : "memory");
}
__device__ __forceinline__ void ldmatrix4(uint32_t a, uint32_t (&r)[4]) {
  asm volatile("ldmatrix.sync.aligned.m8n8.x4.shared.b16 {%0,%1,%2,%3}, [%4];" : "=r"(r[0]), "=r"(r[1]), "=r"(r[2]), "=r"(r[3]) : "r"(a) : "memory");
}
__device__ __forceinline__ uint4 ldg_nc(const void* p) {
  uint4 v; asm volatile("ld.global.nc.L1::no_allocate.v4.u32 {%0,%1,%2,%3}, [%4];" : "=r"(v.x), "=r"(v.y), "=r"(v.z), "=r"(v.w) : "l"(p)); return v;
}
__device__ __forceinline__ void st_tagged(uint2* p, uint32_t v, uint32_t tag) {
  asm volatile("{\n.reg .b64 x;\nmov.b64 x, {%1, %2};\nst.relaxed.gpu.global.b64 [%0], x;\n}" :: "l"(p), "r"(v), "r"(tag) : "memory");
}
__device__ __forceinline__ uint2 ld_tagged(const uint2* p) {
  uint2 v; asm volatile("{\n.reg .b64 x;\nld.relaxed.gpu.global.b64 x, [%2];\nmov.b64 {%0, %1}, x;\n}" : "=r"(v.x), "=r"(v.y) : "l"(p) : "memory"); return v;
}
__device__ __forceinline__ void probe(const uint2* p, uint32_t tag, int& budget) {
  do { __nanosleep(POLL0); budget -= 16; } while (!__all_sync(0xffffffffu, ld_tagged(p).y == tag) && budget > 0);
}
template <int STRIDE, int N>
__device__ __forceinline__ void gather(const uint2* p, uint32_t tag, float& s0, float& s1, int& budget) {
  uint32_t pause = 0;
  bool again;
#pragma unroll 1
  do {
    __nanosleep(pause);
    pause = POLL0;
    uint32_t bad = 0;
    s0 = s1 = 0.f;
#pragma unroll
    for (int i = 0; i < N; i++) {
      const uint2 w = ld_tagged(p + i * STRIDE);
      bad |= w.y ^ tag;
      if (i < N / 2) s0 += __uint_as_float(w.x); else s1 += __uint_as_float(w.x);
    }
    budget -= 16;
    again = __any_sync(0xffffffffu, bad != 0) && budget > 0;
  } while (again);
}
__device__ __forceinline__ void sts16(uint32_t a, uint32_t v) { asm volatile("st.shared.u16 [%0], %1;" :: "r"(a), "h"((uint16_t)v) : "memory"); }
__device__ __forceinline__ void signal_add(uint32_t* p, uint32_t v) { asm volatile("red.release.gpu.global.add.u32 [%0], %1;" :: "l"(p), "r"(v) : "memory"); }
__device__ __forceinline__ float qmax(float v) { v = fmaxf(v, __shfl_xor_sync(0xffffffffu, v, 1)); return fmaxf(v, __shfl_xor_sync(0xffffffffu, v, 2)); }
__device__ __forceinline__ float qsum(float v) { v += __shfl_xor_sync(0xffffffffu, v, 1); return v + __shfl_xor_sync(0xffffffffu, v, 2); }
__device__ __forceinline__ float fold(float a, float b, bool hi, int m) { return (hi ? b : a) + __shfl_xor_sync(0xffffffffu, hi ? a : b, m); }

__device__ __forceinline__ void yield_slot() { asm volatile("pmevent 0;" ::: "memory"); }
__device__ __forceinline__ float fma_v(float a, float b, float c) { float r; asm volatile("fma.rn.f32 %0, %1, %2, %3;" : "=f"(r) : "f"(a), "f"(b), "f"(c)); return r; }
constexpr uint32_t EXP_TOP = 0x58805880u;
__device__ __forceinline__ void exp_plain(const float (&p)[16], float (&ep)[16], float (&em)[16]) {
#pragma unroll
  for (int i = 0; i < 16; i++) { ep[i] = ex2(p[i]); em[i] = ex2(-p[i]); }
}
__device__ __forceinline__ void exp_shifted(const float (&p)[16], float sgn, float (&e)[16]) {
#pragma unroll
  for (int i = 0; i < 16; i++) e[i] = sgn * p[i];
#pragma unroll
  for (int o = 0; o < 4; o += 2) {
    const float mx = qmax(fmaxf(fmaxf(fmaxf(e[o], e[o + 1]), fmaxf(e[o + 4], e[o + 5])), fmaxf(fmaxf(e[o + 8], e[o + 9]), fmaxf(e[o + 12], e[o + 13]))));
#pragma unroll
    for (int c = 0; c < 4; c++) { e[4 * c + o] = ex2(e[4 * c + o] - mx); e[4 * c + o + 1] = ex2(e[4 * c + o + 1] - mx); }
  }
}
__device__ __forceinline__ void pack_sums(const float (&e)[16], uint32_t (&pk)[2][4], float (&s)[2]) {
#pragma unroll
  for (int i = 0; i < 8; i++) pk[i >> 2][i & 3] = pack2(e[2 * i], e[2 * i + 1]);
#pragma unroll
  for (int o = 0; o < 4; o += 2) s[o >> 1] = ((e[o] + e[o + 1]) + (e[o + 4] + e[o + 5])) + ((e[o + 8] + e[o + 9]) + (e[o + 12] + e[o + 13]));
}
__device__ __forceinline__ uint32_t rcp2(float s) { const float r = rcp(s); return pack2(r, r); }
__device__ __forceinline__ uint32_t add2(uint32_t a, uint32_t b) { uint32_t r; asm("add.rn.bf16x2 %0, %1, %2;" : "=r"(r) : "r"(a), "r"(b)); return r; }
__device__ __forceinline__ uint32_t mul2(uint32_t a, uint32_t b) { uint32_t r; asm("mul.rn.bf16x2 %0, %1, %2;" : "=r"(r) : "r"(a), "r"(b)); return r; }
__device__ __forceinline__ void store_phi(uint32_t a, const uint32_t (&pk)[2][4], uint32_t r0, uint32_t r1) {
#pragma unroll
  for (int h = 0; h < 2; h++) stmatrix4(a ^ (h * 32), mul2(pk[h][0], r0), mul2(pk[h][1], r1), mul2(pk[h][2], r0), mul2(pk[h][3], r1));
}
__device__ __forceinline__ uint32_t exp_frags(const float (&p)[16], uint32_t (&ef)[4][4], uint32_t top) {
  float ep[16], em[16];
  exp_plain(p, ep, em);
#pragma unroll
  for (int s = 0; s < 2; s++)
#pragma unroll
    for (int r = 0; r < 4; r++) {
      ef[s][r] = pack2(ep[8 * s + 2 * r], ep[8 * s + 2 * r + 1]);
      ef[2 + s][r] = pack2(em[8 * s + 2 * r], em[8 * s + 2 * r + 1]);
    }
#pragma unroll
  for (int s = 0; s < 4; s++) top = __vimax3_u16x2(__vimax3_u16x2(top, ef[s][0], ef[s][1]), ef[s][2], ef[s][3]);
  return top;
}
__device__ __forceinline__ void issue_pq(float (&p)[4][16], const uint32_t (&qf)[4][2][4], uint64_t dw, int accumulate) {
  wg_fence();
#pragma unroll
  for (int h = 0; h < 4; h++) {
    wgmma_m64n32k16_rs<1>(p[h], qf[h][0], dw + h * 128, accumulate);
    wgmma_m64n32k16_rs<1>(p[h], qf[h][1], dw + h * 128 + 64, 1);
  }
  wg_commit();
}

#define SPLIT_BATCH 2
__device__ __forceinline__ void mainloop128(float (&acc)[2][64], uint64_t da0, uint64_t db0, uint32_t slot, uint32_t ph, int steps, bool lane0, int& budget, int cta, int n0) {
  uint32_t prev = 0;
#pragma unroll 1
  for (int k = 0; k < steps; k++) {
    mbar_wait(bars + B_FX * 8 + slot * 8, ph, budget);
    const uint64_t da = da0 + slot * (STAGE >> 4), db = db0 + slot * (STAGE >> 4);
#pragma unroll
    for (int kk = 0; kk < 4; kk++) {
      if (SPLIT_BATCH == 2 || !(kk & 1)) {
        wg_wait<1>();
        if (kk == 3 - SPLIT_BATCH && k > 0 && lane0) mbar_arrive_n(bars + B_EM * 8 + prev * 8, 2);
        wg_fence();
      }
      wgmma_m64n128k16_ss<0, 1>(acc[0], da + kk * 2, db + kk * 128, kk ? 1 : k);
      wgmma_m64n128k16_ss<0, 1>(acc[1], da + 512 + kk * 2, db + kk * 128, kk ? 1 : k);
      if (SPLIT_BATCH == 2 || (kk & 1)) wg_commit();
    }
    prev = slot;
    if (++slot == NST) { slot = 0; ph ^= 1; }
  }
}
__device__ __forceinline__ void kstep64(float (&acc)[64], uint64_t da, uint64_t db, int accumulate) {
  wg_fence();
#pragma unroll
  for (int kk = 0; kk < 4; kk++) wgmma_m64n128k16_ss<0, 1>(acc, da + kk * 2, db + kk * 128, kk ? 1 : accumulate);
  wg_commit();
}
__device__ __forceinline__ void issue_kv(float (&kv)[20], uint64_t dphi, uint64_t dv, int accumulate) {
  wg_fence();
#pragma unroll
  for (int ks = 0; ks < 4; ks++)
    wgmma_m64n40k16_ss<1, 1>(kv, dphi + ks * 128, dv - (uint64_t)ks * ((64ull << 16) - 64ull), ks ? 1 : accumulate);
  wg_commit();
}
__device__ __forceinline__ void load_x(uint32_t sx, uint32_t (&xf)[8][4]) {
#pragma unroll
  for (int u = 0; u < 8; u++) ldmatrix4((sx ^ ((u & 3) * 32)) + (u >> 2) * 16384, xf[u]);
}
__device__ __forceinline__ uint32_t moe_buf(uint32_t b) { return b == 2 ? SM_V + 8192 : SM_MOE + b * 8192; }
template <bool DOWN>
__device__ __forceinline__ void moe_chunks(float (&a)[4], int n, uint32_t& buf, uint32_t& ph, uint64_t da0, uint64_t db, bool lane0) {
  int budget = BUDGET;
  zero(a);
#pragma unroll 1
  for (int c = 0; c < n; c++) {
    mbar_wait(bars + B_MF * 8 + buf * 8, ph, budget);
    const uint64_t da = da0 + (moe_buf(buf) >> 4);
    wg_fence();
#pragma unroll
    for (int j = 0; j < 4; j++) wgmma_m64n8k16_ss<1, 0>(a, da + j * 128, DOWN ? db - j : db + j * 2, 1);
    wg_commit();
    wg_wait<0>();
    if (lane0) mbar_arrive(bars + B_ME * 8 + buf * 8);
    db += DOWN ? 16 : 8;
    if (++buf >= (DOWN ? 2 : 3)) { buf = 0; ph ^= 1; }
  }
  pin(a);
}
constexpr uint64_t DV_TILE = 4 * ((64ull << 16) - 64ull);

template <bool BY_SM>
__global__ void __launch_bounds__(512, 1)
fused_kernel(const __grid_constant__ CUtensorMap mx, const __grid_constant__ CUtensorMap mw, const __grid_constant__ CUtensorMap mwo,
             const __grid_constant__ CUtensorMap mo, const __grid_constant__ CUtensorMap mout, const __grid_constant__ CUtensorMap mxr,
             const __grid_constant__ CUtensorMap mg, const __grid_constant__ CUtensorMap mu, const __grid_constant__ CUtensorMap md, const Params P) {
  extern __shared__ __align__(1024) uint8_t smem_raw[];
  if (smem_u32(smem_raw) != sb) return;
  const int tid = threadIdx.x, lane = tid & 31;
  if (tid == 256) TS(1);
  const int warp = __shfl_sync(0xffffffffu, tid >> 5, 0), wg = warp >> 2;
  int budget = BUDGET;
  if (warp == 10 && elect_one()) { prefetch_map(&mx); prefetch_map(&mw); }
  int cta;
  {
    uint32_t smid;
    asm volatile("mov.u32 %0, %%smid;" : "=r"(smid));
    if (!BY_SM) cta = blockIdx.x;
    else if (smid < 64) cta = ((smid >> 1) & 7) * 16 + (smid >> 4) * 2 + (smid & 1);
    else if (smid < 120) { const int t = (smid - 64) >> 1, d = (t * 37) >> 8; cta = (1 + t - d * 7) * 16 + 8 + d * 2 + (smid & 1); }
    else cta = smid < 124 ? smid + 8 : smid - 116;
  }
  if (cta >= 128) {
    if (tid == 0) {
      const uint32_t old = atomicAdd(&g_cnt[C_START], 32u);
      wait_count<500>(&g_cnt[C_START], (old & ~255u) + 256u, budget);
    }
    return;
  }
  const int bi = (cta >> 5) * 4 + ((cta >> 2) & 3);
  const int bj = ((cta >> 4) & 1) * 4 + (cta & 3);

  if (wg == 3) {
    asm volatile("setmaxnreg.dec.sync.aligned.u32 64;");
    const int t3 = tid - 384, w3 = warp - 12;
    if (t3 == 0) TSG(0);
    if (t3 < 80) *reinterpret_cast<uint4*>(&g_kvr[cta * 320 + t3 * 4]) = make_uint4(0, 0, 0, 0);
    if (t3 < 17) st_tagged(t3 < 16 ? &g_gate[bi * 128 + bj * 16 + t3] : &g_key[cta], 0, 1);
    bar_sync(0, 512);
#pragma unroll 1
    for (int u = 0; u < 4; u++) {
      const uint4 v = ldg_nc(P.w_phi + bj * 4096 + (u * 128 + t3) * 8);
      sts128(sb + SM_WPHI + u * 2048 + (t3 >> 2) * 64 + (((t3 & 3) ^ ((t3 >> 3) & 3)) << 4),
             pack2(LOG2E * bf_lo(v.x), LOG2E * bf_hi(v.x)), pack2(LOG2E * bf_lo(v.y), LOG2E * bf_hi(v.y)),
             pack2(LOG2E * bf_lo(v.z), LOG2E * bf_hi(v.z)), pack2(LOG2E * bf_lo(v.w), LOG2E * bf_hi(v.w)));
    }
    fence_async_smem();
    warp_arrive(bars + B_WPHI * 8, lane);
    bar_sync(6, 256);
    const uint32_t target = lds32(sb + SM_MISC);
    uint32_t key;
    {
      uint32_t kk[4];
      lds128(sb + SM_MISC + 16, kk);
      if (t3 == 0) st_tagged(&g_key[cta], max(max(kk[0], kk[1]), max(kk[2], kk[3])), target);
      uint2 k, gv;
      __nanosleep(POLLR);
      do {
        __nanosleep(POLL1);
        k = ld_tagged(&g_key[t3]);
        gv = ld_tagged(&g_gate[bi * 128 + t3]);
        budget -= 4;
      } while (!__all_sync(0xffffffffu, k.y == target && gv.y == target) && budget > 0);
      key = __reduce_max_sync(0xffffffffu, k.x);
      if (lane == 0) sts32(sb + SM_MISC + 32 + w3 * 4, key);
      sts32(sb + SM_G + t3 * 4, gv.x);
      bar_sync(5, 128);
      lds128(sb + SM_MISC + 32, kk);
      key = max(max(kk[0], kk[1]), max(kk[2], kk[3]));
    }
    const int idx = (0xFFFF - (key & 0xFFFF)) & (kS - 1);
    if (t3 == 0) { sts32(sb + SM_MISC + 4, idx); TS(8); }
    warp_arrive(bars + B_INFO * 8, lane);
    {
      const uint4 v = ldg_nc(P.x + (size_t)idx * kD + t3 * 8);
      sts128(sb + SM_BAND + t3 * 16, v.x, v.y, v.z, v.w);
    }
    const int t2 = (lane & 3) * 2, row = w3 * 16 + (lane >> 2);
    float a[4];
    uint32_t buf = 0, ph = 0;
    fence_async_smem();
    bar_sync(5, 128);
    {
      const int r = cta >> 4;
#pragma unroll 1
      for (int part = 0; part < 2; part++) {
        const int n = part ? 14 - 2 * r : 2 * r;
        moe_chunks<false>(a, n, buf, ph, P.da, P.dxs + (part ? 0 : (16 - n) * 8), lane == 0);
        uint2* dst = &g_pre[(((cta >> 2) & 2) + 1 - part) * kF + ((r - 1 + part) * 8 + (cta & 7)) * 64 + row];
        if (t2 == 0 && n) { st_tagged(dst, __float_as_uint(a[0]), target); st_tagged(dst + 8, __float_as_uint(a[2]), target); }
      }
    }
    if (t3 == 0) TS(9);
    bar_sync(5, 128);
    sts128(sb + SM_BAND + t3 * 16, 0, 0, 0, 0);
    {
      __nanosleep(POLL0);
      float gs, us;
      gather<kF, 4>(&g_pre[(cta >> 2) * 112 + min(t3, 111)], target, gs, us, budget);
      bar_sync(5, 128);
      if (t3 < 112) sts16(sb + SM_BAND + 112 + (t3 >> 3) * 128 + (t3 & 7) * 2, pack2(gs * sigmoidf(gs) * us, 0.f));
    }
    fence_async_smem();
    bar_sync(5, 128);
    if (t3 == 0) TS(12);
    moe_chunks<true>(a, 7, buf, ph, P.da, P.dband + 7, lane == 0);
    if (t3 == 0) TS(10);
    if (t2 < 4) {
      uint2* dst = &g_yp[(cta >> 2) * kD + (cta & 3) * 256 + t2 * 64 + row];
      st_tagged(dst, __float_as_uint(a[0]), target); st_tagged(dst + 8, __float_as_uint(a[2]), target);
      st_tagged(dst + 64, __float_as_uint(a[1]), target); st_tagged(dst + 72, __float_as_uint(a[3]), target);
    }
    if (lane == 0) mbar_arrive(bars + B_MD * 8);
    if ((idx >> 7) == bi) {
      mbar_wait(bars + (B_PUB + 3) * 8, 0, budget);
      if (w3 == 0) probe(&g_yp[lane * kD + bj * 128], target, budget);
      bar_sync(5, 128);
      float y = 0.f;
#pragma unroll 1
      for (int hf = 0; hf < 2; hf++) {
        float y0, y1;
        gather<kD, 16>(&g_yp[hf * 16 * kD + bj * 128 + t3], target, y0, y1, budget);
        y += y0 + y1;
      }
      const uint32_t ob = key >> 16;
      const float upd = y * sigmoidf(__uint_as_float(((ob & 0x8000u) ? (ob ^ 0x8000u) : (~ob & 0xFFFFu)) << 16));
      const uint32_t a = sb + SM_PHI + (t3 >> 6) * 16384 + (idx & 127) * 128 + ((((t3 >> 3) & 7) ^ (idx & 7)) << 4) + (t3 & 7) * 2;
      mbar_wait(bars + B_XT * 8, 0, budget);
      uint16_t xb;
      asm volatile("ld.shared.u16 %0, [%1];" : "=h"(xb) : "r"(a) : "memory");
      sts16(a, pack2(bf_lo(xb) + upd, 0.f));
      warp_arrive(bars + B_XP * 8, lane);
      if (t3 == 0) TS(11);
    }
  } else if (wg < 2) {
    if ((warp & 3) < EARLY_N && lane < (wg ? 8 : 16)) {
      const int n = warp & 3;
      const __nv_bfloat16* p = wg ? P.w + (size_t)(n * 64 + bi + (lane >> 1) * 16) * (3 * kD) + 1024 + (lane & 1) * 1024 + bj * 128
                                  : P.x + (size_t)(bi * 128 + bj * 16 + lane) * kD + n * 64;
      if (n) __nanosleep(n * EARLY_GAP);
      asm volatile("prefetch.global.L2 [%0];" :: "l"(p));
    }
    __syncwarp();
    asm volatile("setmaxnreg.inc.sync.aligned.u32 208;");
    const int tw = tid & 127, w = warp & 3, g = lane >> 2, t = lane & 3;
    const bool lane0 = lane == 0;
    if (wg == 0) sts128(sb + SM_ONE + (tw & 63) * 16, 0x3f803f80u, 0x3f803f80u, 0x3f803f80u, 0x3f803f80u);
    bar_sync(0, 512);
    if (wg == 1) {
      float sr[4], sg[4];
      zero(sr); zero(sg);
#pragma unroll 1
      for (int c = 0; c < 4; c++) {
        mbar_wait(bars + (B_RX + c) * 8, 0, budget);
        uint32_t rs[4], gs[4], xs[4][4];
        lds128(sb + SM_V + c * 512 + lane * 16, rs);
        lds128(sb + SM_V + 2048 + c * 512 + lane * 16, gs);
#pragma unroll
        for (int r = 0; r < 4; r++) lds128(sb + SM_PHI + c * 8192 + (w * 4 + r) * 512 + lane * 16, xs[r]);
#pragma unroll
        for (int e = 0; e < 4; e++) {
          const float r0 = bf_lo(rs[e]), r1 = bf_hi(rs[e]), g0 = bf_lo(gs[e]), g1 = bf_hi(gs[e]);
#pragma unroll
          for (int r = 0; r < 4; r++) {
            const float x0 = bf_lo(xs[r][e]), x1 = bf_hi(xs[r][e]);
            sr[r] = fma_v(x0, r0, sr[r]); sg[r] = fma_v(x0, g0, sg[r]);
            sr[r] = fma_v(x1, r1, sr[r]); sg[r] = fma_v(x1, g1, sg[r]);
            if (r != 1) yield_slot();
          }
        }
      }
      fence_async_smem();
      __syncwarp();
      if (lane < 3) mbar_arrive(bars + (B_ME + lane) * 8);
      const bool b4 = lane & 16, b3 = lane & 8, b2 = lane & 4;
      const float v = qsum(fold(fold(fold(sr[0], sg[0], b4, 16), fold(sr[2], sg[2], b4, 16), b3, 8),
                                fold(fold(sr[1], sg[1], b4, 16), fold(sr[3], sg[3], b4, 16), b3, 8), b2, 4));
      const int row = bi * 128 + bj * 16 + w * 4 + (g & 3);
      const uint32_t rb = pack2(v + 0.f, 0.f);
      const uint32_t ob = (rb & 0x8000u) ? (~rb & 0xFFFFu) : (rb | 0x8000u);
      const uint32_t best = __reduce_max_sync(0xffffffffu, b4 ? 0u : (ob << 16) | (0xFFFFu - row));
      mbar_wait(bars + B_EPOCH * 8, 0, budget);
      const uint32_t tag = lds32(sb + SM_MISC);
      if (lane0) sts32(sb + SM_MISC + 16 + w * 4, best);
      if (b4 && t == 0) st_tagged(&g_gate[row], __float_as_uint(sigmoidf(v)), tag);
      if (tw == 0) TS(14);
      bar_arrive(6, 256);
      bar_sync(1, 256);
    }

    {
      float acc[2][64];
      if (tw == 0) TS(16 + wg * 16);
      mainloop128(acc, P.da, P.db, wg, wg, 16, lane0, budget, cta, wg * 16);
      bar_sync(1 + wg, 256);
      wg_wait<0>();
      pin(acc[0]); pin(acc[1]);
      if (lane0) mbar_arrive_n(bars + (B_EM + wg) * 8, 2);
      if (tw == 0) TS(17 + wg * 16);
      float p[4][16];
      uint32_t vp[8][4];
      const uint32_t av = sb + SM_V + (w * 16 + g) * 64 + ((t ^ (g >> 1)) << 4);
      {
        uint32_t kf[4][2][4];
#pragma unroll
        for (int u = 0; u < 4; u++)
#pragma unroll
          for (int s = 0; s < 2; s++)
#pragma unroll
            for (int r = 0; r < 4; r++) kf[u][s][r] = pack2(acc[u & 1][16 * (u >> 1) + 8 * s + 2 * r], acc[u & 1][16 * (u >> 1) + 8 * s + 2 * r + 1]);
        mbar_wait(bars + B_WPHI * 8, 0, budget);
        const uint64_t dw = P.dw + wg * 256;
        wg_fence();
#pragma unroll
        for (int u = 0; u < 4; u++) {
          wgmma_m64n32k16_rs<1>(p[u], kf[u][0], dw + (u >> 1) * 128, 0);
          wgmma_m64n32k16_rs<1>(p[u], kf[u][1], dw + (u >> 1) * 128 + 64, 1);
        }
        wg_commit();
#pragma unroll
        for (int u = 0; u < 8; u++) {
          const float* a = &acc[(u >> 1) & 1][32 + 16 * (u >> 2) + 2 * (u & 1)];
          vp[u][0] = pack2(a[0], a[1]); vp[u][1] = pack2(a[4], a[5]); vp[u][2] = pack2(a[8], a[9]); vp[u][3] = pack2(a[12], a[13]);
          if (u < 4) sts128(av + (u >> 1) * 4096 + (u & 1) * 512, vp[u][0], vp[u][1], vp[u][2], vp[u][3]);
        }
        pinr(vp);
        wg_wait<0>();
#pragma unroll
        for (int u = 0; u < 4; u++) pin(p[u]);
      }
      if (tw == 0) TS(18 + wg * 16);
      float kv[2][20];
      {
        const uint32_t sphi = sb + SM_PHI + (w * 16 + (lane & 15)) * 128 + (((lane >> 4) ^ (lane & 7)) << 4);
        uint32_t top = EXP_TOP;
        uint32_t pk[4][2][4];
        float ps[2];
        uint32_t sh[1][4];
        uint32_t redo = 0, redo0 = 0;
        const uint32_t astage = sb + (w * 16 + (lane & 15)) * 64 + (((lane >> 4) ^ ((lane >> 1) & 3)) << 4);
        auto stage_kv = [&](int hh) {
#pragma unroll
          for (int q = 0; q < 2; q++) {
            const float* a = &kv[hh][8 * q];
            stmatrix4((astage ^ (q * 32)) + (hh ? SM_PHI : SM_Z), pack2(a[0], a[1]), pack2(a[2], a[3]), pack2(a[4], a[5]), pack2(a[6], a[7]));
          }
        };
#pragma unroll
        for (int i = 0; i < 11; i++) {
          if (i >= 3) {
            const int j = i - 3;
            const uint32_t s2 = add2(sh[0][2], sh[0][3]);
            top = __vmaxu2(top, s2);
            store_phi((sphi ^ ((j & 1) * 64)) + (j & 2) * 4096, pk[j & 3], rcp2(bf_lo(s2)), rcp2(bf_hi(s2)));
          }
          if (i >= 2 && i <= 9) { sh[0][2] = add2(sh[0][0], sh[0][1]); sh[0][3] = __shfl_xor_sync(0xffffffffu, sh[0][2], 2); }
          if (i >= 1 && i <= 8) { sh[0][0] = pack2(ps[0], ps[1]); sh[0][1] = __shfl_xor_sync(0xffffffffu, sh[0][0], 1); }
          if (i == 1) sh[0][2] = sh[0][3] = 0;
          if (i < 8) {
            pin(p[i >> 1]);
            float e[16];
#pragma unroll
            for (int c = 0; c < 16; c++) e[c] = ex2((i & 1) ? -p[i >> 1][c] : p[i >> 1][c]);
            pack_sums(e, pk[i & 3], ps);
            pinr(pk[i & 3]); pin(ps);
          }
          if (i < 10) yield_slot();
          if (i >= 1 && i <= 9) pinr(sh);
          if (i == 7) { wg_wait<0>(); pin(kv[0]); stage_kv(0); }
          if (i == 2 && wg) mbar_wait(bars + B_RD * 8, 0, budget);
          if (i >= 4 && !(i & 1)) {
            const int u = (i - 4) >> 1;
            fence_async_smem();
            wg_wait<0>();
            if (!(u & 1)) bar_sync(7 + wg, 128);
            else asm volatile("{\n.reg .pred p, q;\nsetp.ne.b32 p, %2, %3;\nbar.red.or.pred q, %1, 128, p;\nselp.u32 %0, 1, 0, q;\n}"
                              : "=r"(redo) : "r"(7 + wg), "r"(top), "n"(EXP_TOP) : "memory");
            if (u == 1) redo0 = redo;
            if (u == 2 && lane0 && !redo0) mbar_arrive(bars + (B_RH + wg) * 8);
            issue_kv(kv[u >> 1], P.dphi + (u & 1) * 512, P.dv - (u & 1) * DV_TILE, u & 1);
            if (u == 1 || u == 2) {
#pragma unroll
              for (int r = 0; r < 2; r++) sts128(av + ((u + 1) & 1) * 4096 + r * 512, vp[2 * u + 2 + r][0], vp[2 * u + 2 + r][1], vp[2 * u + 2 + r][2], vp[2 * u + 2 + r][3]);
            }
            if (u < 3) yield_slot();
          }
        }
        if (tw == 0) TS(19 + wg * 16);
        wg_wait<0>();
        pin(kv[0]); pin(kv[1]);
        if (__builtin_expect(__any_sync(0xffffffffu, redo), 0)) {
#pragma unroll 1
          for (int u = 0; u < 4; u++) {
            bar_sync(7 + wg, 128);
#pragma unroll 1
            for (int sg = 0; sg < 2; sg++) {
              float e[16];
              exp_shifted(p[0], sg ? -1.f : 1.f, e);
              pack_sums(e, pk[0], ps);
              store_phi(sphi ^ (sg * 64), pk[0], rcp2(qsum(ps[0])), rcp2(qsum(ps[1])));
            }
            sts128(av, vp[0][0], vp[0][1], vp[0][2], vp[0][3]);
            sts128(av + 512, vp[1][0], vp[1][1], vp[1][2], vp[1][3]);
            fence_async_smem();
            bar_sync(7 + wg, 128);
            issue_kv(kv[1], P.dphi, P.dv, u & 1);
            wg_wait<0>();
            pin(kv[1]);
#pragma unroll
            for (int c = 0; c < 16; c++) { p[0][c] = p[1][c]; p[1][c] = p[2][c]; p[2][c] = p[3][c]; }
#pragma unroll
            for (int c = 0; c < 24; c++) vp[c >> 2][c & 3] = vp[(c >> 2) + 2][c & 3];
            if (u == 1) {
#pragma unroll
              for (int c = 0; c < 20; c++) kv[0][c] = kv[1][c];
            }
          }
          if (__any_sync(0xffffffffu, redo0)) {
            stage_kv(0);
            fence_async_smem();
            warp_arrive(bars + (B_RH + wg) * 8, lane);
          }
        }
        if (tw == 0) TS(20 + wg * 16);
        bar_sync(7 + wg, 128);
        stage_kv(1);
      }
      {
        const uint32_t z = pack2(t == 0 ? kv[0][16] : t == 1 ? kv[1][16] : t == 2 ? kv[0][18] : kv[1][18], 0.0625f);
        sts128(sb + SM_PHI + 4096 + ((w & 1) * 16 + (t >> 1) * 8 + g) * 64 + ((((w & 2) + (t & 1)) ^ (g >> 1)) << 4), z, z, z, z);
      }
      fence_async_smem();
      warp_arrive(bars + (B_RED + wg) * 8, lane);
      if (tw == 0) TS(51 + wg * 4);
    }

    uint32_t stash = sb + 3 * STAGE + w * 4096 + lane * 16;
    const int rowl = wg * 64 + w * 16 + g;
    mbar_wait(bars + B_INFO * 8, 0, budget);
    const float gA = ldsf(sb + SM_G + rowl * 4), gB = ldsf(sb + SM_G + rowl * 4 + 32);
    __nv_bfloat16* og = P.o + (size_t)(bi * 128 + rowl) * kD + bj * 128 + t * 8;
    uint32_t own = sb + 3 * STAGE + rowl * 128 + ((t ^ g) << 4);
    uint32_t sx = sb + SM_PHI + (wg * 64 + w * 16 + (lane & 15)) * 128 + (((lane >> 4) ^ (lane & 7)) << 4);
    uint32_t routed = (lds32(sb + SM_MISC + 4) >> 4) == (uint32_t)(bi * 8 + warp);
    asm volatile("" : "+l"(og), "+r"(own), "+r"(stash), "+r"(sx), "+r"(routed));
    {
      float p[4][16];
      uint32_t ef[2][4][4];
      uint32_t qf[4][2][4];
      auto pack_q = [&](const float (&a)[64]) {
#pragma unroll
        for (int i = 0; i < 32; i++) qf[i >> 3][(i >> 2) & 1][i & 3] = pack2(a[2 * i], a[2 * i + 1]);
      };
      if (wg == 0) {
        float acc[2][64];
        bar_sync(2, 256);
        if (tw == 0) TS(22);
        mainloop128(acc, P.da, P.db, 32 % NST, (32 / NST) & 1, 12, lane0, budget, cta, 32);
#pragma unroll
        for (int n = 44; n < 48; n++) {
          mbar_wait(bars + (B_FX + n % NST) * 8, (n / NST) & 1, budget);
          kstep64(acc[0], P.da + (n % NST) * (STAGE >> 4), P.db + (n % NST) * (STAGE >> 4), 1);
          if (n == 47) break;
          wg_wait<1>();
          if (n == 44) {
            if (lane0) mbar_arrive_n(bars + (B_EM + 43 % NST) * 8, 2);
            pin(acc[1]);
            bar_sync(7, 128);
          }
          if (n <= 45) {
#pragma unroll
            for (int u = (n - 44) * 4; u < (n - 43) * 4; u++) {
              const float* a = &acc[1][8 * u];
              sts128(stash + u * 512, pack2(a[0], a[1]), pack2(a[2], a[3]), pack2(a[4], a[5]), pack2(a[6], a[7]));
            }
          }
          if (n == 45) warp_arrive(bars + B_QS * 8, lane);
        }
        bar_sync(13, 256);
        wg_wait<0>();
        pin(acc[0]);
        if (tw == 0) TS(15);
        pack_q(acc[0]);
        issue_pq(p, qf, P.dw, 0);
        wg_wait<0>();
      } else {
        float acc[64];
        mbar_wait(bars + B_QS * 8, 0, budget);
#pragma unroll
        for (int u = 0; u < 8; u++) lds128(stash + u * 512, qf[u >> 1][u & 1]);
        pinr(qf[3]);
        bar_sync(13, 256);
#pragma unroll
        for (int n = 44; n < 48; n++) {
#pragma unroll
          for (int hf = 0; hf < 2; hf++) {
            const uint64_t da = P.da + 512 + (n % NST) * (STAGE >> 4) + hf * 4, db = P.db + (n % NST) * (STAGE >> 4) + hf * 256;
            wg_wait<1>();
            if (hf && n > 44 && lane0) mbar_arrive_n(bars + (B_EM + (n - 1) % NST) * 8, 2);
            wg_fence();
            wgmma_m64n128k16_ss<0, 1>(acc, da, db, n > 44 || hf);
            wgmma_m64n128k16_ss<0, 1>(acc, da + 2, db + 128, 1);
            wg_commit();
          }
          if (n == 46) issue_pq(p, qf, P.dw, 0);
        }
        wg_wait<0>();
        pin(acc);
        if (lane0) { mbar_arrive_n(bars + (B_EM + 47 % NST) * 8, 2); mbar_arrive(bars + B_T3 * 8); }
        if (tw == 0) TS(23);
        pack_q(acc);
        issue_pq(p, qf, P.dw, 1);
        wg_wait<0>();
      }
#pragma unroll
      for (int h = 0; h < 4; h++) pin(p[h]);
      if (tw == 0) TS(24 + wg * 16);

#pragma unroll 1
      for (int pr = 0; pr < 2; pr++) {
        if (YIELD_EXP && pr > wg) bar_sync(11, 256);
        const uint32_t top = exp_frags(p[1], ef[1], exp_frags(p[0], ef[0], EXP_TOP));
        if (YIELD_EXP && pr < wg) { pinr(ef[0]); pinr(ef[1]); bar_arrive(11, 256); }
        if (__builtin_expect(__any_sync(0xffffffffu, top != EXP_TOP), 0)) {
#pragma unroll 1
          for (int u = 0; u < 4; u++) {
            float e[16];
            exp_shifted(p[0], (u & 1) ? -1.f : 1.f, e);
#pragma unroll
            for (int r = 0; r < 4; r++) {
#pragma unroll
              for (int s = 0; s < 6; s++) ef[s >> 2][s & 3][r] = ef[(s + 2) >> 2][(s + 2) & 3][r];
              ef[1][2][r] = pack2(e[2 * r], e[2 * r + 1]);
              ef[1][3][r] = pack2(e[8 + 2 * r], e[8 + 2 * r + 1]);
            }
            if (u & 1) {
#pragma unroll
              for (int e2 = 0; e2 < 16; e2++) p[0][e2] = p[1][e2];
            }
          }
        }
        float np[2][20], nm[2][20];
        mbar_wait(bars + (B_KV + pr) * 8, 0, budget);
        wg_fence();
#pragma unroll
        for (int hh = 0; hh < 2; hh++) {
          const uint64_t dk = P.dkv - (uint64_t)pr * ((384ull << 16) - 512ull) - hh * ((255ull << 16) - 256ull);
          wgmma_m64n40k16_rs<1>(np[hh], ef[hh][0], dk, 0);
          wgmma_m64n40k16_rs<1>(np[hh], ef[hh][1], dk + 64, 1);
          wgmma_m64n40k16_rs<1>(nm[hh], ef[hh][2], dk + 128 - (126ull << 16), 0);
          wgmma_m64n40k16_rs<1>(nm[hh], ef[hh][3], dk + 192 - (126ull << 16), 1);
          wg_commit();
        }
#pragma unroll
        for (int hh = 0; hh < 2; hh++) {
          if (hh == 0) wg_wait<1>(); else wg_wait<0>();
          pin(np[hh]); pin(nm[hh]);
          uint32_t o[2][4];
#pragma unroll
          for (int r = 0; r < 2; r++) {
            const float dp = np[hh][16 + 2 * r], sp = np[hh][17 + 2 * r], dm = nm[hh][16 + 2 * r], sm = nm[hh][17 + 2 * r];
            const float inv = (r == 0 ? gA : gB) * rcp(fmaf(dp, sm, fmaf(1e-6f, sm, dm) * sp));
            const float cp = sm * inv, cm = sp * inv;
#pragma unroll
            for (int c = 0; c < 4; c++)
              o[r][c] = pack2(fmaf(np[hh][4 * c + 2 * r], cp, nm[hh][4 * c + 2 * r] * cm), fmaf(np[hh][4 * c + 2 * r + 1], cp, nm[hh][4 * c + 2 * r + 1] * cm));
            sts128((own ^ (hh * 64)) + r * 1024, o[r][0], o[r][1], o[r][2], o[r][3]);
          }
          if (hh == 1 && pr == 1) fence_async_smem();
#pragma unroll
          for (int r = 0; r < 2; r++) asm volatile("st.global.v4.u32 [%0], {%1,%2,%3,%4};" :: "l"(og + r * 8 * kD + hh * 32), "r"(o[r][0]), "r"(o[r][1]), "r"(o[r][2]), "r"(o[r][3]) : "memory");
        }
        warp_arrive(bars + (B_PUB + wg * 2 + pr) * 8, lane);
        if (tw == 0) TS(25 + pr + wg * 16);
        if (pr) break;
        og += 64; own += STAGE;
#pragma unroll
        for (int e = 0; e < 16; e++) { p[0][e] = p[2][e]; p[1][e] = p[3][e]; }
      }
    }
    uint32_t xf[8][4];
    if (!wg) {
      mbar_wait(bars + B_XT * 8, 0, budget);
      load_x(sx, xf);
      mbar_wait(bars + (B_PUB + 3) * 8, 0, budget);
    } else {
#pragma unroll
      for (int i = 0; i < 32; i++) xf[i >> 2][i & 3] = 0;
    }
    bar_sync(7 + wg, 128);

    float oacc[64];
    {
      const uint64_t dam = P.da + wg * 512;
      uint32_t slot = 3, ph = 1, prev = 0;
#pragma unroll 1
      for (int s = 0; s < 16; s++) {
        if (tid == 0) KS(128 + 48 + s);
        if (!wg || s <= 16 - END_SKEW) {
          mbar_wait(bars + B_FX * 8 + slot * 8, ph, budget);
          if (s >= 2) mbar_wait(bars + (B_FY + wg * NST) * 8 + slot * 8, ph, budget);
        }
        if (tid == 0) KS(48 + s);
        if (tid == 128) KS(192 + 48 + s);
        if (wg && s == 16 - END_SKEW) {
          mbar_wait(bars + B_XT * 8, 0, budget);
          load_x(sx, xf);
#pragma unroll
          for (int n = 65 - END_SKEW; n < 64; n++) mbar_wait(bars + (B_FY + NST + n % NST) * 8, (n / NST) & 1, budget);
          bar_sync(12, 256);
        }
        const uint64_t da = dam + slot * (STAGE >> 4), db = P.db + slot * (STAGE >> 4);
#pragma unroll
        for (int hf = 0; hf < 2; hf++) {
          wg_wait<1>();
          if (hf && s > 0 && s < 12 && lane0) mbar_arrive(bars + B_EM * 8 + prev * 8);
          wg_fence();
          wgmma_m64n128k16_ss<0, 1>(oacc, da + hf * 4, db + hf * 256, hf ? 1 : s);
          wgmma_m64n128k16_ss<0, 1>(oacc, da + hf * 4 + 2, db + hf * 256 + 128, 1);
          wg_commit();
        }
        prev = slot;
        if (++slot == NST) { slot = 0; ph ^= 1; }
      }
      if (!wg) bar_arrive(12, 256);
    }
    if (__any_sync(0xffffffffu, routed)) { mbar_wait(bars + B_XP * 8, 0, budget); load_x(sx, xf); }
    const float hA = 1.0f - gA, hB = 1.0f - gB;
    float xv[64];
#pragma unroll
    for (int i = 0; i < 32; i++) { xv[2 * i] = bf_lo(xf[i >> 2][i & 3]); xv[2 * i + 1] = bf_hi(xf[i >> 2][i & 3]); }
    pin(xv);
    yield_slot();
    wg_wait<0>();
    pin(oacc);
    if (tw == 0) TS(29 + wg * 16);
#pragma unroll
    for (int hf = 0; hf < 2; hf++) {
#pragma unroll
      for (int u = hf * 4; u < hf * 4 + 4; u++) {
        const float* a = &oacc[8 * u];
        const float* b = &xv[8 * u];
        stmatrix4((sx ^ ((u & 3) * 32)) + hf * 16384,
                  pack2(fmaf(hA, b[0], a[0]), fmaf(hA, b[1], a[1])), pack2(fmaf(hB, b[2], a[2]), fmaf(hB, b[3], a[3])),
                  pack2(fmaf(hA, b[4], a[4]), fmaf(hA, b[5], a[5])), pack2(fmaf(hB, b[6], a[6]), fmaf(hB, b[7], a[7])));
        if (FIN_YIELD) yield_slot();
      }
      fence_async_smem();
      __syncwarp();
      if (elect_one()) tma_store(&mout, sb + SM_PHI + hf * 16384 + warp * 2048, bj * 128 + hf * 64, bi * 128 + warp * 16);
    }
    if (elect_one()) {
      asm volatile("cp.async.bulk.commit_group;" ::: "memory");
      asm volatile("cp.async.bulk.wait_group.read 0;" ::: "memory");
    }
  } else {
    asm volatile("setmaxnreg.dec.sync.aligned.u32 32;");
    if (warp == 8) {
      if (elect_one()) {
        TS(7);
#pragma unroll
        for (int s = 0; s < NST; s++) mbar_init(bars + (B_FX + s) * 8, 1);
        asm volatile("fence.mbarrier_init.release.cluster;" ::: "memory");
        fence_async_smem();
      }
      __syncwarp();
      bar_arrive(0, 512);
      if (elect_one()) {
#pragma unroll 1
        for (int n = 0; n < NST; n++) {
          const uint32_t st = sb + n * STAGE, fb = bars + (B_FX + n) * 8;
          KS(64 + n);
          mbar_expect_tx(fb, STAGE);
          tma_load(st, &mx, fb, n * 64, bi * 128);
          tma_load(st + 16384, &mw, fb, 1024 + bj * 128, n * 64);
          tma_load(st + 24576, &mw, fb, 2048 + bj * 128, n * 64);
        }
      }
      __syncwarp();
      bar_sync(10, 64);
    } else {
      if (warp == 9) {
        if (elect_one()) {
#pragma unroll
          for (int s = B_FY; s < B_NUM; s++) mbar_init(bars + s * 8, s < B_WPHI ? 1 : s < B_EM ? 4 : 8);
          asm volatile("fence.mbarrier_init.release.cluster;" ::: "memory");
          fence_async_smem();
        }
        __syncwarp();
        bar_arrive(10, 64);
      }
      bar_sync(0, 512);
    }
    if (!elect_one()) return;
    if (warp == 8) {
      uint32_t slot = 0, ph = 0;
#pragma unroll 1
      for (int n = NST; n < 48; n++) {
        const int t = n >> 4, k = n & 15;
        const int c0 = t == 2 ? bj * 128 : 1024 + bj * 128 + t * 64, c1 = t == 2 ? c0 + 64 : c0 + 1024;
        const uint32_t st = sb + slot * STAGE, fb = bars + (B_FX + slot) * 8;
        if (n <= NST + 3 * RSTEP && (n - NST) % RSTEP == 0) {
          const int c = (n - NST) / RSTEP;
          mbar_expect_tx(bars + (B_RX + c) * 8, c == 0 ? 8192 + 4096 : 8192);
          tma_load(sb + SM_PHI + c * 8192, &mxr, bars + (B_RX + c) * 8, c * 256, bi * 128 + bj * 16);
          if (c == 0) { bulk_load(sb + SM_V, P.w_r, 2048, bars + B_RX * 8); bulk_load(sb + SM_V + 2048, P.gate_w, 2048, bars + B_RX * 8); }
        }
        mbar_wait(bars + (B_EM + slot) * 8, ph, budget);
        KS(64 + n);
        mbar_expect_tx(fb, STAGE);
        tma_load(st, &mx, fb, k * 64, bi * 128);
        tma_load(st + 16384, &mw, fb, c0, k * 64);
        tma_load(st + 24576, &mw, fb, c1, k * 64);
        {
          const int m = n + WLEAD, tm = m >> 4;
          if ((m & 3) == (bi & 3)) {
            const int d0 = tm >= 2 ? bj * 128 : 1024 + bj * 128 + tm * 64, d1 = tm >= 2 ? d0 + 64 : d0 + 1024;
            tma_prefetch(tm == 3 ? &mwo : &mw, d0, (m & 15) * 64); tma_prefetch(tm == 3 ? &mwo : &mw, d1, (m & 15) * 64);
          }
        }
        if (++slot == NST) { slot = 0; ph ^= 1; }
      }
#pragma unroll 1
      for (int m = WLEAD + ((bi - WLEAD) & 3); m < 16; m += 4) { tma_prefetch(&mwo, bj * 128, m * 64); tma_prefetch(&mwo, bj * 128 + 64, m * 64); }
#pragma unroll 1
      for (int s = 0; s < 16; s++) {
        const int p = s < 2 ? s : (s >= 9), q = s < 9 ? s - 2 : s - 9;
        const int k0 = (s < 2 ? bj : q + (q >= bj)) * 128 + p * 64;
        const uint32_t st = sb + slot * STAGE, fb = bars + (B_FX + slot) * 8;
        mbar_wait(bars + (B_EM + slot) * 8, ph, budget);
        KS(64 + 48 + s);
        mbar_expect_tx(fb, 16384);
        tma_load(st + 16384, &mwo, fb, bj * 128, k0);
        tma_load(st + 24576, &mwo, fb, bj * 128 + 64, k0);
        if (++slot == NST) { slot = 0; ph ^= 1; }
      }
      if (REPF) prefetch_map(&mout);
    } else if (warp == 9) {
      prefetch_map(&mo); prefetch_map(&mout);
      uint32_t old;
      asm volatile("atom.add.release.gpu.global.u32 %0, [%1], 1;" : "=r"(old) : "l"(&g_cnt[C_START]) : "memory");
      sts32(sb + SM_MISC, (old & ~255u) + 256u);
      mbar_arrive(bars + B_EPOCH * 8);
      const CUtensorMap* m = (cta & 8) ? &mu : &mg;
      const int l0 = (cta >> 4) * 14, a0 = (cta & 7) * 64, d1 = (cta >> 2) * 112 - 14 * 16, d2 = (cta & 3) * 4;
      uint32_t buf = 0, ph = 0, tnext;
      asm volatile("mov.u32 %0, %%clock;" : "=r"(tnext));
#pragma unroll 1
      for (int c = 0; c < 21; c++) {
        const uint32_t dst = sb + moe_buf(buf), fb = bars + (B_MF + buf) * 8;
        mbar_wait(bars + (B_ME + buf) * 8, ph, budget);
        mbar_expect_tx(fb, 8192);
        if (c < 14) tma_load(dst, m, fb, a0 + ((l0 + c) >> 4) * 512, ((l0 + c) & 15) * 64); else tma_load3(dst, &md, fb, d1 + c * 16, d2);
        if (MLEAD && c >= 2 && c + MLEAD < 17) {
          const int f = c + MLEAD;
          if (f < 14) tma_prefetch(m, a0 + ((l0 + f) >> 4) * 512, ((l0 + f) & 15) * 64); else tma_prefetch3(&md, d1 + f * 16, d2);
        }
        if (MPACE) { uint32_t now; do { asm volatile("mov.u32 %0, %%clock;" : "=r"(now)); if ((int32_t)(now - tnext) >= 0) break; __nanosleep(20); } while (true); tnext = now + MPACE; }
        if (c == 16) {
#pragma unroll 1
          for (int f = 17; f < 21; f++) { __nanosleep(MGAP); tma_prefetch3(&md, d1 + f * 16, d2); }
        }
        if (c < 2) __nanosleep(MGAP);
        if (c == 17) mbar_arrive(bars + B_M2 * 8);
        if (++buf >= (c >= 14 ? 2 : 3)) { buf = 0; ph ^= 1; }
      }
      mbar_wait(bars + B_MD * 8, 0, budget);
      mbar_wait(bars + (B_RD + 1) * 8, 0, budget);
      mbar_wait(bars + XT_GATE * 8, 0, budget);
      mbar_expect_tx(bars + B_XT * 8, 32768);
      tma_load(sb + SM_PHI, &mx, bars + B_XT * 8, bj * 128, bi * 128);
      tma_load(sb + SM_PHI + 16384, &mx, bars + B_XT * 8, bj * 128 + 64, bi * 128);
      mbar_wait(bars + (B_PUB + 1) * 8, 0, budget);
      mbar_wait(bars + (B_PUB + 3) * 8, 0, budget);
      signal_add(&g_cnt[(C_O + bi * 4 + 1) * 32], 32u);
      TS(57);
      wait_count<POLLF>(&g_cnt[(C_O + bi * 4 + 1) * 32], (old & ~255u) + 256u, budget);
      mbar_arrive(bars + B_P1 * 8);
      TS(3);
    } else {
      const int u = warp - 10, hp = bj * 2 + u;
      mbar_wait(bars + B_EPOCH * 8, 0, budget);
      const uint32_t target = lds32(sb + SM_MISC);
      mbar_wait(bars + B_INFO * 8, 0, budget);
      wait_count<200>(&g_cnt[C_START], target, budget);
      fence_async_global();
#pragma unroll 1
      for (int e = 0; e < 2; e++) {
        uint32_t* cnt = &g_cnt[(e ? C_O + bi * 4 + u * 2 : C_KV + hp) * 32];
        mbar_wait(bars + (e ? B_PUB + u * 2 : B_RH + u) * 8, 0, budget);
        if (e == 0) {
          static_assert(SM_PHI == SM_Z + 4096, "staging is contiguous");
#pragma unroll 1
          for (uint32_t c = 0; c < 10; c++) {
            if (c == 4) mbar_wait(bars + (B_RED + u) * 8, 0, budget);
            bulk_reduce(&g_kvr[hp * 2560 + c * 256], sb + SM_Z + c * 1024, 1024);
            if (c < 9) __nanosleep(u && c >= 3 ? RED_GAP1 : RED_GAP0);
          }
          asm volatile("cp.async.bulk.commit_group;" ::: "memory");
          asm volatile("cp.async.bulk.wait_group 0;" ::: "memory");
          TS(21 + u * 16);
          mbar_arrive(bars + (B_RD + u) * 8);
        }
        signal_add(cnt, e ? 32u : 16u);
        TS(e ? 56 + u * 2 : 60 + u);
        if (REPF && e) prefetch_map(&mo);
        if (e == 0) {
          mbar_wait(bars + (u ? B_M2 : B_RD + 1) * 8, 0, budget);
        }
        wait_count<POLLF>(cnt, target, budget);
        fence_async_global();
        if (e == 0) {
          mbar_expect_tx(bars + (B_KV + u) * 8, 10240);
          bulk_load(sb + SM_V + u * 8192, &g_kvr[hp * 2560], 8192, bars + (B_KV + u) * 8);
          bulk_load(sb + SM_Z + u * 2048, &g_kvr[hp * 2560 + 2048], 2048, bars + (B_KV + u) * 8);
          TS(38 + u);
        }
      }
      TS(2 + u * 2);
      if (u == 0) mbar_wait(bars + B_T3 * 8, 0, budget);
      uint32_t slot = 0, ph = 1;
#pragma unroll 1
      for (int s = 2; s < 16; s++) {
        const int p = s >= 9, q = s < 9 ? s - 2 : s - 9;
        if (s == 9) { mbar_wait(bars + B_P1 * 8, 0, budget); fence_async_global(); }
        const uint32_t fb = bars + (B_FY + u * NST + slot) * 8;
        mbar_wait(bars + (B_EM + slot) * 8, ph, budget);
        mbar_expect_tx(fb, 8192);
        tma_load(sb + slot * STAGE + u * 8192, &mo, fb, (q + (q >= bj)) * 128 + p * 64, bi * 128 + u * 64);
        if (++slot == NST) { slot = 0; ph ^= 1; }
      }
    }
  }
}

typedef CUresult (*EncodeFn)(CUtensorMap*, CUtensorMapDataType, cuuint32_t, void*, const cuuint64_t*, const cuuint64_t*, const cuuint32_t*,
                             const cuuint32_t*, CUtensorMapInterleave, CUtensorMapSwizzle, CUtensorMapL2promotion, CUtensorMapFloatOOBfill);

void make_map(EncodeFn enc, CUtensorMap* m, const void* ptr, uint64_t cols, uint64_t rows, uint32_t bc, uint32_t br, CUtensorMapSwizzle swz) {
  const cuuint64_t dims[2] = {cols, rows}, strides[1] = {cols * 2};
  const cuuint32_t box[2] = {bc, br}, es[2] = {1, 1};
  enc(m, CU_TENSOR_MAP_DATA_TYPE_BFLOAT16, 2, const_cast<void*>(ptr), dims, strides, box, es, CU_TENSOR_MAP_INTERLEAVE_NONE, swz,
      CU_TENSOR_MAP_L2_PROMOTION_L2_128B, CU_TENSOR_MAP_FLOAT_OOB_FILL_NONE);
}

}

extern "C" void kernel_launch(void* const* d_in, const int* in_sizes, int n_in, void* d_out, int out_size) {
  (void)in_sizes; (void)n_in; (void)out_size;
  void* fn = nullptr;
  cudaDriverEntryPointQueryResult qr;
  cudaGetDriverEntryPoint("cuTensorMapEncodeTiled", &fn, cudaEnableDefault, &qr);
  EncodeFn enc = (EncodeFn)fn;
  void* o_ptr = nullptr;
  cudaGetSymbolAddress(&o_ptr, g_o);
  CUtensorMap mx, mw, mwo, mo, mout, mxr, mg, mu, md;
  make_map(enc, &mx, d_in[0], kD, kS, 64, 128, CU_TENSOR_MAP_SWIZZLE_128B);
  make_map(enc, &mxr, d_in[0], kD, kS, 256, 16, CU_TENSOR_MAP_SWIZZLE_NONE);
  make_map(enc, &mw, d_in[1], 3 * kD, kD, 64, 64, CU_TENSOR_MAP_SWIZZLE_128B);
  make_map(enc, &mwo, d_in[3], kD, kD, 64, 64, CU_TENSOR_MAP_SWIZZLE_128B);
  make_map(enc, &mo, o_ptr, kD, kS, 64, 64, CU_TENSOR_MAP_SWIZZLE_128B);
  make_map(enc, &mout, d_out, kD, kS, 64, 16, CU_TENSOR_MAP_SWIZZLE_128B);
  make_map(enc, &mg, d_in[6], kF, kD, 64, 64, CU_TENSOR_MAP_SWIZZLE_128B);
  make_map(enc, &mu, d_in[7], kF, kD, 64, 64, CU_TENSOR_MAP_SWIZZLE_128B);
  {
    const cuuint64_t dims[3] = {64, kF, 16}, strides[2] = {kD * 2, 128};
    const cuuint32_t box[3] = {64, 16, 4}, es[3] = {1, 1, 1};
    enc(&md, CU_TENSOR_MAP_DATA_TYPE_BFLOAT16, 3, d_in[8], dims, strides, box, es, CU_TENSOR_MAP_INTERLEAVE_NONE, CU_TENSOR_MAP_SWIZZLE_128B,
        CU_TENSOR_MAP_L2_PROMOTION_L2_128B, CU_TENSOR_MAP_FLOAT_OOB_FILL_NONE);
  }
  Params P;
  P.x = (const __nv_bfloat16*)d_in[0];
  P.w = (const __nv_bfloat16*)d_in[1];
  P.o = (__nv_bfloat16*)o_ptr;
  P.w_phi = (const __nv_bfloat16*)d_in[2];
  P.w_r = (const __nv_bfloat16*)d_in[5];
  P.gate_w = (const __nv_bfloat16*)d_in[9];
  P.da = make_desc(sb, 16, 1024, 1);
  P.db = make_desc(sb + 16384, 8192, 1024, 1);
  P.dw = make_desc(sb + SM_WPHI, 16, 512, 2);
  P.dphi = make_desc(sb + SM_PHI, 16, 1024, 1);
  P.dv = make_desc(sb + SM_V, SM_ONE - SM_V, 512, 2);
  P.dkv = make_desc(sb + SM_V, SM_Z - SM_V, 512, 2);
  P.dband = make_desc(sb + SM_BAND, 128, 128, 0);
  P.dxs = make_desc(sb + SM_BAND, 16, 128, 0);
  int dev = 0, sms = 0;
  cudaGetDevice(&dev);
  cudaDeviceGetAttribute(&sms, cudaDevAttrMultiProcessorCount, dev);
  auto kern = sms == 132 ? fused_kernel<true> : fused_kernel<false>;
  cudaFuncSetAttribute(kern, cudaFuncAttributeMaxDynamicSharedMemorySize, SM_ALLOC);
  kern<<<132, 512, SM_ALLOC, cudaStreamPerThread>>>(mx, mw, mwo, mo, mout, mxr, mg, mu, md, P);
}
```

```cpp
#include <cuda_runtime.h>
#include <cuda_bf16.h>
#include <cuda.h>
#include <stdint.h>

namespace {

template<int TA, int TB> __device__ __forceinline__ void wgmma_m64n128k16_ss(float (&d)[64], uint64_t da, uint64_t db, int scale_d) {
  asm volatile("{\n.reg .pred p;\nsetp.ne.b32 p, %66, 0;\n"
    "wgmma.mma_async.sync.aligned.m64n128k16.f32.bf16.bf16 "
    "{%0, %1, %2, %3, %4, %5, %6, %7, %8, %9, %10, %11, %12, %13, %14, %15, "
    "%16, %17, %18, %19, %20, %21, %22, %23, %24, %25, %26, %27, %28, %29, %30, %31, "
    "%32, %33, %34, %35, %36, %37, %38, %39, %40, %41, %42, %43, %44, %45, %46, %47, "
    "%48, %49, %50, %51, %52, %53, %54, %55, %56, %57, %58, %59, %60, %61, %62, %63}, "
    "%64, %65, p, 1, 1, %67, %68;\n}\n"
    : "+f"(d[0]), "+f"(d[1]), "+f"(d[2]), "+f"(d[3]), "+f"(d[4]), "+f"(d[5]), "+f"(d[6]), "+f"(d[7]),
      "+f"(d[8]), "+f"(d[9]), "+f"(d[10]), "+f"(d[11]), "+f"(d[12]), "+f"(d[13]), "+f"(d[14]), "+f"(d[15]),
      "+f"(d[16]), "+f"(d[17]), "+f"(d[18]), "+f"(d[19]), "+f"(d[20]), "+f"(d[21]), "+f"(d[22]), "+f"(d[23]),
      "+f"(d[24]), "+f"(d[25]), "+f"(d[26]), "+f"(d[27]), "+f"(d[28]), "+f"(d[29]), "+f"(d[30]), "+f"(d[31]),
      "+f"(d[32]), "+f"(d[33]), "+f"(d[34]), "+f"(d[35]), "+f"(d[36]), "+f"(d[37]), "+f"(d[38]), "+f"(d[39]),
      "+f"(d[40]), "+f"(d[41]), "+f"(d[42]), "+f"(d[43]), "+f"(d[44]), "+f"(d[45]), "+f"(d[46]), "+f"(d[47]),
      "+f"(d[48]), "+f"(d[49]), "+f"(d[50]), "+f"(d[51]), "+f"(d[52]), "+f"(d[53]), "+f"(d[54]), "+f"(d[55]),
      "+f"(d[56]), "+f"(d[57]), "+f"(d[58]), "+f"(d[59]), "+f"(d[60]), "+f"(d[61]), "+f"(d[62]), "+f"(d[63])
    : "l"(da), "l"(db), "r"(scale_d), "n"(TA), "n"(TB));
}

template<int TB> __device__ __forceinline__ void wgmma_m64n32k16_rs(float (&d)[16], const uint32_t (&a)[4], uint64_t db, int scale_d) {
  asm volatile("{\n.reg .pred p;\nsetp.ne.b32 p, %21, 0;\n"
    "wgmma.mma_async.sync.aligned.m64n32k16.f32.bf16.bf16 "
    "{%0, %1, %2, %3, %4, %5, %6, %7, %8, %9, %10, %11, %12, %13, %14, %15}, "
    "{%16, %17, %18, %19}, %20, p, 1, 1, %22;\n}\n"
    : "+f"(d[0]), "+f"(d[1]), "+f"(d[2]), "+f"(d[3]), "+f"(d[4]), "+f"(d[5]), "+f"(d[6]), "+f"(d[7]),
      "+f"(d[8]), "+f"(d[9]), "+f"(d[10]), "+f"(d[11]), "+f"(d[12]), "+f"(d[13]), "+f"(d[14]), "+f"(d[15])
    : "r"(a[0]), "r"(a[1]), "r"(a[2]), "r"(a[3]), "l"(db), "r"(scale_d), "n"(TB));
}

template<int TA, int TB> __device__ __forceinline__ void wgmma_m64n40k16_ss(float (&d)[20], uint64_t da, uint64_t db, int scale_d) {
  asm volatile("{\n.reg .pred p;\nsetp.ne.b32 p, %22, 0;\n"
    "wgmma.mma_async.sync.aligned.m64n40k16.f32.bf16.bf16 "
    "{%0, %1, %2, %3, %4, %5, %6, %7, %8, %9, %10, %11, %12, %13, %14, %15, "
    "%16, %17, %18, %19}, "
    "%20, %21, p, 1, 1, %23, %24;\n}\n"
    : "+f"(d[0]), "+f"(d[1]), "+f"(d[2]), "+f"(d[3]), "+f"(d[4]), "+f"(d[5]), "+f"(d[6]), "+f"(d[7]),
      "+f"(d[8]), "+f"(d[9]), "+f"(d[10]), "+f"(d[11]), "+f"(d[12]), "+f"(d[13]), "+f"(d[14]), "+f"(d[15]),
      "+f"(d[16]), "+f"(d[17]), "+f"(d[18]), "+f"(d[19])
    : "l"(da), "l"(db), "r"(scale_d), "n"(TA), "n"(TB));
}

template<int TB> __device__ __forceinline__ void wgmma_m64n40k16_rs(float (&d)[20], const uint32_t (&a)[4], uint64_t db, int scale_d) {
  asm volatile("{\n.reg .pred p;\nsetp.ne.b32 p, %25, 0;\n"
    "wgmma.mma_async.sync.aligned.m64n40k16.f32.bf16.bf16 "
    "{%0, %1, %2, %3, %4, %5, %6, %7, %8, %9, %10, %11, %12, %13, %14, %15, "
    "%16, %17, %18, %19}, "
    "{%20, %21, %22, %23}, %24, p, 1, 1, %26;\n}\n"
    : "+f"(d[0]), "+f"(d[1]), "+f"(d[2]), "+f"(d[3]), "+f"(d[4]), "+f"(d[5]), "+f"(d[6]), "+f"(d[7]),
      "+f"(d[8]), "+f"(d[9]), "+f"(d[10]), "+f"(d[11]), "+f"(d[12]), "+f"(d[13]), "+f"(d[14]), "+f"(d[15]),
      "+f"(d[16]), "+f"(d[17]), "+f"(d[18]), "+f"(d[19])
    : "r"(a[0]), "r"(a[1]), "r"(a[2]), "r"(a[3]), "l"(db), "r"(scale_d), "n"(TB));
}

template<int TA, int TB> __device__ __forceinline__ void wgmma_m64n8k16_ss(float (&d)[4], uint64_t da, uint64_t db, int scale_d) {
  asm volatile("{\n.reg .pred p;\nsetp.ne.b32 p, %6, 0;\n"
    "wgmma.mma_async.sync.aligned.m64n8k16.f32.bf16.bf16 "
    "{%0, %1, %2, %3}, "
    "%4, %5, p, 1, 1, %7, %8;\n}\n"
    : "+f"(d[0]), "+f"(d[1]), "+f"(d[2]), "+f"(d[3])
    : "l"(da), "l"(db), "r"(scale_d), "n"(TA), "n"(TB));
}

constexpr int kS = 2048, kD = 1024, kF = 3584;
constexpr int NST = 5, STAGE = 32768;
constexpr uint32_t sb = 1024;
constexpr int SM_V    = NST * STAGE;
constexpr int SM_Z    = SM_V + 16384;
constexpr int SM_PHI  = SM_Z + 4096;
constexpr int SM_MOE  = SM_PHI + 16384;
constexpr int SM_WPHI = SM_MOE + 16384;
constexpr int SM_ONE  = SM_WPHI + 8192;
constexpr int SM_BAND = SM_ONE + 1024;
constexpr int SM_G    = SM_BAND + 2176;
constexpr int SM_BAR  = SM_G + 512;
constexpr int SM_MISC = SM_BAR + 448;
constexpr int SM_TOTAL = SM_MISC + 64;
static_assert(SM_TOTAL <= 232448, "smem");
constexpr uint32_t bars = sb + SM_BAR;
constexpr int B_FX = 0  , B_FY = 5  , B_XT = 15, B_EPOCH = 16, B_RX = 17  , B_MF = 21  , B_RD = 24  , B_KV = 26  , B_M2 = 28, B_P1 = 29, B_PS = 30;
constexpr int B_WPHI = 31, B_INFO = 32, B_QS = 33, B_XP = 34, B_RED = 35  , B_PUB = 37  , B_ME = 41  , B_MD = 44, B_T3 = 45, B_RH = 46  ;
constexpr int B_EM = 48  , B_DUMMY = 53, B_NUM = 54;
constexpr int C_START = 0, C_O = 1, C_KV = C_O + 64;

__device__ uint2 g_gate[kS];
__device__ uint2 g_key[128];
__device__ uint2 g_pre[4 * kF];
__device__ uint2 g_yp[32 * kD];
__device__ __align__(128) uint32_t g_kvr[16 * 2560];
__device__ __align__(128) uint32_t g_cnt[(C_KV + 32) * 32];
__device__ __align__(1024) __nv_bfloat16 g_o[kS * kD];
#define KS(id)
#define RG(id)
#define TS(id)
#define TSG(id)
constexpr int SM_ALLOC = SM_TOTAL;

#define POLL0 500
#define POLL1 150
#define RSTEP 1
#define POLLR 400
#define EARLY_N 2
#define EARLY_GAP 200
#define POLLF 50
#define RED_GAP0 250
#define RED_GAP1 0
#define YIELD_EXP 1
#define XT_GATE B_T3
#define FIN_YIELD 0
#define MLEAD 0
#define MPACE 0
#define REPF 1
#define PQ_FIRST 1
#define PUB_TMA 1
#define WLEAD 11
#define MGAP 300

struct Params {
  const __nv_bfloat16 *x, *w, *w_phi, *w_r, *gate_w;
  __nv_bfloat16* o;
  uint64_t da, db, dw, dphi, dv, dkv, dband, dxs;
};

__device__ __forceinline__ uint32_t smem_u32(const void* p) { return (uint32_t)__cvta_generic_to_shared(p); }
__device__ __forceinline__ void mbar_init(uint32_t bar, uint32_t cnt) { asm volatile("mbarrier.init.shared::cta.b64 [%0], %1;" :: "r"(bar), "r"(cnt) : "memory"); }
__device__ __forceinline__ void mbar_expect_tx(uint32_t bar, uint32_t bytes) { asm volatile("mbarrier.arrive.expect_tx.shared::cta.b64 _, [%0], %1;" :: "r"(bar), "r"(bytes) : "memory"); }
__device__ __forceinline__ void mbar_arrive(uint32_t bar) { asm volatile("mbarrier.arrive.shared::cta.b64 _, [%0];" :: "r"(bar) : "memory"); }
__device__ __forceinline__ void mbar_arrive_n(uint32_t bar, uint32_t n) { asm volatile("mbarrier.arrive.shared::cta.b64 _, [%0], %1;" :: "r"(bar), "r"(n) : "memory"); }
constexpr int BUDGET = 1 << 20;
__device__ __forceinline__ void mbar_wait(uint32_t bar, uint32_t parity, int& budget) {
  asm volatile("{\n.reg .pred p;\n"
               "WAIT_L:\nmbarrier.try_wait.parity.shared::cta.b64 p, [%1], %2;\n@p bra WAIT_D;\n"
               "add.s32 %0, %0, -1;\nsetp.gt.s32 p, %0, 0;\n@p bra WAIT_L;\nWAIT_D:\n}"
               : "+r"(budget) : "r"(bar), "r"(parity) : "memory");
}
__device__ __forceinline__ void mbar_wait2(uint32_t bar0, uint32_t bar1, uint32_t parity, int& budget) {
  asm volatile("{\n.reg .pred p, q;\n"
               "WAIT_L:\nmbarrier.try_wait.parity.shared::cta.b64 p, [%1], %3;\nmbarrier.try_wait.parity.shared::cta.b64 q, [%2], %3;\n"
               "and.pred p, p, q;\n@p bra WAIT_D;\n"
               "add.s32 %0, %0, -1;\nsetp.gt.s32 p, %0, 0;\n@p bra WAIT_L;\nWAIT_D:\n}"
               : "+r"(budget) : "r"(bar0), "r"(bar1), "r"(parity) : "memory");
}
template <int SLEEP>
__device__ __forceinline__ void wait_count(const uint32_t* p, uint32_t target, int& budget) {
  asm volatile("{\n.reg .pred p;\n.reg .s32 v;\n"
               "WAIT_L:\nld.acquire.gpu.global.s32 v, [%1];\nsub.s32 v, v, %2;\nsetp.ge.s32 p, v, 0;\n@p bra WAIT_D;\n"
               "nanosleep.u32 %3;\nadd.s32 %0, %0, -4;\nsetp.gt.s32 p, %0, 0;\n@p bra WAIT_L;\nWAIT_D:\n}"
               : "+r"(budget) : "l"(p), "r"(target), "n"(SLEEP) : "memory");
}
__device__ __forceinline__ void tma_load(uint32_t dst, const CUtensorMap* m, uint32_t bar, int c0, int c1) {
  asm volatile("cp.async.bulk.tensor.2d.shared::cluster.global.mbarrier::complete_tx::bytes [%0], [%1, {%3, %4}], [%2];"
    :: "r"(dst), "l"(m), "r"(bar), "r"(c0), "r"(c1) : "memory");
}
__device__ __forceinline__ void tma_load3(uint32_t dst, const CUtensorMap* m, uint32_t bar, int c1, int c2) {
  asm volatile("cp.async.bulk.tensor.3d.shared::cluster.global.mbarrier::complete_tx::bytes [%0], [%1, {%5, %3, %4}], [%2];"
    :: "r"(dst), "l"(m), "r"(bar), "r"(c1), "r"(c2), "r"(0) : "memory");
}
__device__ __forceinline__ void tma_prefetch3(const CUtensorMap* m, int c1, int c2) {
  asm volatile("cp.async.bulk.prefetch.tensor.3d.L2.global [%0, {%3, %1, %2}];" :: "l"(m), "r"(c1), "r"(c2), "r"(0) : "memory");
}
__device__ __forceinline__ void tma_prefetch(const CUtensorMap* m, int c0, int c1) {
  asm volatile("cp.async.bulk.prefetch.tensor.2d.L2.global [%0, {%1, %2}];" :: "l"(m), "r"(c0), "r"(c1) : "memory");
}
__device__ __forceinline__ void tma_store(const CUtensorMap* m, uint32_t src, int c0, int c1) {
  asm volatile("cp.async.bulk.tensor.2d.global.shared::cta.bulk_group [%0, {%2, %3}], [%1];" :: "l"(m), "r"(src), "r"(c0), "r"(c1) : "memory");
}
__device__ __forceinline__ void bulk_load(uint32_t dst, const void* src, uint32_t bytes, uint32_t bar) {
  asm volatile("cp.async.bulk.shared::cluster.global.mbarrier::complete_tx::bytes [%0], [%1], %2, [%3];" :: "r"(dst), "l"(src), "r"(bytes), "r"(bar) : "memory");
}
__device__ __forceinline__ void bulk_reduce(void* dst, uint32_t src, uint32_t bytes) {
  asm volatile("cp.reduce.async.bulk.global.shared::cta.bulk_group.add.noftz.bf16 [%0], [%1], %2;" :: "l"(dst), "r"(src), "r"(bytes) : "memory");
}
__device__ __forceinline__ void prefetch_map(const CUtensorMap* m) { asm volatile("prefetch.tensormap [%0];" :: "l"(m) : "memory"); }
__device__ __forceinline__ bool elect_one() {
  uint32_t p;
  asm volatile("{\n.reg .pred P;\nelect.sync _|P, 0xffffffff;\nselp.u32 %0, 1, 0, P;\n}" : "=r"(p));
  return p;
}
__device__ __forceinline__ void wg_fence() { asm volatile("wgmma.fence.sync.aligned;" ::: "memory"); }
__device__ __forceinline__ void wg_commit() { asm volatile("wgmma.commit_group.sync.aligned;" ::: "memory"); }
template <int N> __device__ __forceinline__ void wg_wait() { asm volatile("wgmma.wait_group.sync.aligned %0;" :: "n"(N) : "memory"); }
template <int N> __device__ __forceinline__ void zero(float (&r)[N]) {
#pragma unroll
  for (int i = 0; i < N; i++) r[i] = 0.f;
}
template <int N> __device__ __forceinline__ void pin(float (&r)[N]) {
#pragma unroll
  for (int i = 0; i < N; i++) asm volatile("" : "+f"(r[i]) :: "memory");
}
template <int N> __device__ __forceinline__ void pinr(uint32_t (&r)[N][4]) {
#pragma unroll
  for (int i = 0; i < N; i++) asm volatile("" : "+r"(r[i][0]), "+r"(r[i][1]), "+r"(r[i][2]), "+r"(r[i][3]) :: "memory");
}
__device__ __forceinline__ void fence_async_smem() { asm volatile("fence.proxy.async.shared::cta;" ::: "memory"); }
__device__ __forceinline__ void fence_async_global() { asm volatile("fence.proxy.async.global;" ::: "memory"); }
__device__ __forceinline__ void bar_sync(int id, int n) { asm volatile("bar.sync %0, %1;" :: "r"(id), "r"(n) : "memory"); }
__device__ __forceinline__ void bar_arrive(int id, int n) { asm volatile("bar.arrive %0, %1;" :: "r"(id), "r"(n) : "memory"); }
__device__ __forceinline__ void arrive_one(uint32_t bar) {
  asm volatile("{\n.reg .pred p;\nelect.sync _|p, 0xffffffff;\n@p mbarrier.arrive.shared::cta.b64 _, [%0];\n}" :: "r"(bar) : "memory");
}
__device__ __forceinline__ void warp_arrive(uint32_t bar, int lane) { __syncwarp(); if (lane == 0) mbar_arrive(bar); }
__host__ __device__ constexpr uint64_t make_desc(uint32_t addr, uint32_t lbo, uint32_t sbo, uint32_t swz) {
  return (uint64_t)((addr & 0x3FFFF) >> 4) | ((uint64_t)((lbo & 0x3FFFF) >> 4) << 16) | ((uint64_t)(sbo >> 4) << 32) | ((uint64_t)swz << 62);
}
__device__ __forceinline__ uint32_t pack2(float lo, float hi) {
  uint32_t r; asm("cvt.rn.bf16x2.f32 %0, %1, %2;" : "=r"(r) : "f"(hi), "f"(lo)); return r;
}
__device__ __forceinline__ float bf_lo(uint32_t v) { return __uint_as_float(v << 16); }
__device__ __forceinline__ float bf_hi(uint32_t v) { return __uint_as_float(v & 0xffff0000u); }
__device__ __forceinline__ float ex2(float x) { float r; asm("ex2.approx.ftz.f32 %0, %1;" : "=f"(r) : "f"(x)); return r; }
__device__ __forceinline__ float rcp(float x) { float r; asm("rcp.approx.ftz.f32 %0, %1;" : "=f"(r) : "f"(x)); return r; }
constexpr float LOG2E = 1.4426950408889634f;
__device__ __forceinline__ float sigmoidf(float x) { return rcp(1.0f + ex2(-LOG2E * x)); }
__device__ __forceinline__ void sts128(uint32_t a, uint32_t x, uint32_t y, uint32_t z, uint32_t w) {
  asm volatile("st.shared.v4.u32 [%0], {%1,%2,%3,%4};" :: "r"(a), "r"(x), "r"(y), "r"(z), "r"(w) : "memory");
}
__device__ __forceinline__ void lds128(uint32_t a, uint32_t (&r)[4]) {
  asm volatile("ld.shared.v4.u32 {%0,%1,%2,%3}, [%4];" : "=r"(r[0]), "=r"(r[1]), "=r"(r[2]), "=r"(r[3]) : "r"(a) : "memory");
}
__device__ __forceinline__ void sts32(uint32_t a, uint32_t v) { asm volatile("st.shared.u32 [%0], %1;" :: "r"(a), "r"(v) : "memory"); }
__device__ __forceinline__ uint32_t lds32(uint32_t a) { uint32_t v; asm volatile("ld.shared.u32 %0, [%1];" : "=r"(v) : "r"(a) : "memory"); return v; }
__device__ __forceinline__ float ldsf(uint32_t a) { return __uint_as_float(lds32(a)); }
__device__ __forceinline__ void stmatrix4(uint32_t a, uint32_t r0, uint32_t r1, uint32_t r2, uint32_t r3) {
  asm volatile("stmatrix.sync.aligned.m8n8.x4.shared.b16 [%0], {%1,%2,%3,%4};" :: "r"(a), "r"(r0), "r"(r1), "r"(r2), "r"(r3) : "memory");
}
__device__ __forceinline__ void ldmatrix4(uint32_t a, uint32_t (&r)[4]) {
  asm volatile("ldmatrix.sync.aligned.m8n8.x4.shared.b16 {%0,%1,%2,%3}, [%4];" : "=r"(r[0]), "=r"(r[1]), "=r"(r[2]), "=r"(r[3]) : "r"(a) : "memory");
}
__device__ __forceinline__ uint4 ldg_nc(const void* p) {
  uint4 v; asm volatile("ld.global.nc.L1::no_allocate.v4.u32 {%0,%1,%2,%3}, [%4];" : "=r"(v.x), "=r"(v.y), "=r"(v.z), "=r"(v.w) : "l"(p)); return v;
}
__device__ __forceinline__ void st_tagged(uint2* p, uint32_t v, uint32_t tag) {
  asm volatile("{\n.reg .b64 x;\nmov.b64 x, {%1, %2};\nst.relaxed.gpu.global.b64 [%0], x;\n}" :: "l"(p), "r"(v), "r"(tag) : "memory");
}
__device__ __forceinline__ uint2 ld_tagged(const uint2* p) {
  uint2 v; asm volatile("{\n.reg .b64 x;\nld.relaxed.gpu.global.b64 x, [%2];\nmov.b64 {%0, %1}, x;\n}" : "=r"(v.x), "=r"(v.y) : "l"(p) : "memory"); return v;
}
__device__ __forceinline__ void probe(const uint2* p, uint32_t tag, int& budget) {
  do { __nanosleep(POLL0); budget -= 16; } while (!__all_sync(0xffffffffu, ld_tagged(p).y == tag) && budget > 0);
}
template <int STRIDE, int N>
__device__ __forceinline__ void gather(const uint2* p, uint32_t tag, float& s0, float& s1, int& budget) {
  uint32_t pause = 0;
  bool again;
#pragma unroll 1
  do {
    __nanosleep(pause);
    pause = POLL0;
    uint32_t bad = 0;
    s0 = s1 = 0.f;
#pragma unroll
    for (int i = 0; i < N; i++) {
      const uint2 w = ld_tagged(p + i * STRIDE);
      bad |= w.y ^ tag;
      if (i < N / 2) s0 += __uint_as_float(w.x); else s1 += __uint_as_float(w.x);
    }
    budget -= 16;
    again = __any_sync(0xffffffffu, bad != 0) && budget > 0;
  } while (again);
}
__device__ __forceinline__ void sts16(uint32_t a, uint32_t v) { asm volatile("st.shared.u16 [%0], %1;" :: "r"(a), "h"((uint16_t)v) : "memory"); }
__device__ __forceinline__ void signal_add(uint32_t* p, uint32_t v) { asm volatile("red.release.gpu.global.add.u32 [%0], %1;" :: "l"(p), "r"(v) : "memory"); }
__device__ __forceinline__ float qmax(float v) { v = fmaxf(v, __shfl_xor_sync(0xffffffffu, v, 1)); return fmaxf(v, __shfl_xor_sync(0xffffffffu, v, 2)); }
__device__ __forceinline__ float qsum(float v) { v += __shfl_xor_sync(0xffffffffu, v, 1); return v + __shfl_xor_sync(0xffffffffu, v, 2); }
__device__ __forceinline__ float fold(float a, float b, bool hi, int m) { return (hi ? b : a) + __shfl_xor_sync(0xffffffffu, hi ? a : b, m); }

__device__ __forceinline__ void yield_slot() { asm volatile("pmevent 0;" ::: "memory"); }
__device__ __forceinline__ float fma_v(float a, float b, float c) { float r; asm volatile("fma.rn.f32 %0, %1, %2, %3;" : "=f"(r) : "f"(a), "f"(b), "f"(c)); return r; }
constexpr uint32_t EXP_TOP = 0x58805880u;
__device__ __forceinline__ void exp_plain(const float (&p)[16], float (&ep)[16], float (&em)[16]) {
#pragma unroll
  for (int i = 0; i < 16; i++) { ep[i] = ex2(p[i]); em[i] = ex2(-p[i]); }
}
__device__ __forceinline__ void exp_shifted(const float (&p)[16], float sgn, float (&e)[16]) {
#pragma unroll
  for (int i = 0; i < 16; i++) e[i] = sgn * p[i];
#pragma unroll
  for (int o = 0; o < 4; o += 2) {
    const float mx = qmax(fmaxf(fmaxf(fmaxf(e[o], e[o + 1]), fmaxf(e[o + 4], e[o + 5])), fmaxf(fmaxf(e[o + 8], e[o + 9]), fmaxf(e[o + 12], e[o + 13]))));
#pragma unroll
    for (int c = 0; c < 4; c++) { e[4 * c + o] = ex2(e[4 * c + o] - mx); e[4 * c + o + 1] = ex2(e[4 * c + o + 1] - mx); }
  }
}
__device__ __forceinline__ void pack_sums(const float (&e)[16], uint32_t (&pk)[2][4], float (&s)[2]) {
#pragma unroll
  for (int i = 0; i < 8; i++) pk[i >> 2][i & 3] = pack2(e[2 * i], e[2 * i + 1]);
#pragma unroll
  for (int o = 0; o < 4; o += 2) s[o >> 1] = ((e[o] + e[o + 1]) + (e[o + 4] + e[o + 5])) + ((e[o + 8] + e[o + 9]) + (e[o + 12] + e[o + 13]));
}
__device__ __forceinline__ uint32_t rcp2(float s) { const float r = rcp(s); return pack2(r, r); }
__device__ __forceinline__ uint32_t add2(uint32_t a, uint32_t b) { uint32_t r; asm("add.rn.bf16x2 %0, %1, %2;" : "=r"(r) : "r"(a), "r"(b)); return r; }
__device__ __forceinline__ uint32_t mul2(uint32_t a, uint32_t b) { uint32_t r; asm("mul.rn.bf16x2 %0, %1, %2;" : "=r"(r) : "r"(a), "r"(b)); return r; }
__device__ __forceinline__ void store_phi(uint32_t a, const uint32_t (&pk)[2][4], uint32_t r0, uint32_t r1) {
#pragma unroll
  for (int h = 0; h < 2; h++) stmatrix4(a ^ (h * 32), mul2(pk[h][0], r0), mul2(pk[h][1], r1), mul2(pk[h][2], r0), mul2(pk[h][3], r1));
}
__device__ __forceinline__ uint32_t exp_frags(const float (&p)[16], uint32_t (&ef)[4][4], uint32_t top) {
  float ep[16], em[16];
  exp_plain(p, ep, em);
#pragma unroll
  for (int s = 0; s < 2; s++)
#pragma unroll
    for (int r = 0; r < 4; r++) {
      ef[s][r] = pack2(ep[8 * s + 2 * r], ep[8 * s + 2 * r + 1]);
      ef[2 + s][r] = pack2(em[8 * s + 2 * r], em[8 * s + 2 * r + 1]);
    }
#pragma unroll
  for (int s = 0; s < 4; s++) top = __vimax3_u16x2(__vimax3_u16x2(top, ef[s][0], ef[s][1]), ef[s][2], ef[s][3]);
  return top;
}
__device__ __forceinline__ void pair_frags(float (&p0)[16], const float (&p1)[16], uint32_t (&ef)[2][4][4]) {
  const uint32_t top = exp_frags(p1, ef[1], exp_frags(p0, ef[0], EXP_TOP));
  if (__builtin_expect(__any_sync(0xffffffffu, top != EXP_TOP), 0)) {
#pragma unroll 1
    for (int u = 0; u < 4; u++) {
      float e[16];
      exp_shifted(p0, (u & 1) ? -1.f : 1.f, e);
#pragma unroll
      for (int r = 0; r < 4; r++) {
#pragma unroll
        for (int s = 0; s < 6; s++) ef[s >> 2][s & 3][r] = ef[(s + 2) >> 2][(s + 2) & 3][r];
        ef[1][2][r] = pack2(e[2 * r], e[2 * r + 1]);
        ef[1][3][r] = pack2(e[8 + 2 * r], e[8 + 2 * r + 1]);
      }
      if (u & 1) {
#pragma unroll
        for (int c = 0; c < 16; c++) p0[c] = p1[c];
      }
    }
  }
}
__device__ __forceinline__ void issue_pq(float (&p)[4][16], const uint32_t (&qf)[4][2][4], uint64_t dw, int accumulate) {
  wg_fence();
#pragma unroll
  for (int h = 0; h < 4; h++) {
    wgmma_m64n32k16_rs<1>(p[h], qf[h][0], dw + h * 128, accumulate);
    wgmma_m64n32k16_rs<1>(p[h], qf[h][1], dw + h * 128 + 64, 1);
  }
  wg_commit();
}

#define SPLIT_BATCH 2
__device__ __forceinline__ void mainloop128(float (&acc)[2][64], uint64_t da0, uint64_t db0, uint32_t slot, uint32_t ph, int steps, bool lane0, int& budget, int cta, int n0) {
  uint32_t prev = 0;
#pragma unroll 1
  for (int k = 0; k < steps; k++) {
    mbar_wait(bars + B_FX * 8 + slot * 8, ph, budget);
    const uint64_t da = da0 + slot * (STAGE >> 4), db = db0 + slot * (STAGE >> 4);
#pragma unroll
    for (int kk = 0; kk < 4; kk++) {
      if (SPLIT_BATCH == 2 || !(kk & 1)) {
        wg_wait<1>();
        if (kk == 3 - SPLIT_BATCH && k > 0 && lane0) mbar_arrive_n(bars + B_EM * 8 + prev * 8, 2);
        wg_fence();
      }
      wgmma_m64n128k16_ss<0, 1>(acc[0], da + kk * 2, db + kk * 128, kk ? 1 : k);
      wgmma_m64n128k16_ss<0, 1>(acc[1], da + 512 + kk * 2, db + kk * 128, kk ? 1 : k);
      if (SPLIT_BATCH == 2 || (kk & 1)) wg_commit();
    }
    prev = slot;
    if (++slot == NST) { slot = 0; ph ^= 1; }
  }
}
__device__ __forceinline__ void kstep64(float (&acc)[64], uint64_t da, uint64_t db, int accumulate) {
  wg_fence();
#pragma unroll
  for (int kk = 0; kk < 4; kk++) wgmma_m64n128k16_ss<0, 1>(acc, da + kk * 2, db + kk * 128, kk ? 1 : accumulate);
  wg_commit();
}
__device__ __forceinline__ void issue_kv(float (&kv)[20], uint64_t dphi, uint64_t dv, int accumulate) {
  wg_fence();
#pragma unroll
  for (int ks = 0; ks < 4; ks++)
    wgmma_m64n40k16_ss<1, 1>(kv, dphi + ks * 128, dv - (uint64_t)ks * ((64ull << 16) - 64ull), ks ? 1 : accumulate);
  wg_commit();
}
__device__ __forceinline__ void load_x(uint32_t sx, uint32_t (&xf)[8][4]) {
#pragma unroll
  for (int u = 0; u < 8; u++) ldmatrix4((sx ^ ((u & 3) * 32)) + (u >> 2) * 16384, xf[u]);
}
__device__ __forceinline__ uint32_t moe_buf(uint32_t b) { return b == 2 ? SM_V + 8192 : SM_MOE + b * 8192; }
template <bool DOWN>
__device__ __forceinline__ void moe_chunks(float (&a)[4], int n, uint32_t& buf, uint32_t& ph, uint64_t da0, uint64_t db, bool lane0) {
  int budget = BUDGET;
  zero(a);
#pragma unroll 1
  for (int c = 0; c < n; c++) {
    mbar_wait(bars + B_MF * 8 + buf * 8, ph, budget);
    const uint64_t da = da0 + (moe_buf(buf) >> 4);
    wg_fence();
#pragma unroll
    for (int j = 0; j < 4; j++) wgmma_m64n8k16_ss<1, 0>(a, da + j * 128, DOWN ? db - j : db + j * 2, 1);
    wg_commit();
    wg_wait<0>();
    if (lane0) mbar_arrive(bars + B_ME * 8 + buf * 8);
    db += DOWN ? 16 : 8;
    if (++buf >= (DOWN ? 2 : 3)) { buf = 0; ph ^= 1; }
  }
  pin(a);
}
constexpr uint64_t DV_TILE = 4 * ((64ull << 16) - 64ull);

template <bool BY_SM>
__global__ void __launch_bounds__(512, 1)
fused_kernel(const __grid_constant__ CUtensorMap mx, const __grid_constant__ CUtensorMap mw, const __grid_constant__ CUtensorMap mwo,
             const __grid_constant__ CUtensorMap mo, const __grid_constant__ CUtensorMap mout, const __grid_constant__ CUtensorMap mxr,
             const __grid_constant__ CUtensorMap mg, const __grid_constant__ CUtensorMap mu, const __grid_constant__ CUtensorMap md, const Params P) {
  extern __shared__ __align__(1024) uint8_t smem_raw[];
  if (smem_u32(smem_raw) != sb) return;
  const int tid = threadIdx.x, lane = tid & 31;
  if (tid == 256) TS(1);
  const int warp = __shfl_sync(0xffffffffu, tid >> 5, 0), wg = warp >> 2;
  int budget = BUDGET;
  if (warp == 10 && elect_one()) { prefetch_map(&mx); prefetch_map(&mw); }
  int cta;
  {
    uint32_t smid;
    asm volatile("mov.u32 %0, %%smid;" : "=r"(smid));
    if (!BY_SM) cta = blockIdx.x;
    else if (smid < 64) cta = ((smid >> 1) & 7) * 16 + (smid >> 4) * 2 + (smid & 1);
    else if (smid < 120) { const int t = (smid - 64) >> 1, d = (t * 37) >> 8; cta = (1 + t - d * 7) * 16 + 8 + d * 2 + (smid & 1); }
    else cta = smid < 124 ? smid + 8 : smid - 116;
  }
  if (cta >= 128) {
    if (tid == 0) {
      const uint32_t old = atomicAdd(&g_cnt[C_START], 32u);
      wait_count<500>(&g_cnt[C_START], (old & ~255u) + 256u, budget);
    }
    return;
  }
  const int bi = (cta >> 5) * 4 + ((cta >> 2) & 3);
  const int bj = ((cta >> 4) & 1) * 4 + (cta & 3);

  if (wg == 3) {
    asm volatile("setmaxnreg.dec.sync.aligned.u32 64;");
    const int t3 = tid - 384, w3 = warp - 12;
    if (t3 == 0) TSG(0);
    if (t3 < 80) *reinterpret_cast<uint4*>(&g_kvr[cta * 320 + t3 * 4]) = make_uint4(0, 0, 0, 0);
    if (t3 < 17) st_tagged(t3 < 16 ? &g_gate[bi * 128 + bj * 16 + t3] : &g_key[cta], 0, 1);
    bar_sync(0, 512);
#pragma unroll 1
    for (int u = 0; u < 4; u++) {
      const uint4 v = ldg_nc(P.w_phi + bj * 4096 + (u * 128 + t3) * 8);
      sts128(sb + SM_WPHI + u * 2048 + (t3 >> 2) * 64 + (((t3 & 3) ^ ((t3 >> 3) & 3)) << 4),
             pack2(LOG2E * bf_lo(v.x), LOG2E * bf_hi(v.x)), pack2(LOG2E * bf_lo(v.y), LOG2E * bf_hi(v.y)),
             pack2(LOG2E * bf_lo(v.z), LOG2E * bf_hi(v.z)), pack2(LOG2E * bf_lo(v.w), LOG2E * bf_hi(v.w)));
    }
    fence_async_smem();
    warp_arrive(bars + B_WPHI * 8, lane);
    bar_sync(6, 256);
    const uint32_t target = lds32(sb + SM_MISC);
    uint32_t key;
    {
      uint32_t kk[4];
      lds128(sb + SM_MISC + 16, kk);
      if (t3 == 0) st_tagged(&g_key[cta], max(max(kk[0], kk[1]), max(kk[2], kk[3])), target);
      uint2 k, gv;
      __nanosleep(POLLR);
      do {
        __nanosleep(POLL1);
        k = ld_tagged(&g_key[t3]);
        gv = ld_tagged(&g_gate[bi * 128 + t3]);
        budget -= 4;
      } while (!__all_sync(0xffffffffu, k.y == target && gv.y == target) && budget > 0);
      key = __reduce_max_sync(0xffffffffu, k.x);
      if (lane == 0) sts32(sb + SM_MISC + 32 + w3 * 4, key);
      sts32(sb + SM_G + t3 * 4, gv.x);
      bar_sync(5, 128);
      lds128(sb + SM_MISC + 32, kk);
      key = max(max(kk[0], kk[1]), max(kk[2], kk[3]));
    }
    const int idx = (0xFFFF - (key & 0xFFFF)) & (kS - 1);
    if (t3 == 0) { sts32(sb + SM_MISC + 4, idx); TS(8); }
    warp_arrive(bars + B_INFO * 8, lane);
    {
      const uint4 v = ldg_nc(P.x + (size_t)idx * kD + t3 * 8);
      sts128(sb + SM_BAND + t3 * 16, v.x, v.y, v.z, v.w);
    }
    const int t2 = (lane & 3) * 2, row = w3 * 16 + (lane >> 2);
    float a[4];
    uint32_t buf = 0, ph = 0;
    fence_async_smem();
    bar_sync(5, 128);
    {
      const int r = cta >> 4;
#pragma unroll 1
      for (int part = 0; part < 2; part++) {
        const int n = part ? 14 - 2 * r : 2 * r;
        moe_chunks<false>(a, n, buf, ph, P.da, P.dxs + (part ? 0 : (16 - n) * 8), lane == 0);
        uint2* dst = &g_pre[(((cta >> 2) & 2) + 1 - part) * kF + ((r - 1 + part) * 8 + (cta & 7)) * 64 + row];
        if (t2 == 0 && n) { st_tagged(dst, __float_as_uint(a[0]), target); st_tagged(dst + 8, __float_as_uint(a[2]), target); }
      }
    }
    if (t3 == 0) TS(9);
    bar_sync(5, 128);
    sts128(sb + SM_BAND + t3 * 16, 0, 0, 0, 0);
    {
      __nanosleep(POLL0);
      float gs, us;
      gather<kF, 4>(&g_pre[(cta >> 2) * 112 + min(t3, 111)], target, gs, us, budget);
      bar_sync(5, 128);
      if (t3 < 112) sts16(sb + SM_BAND + 112 + (t3 >> 3) * 128 + (t3 & 7) * 2, pack2(gs * sigmoidf(gs) * us, 0.f));
    }
    fence_async_smem();
    bar_sync(5, 128);
    if (t3 == 0) TS(12);
    moe_chunks<true>(a, 7, buf, ph, P.da, P.dband + 7, lane == 0);
    if (t3 == 0) TS(10);
    if (t2 < 4) {
      uint2* dst = &g_yp[(cta >> 2) * kD + (cta & 3) * 256 + t2 * 64 + row];
      st_tagged(dst, __float_as_uint(a[0]), target); st_tagged(dst + 8, __float_as_uint(a[2]), target);
      st_tagged(dst + 64, __float_as_uint(a[1]), target); st_tagged(dst + 72, __float_as_uint(a[3]), target);
    }
    if (lane == 0) mbar_arrive(bars + B_MD * 8);
    if ((idx >> 7) == bi) {
      mbar_wait(bars + (B_PUB + 3) * 8, 0, budget);
      if (w3 == 0) probe(&g_yp[lane * kD + bj * 128], target, budget);
      bar_sync(5, 128);
      float y = 0.f;
#pragma unroll 1
      for (int hf = 0; hf < 2; hf++) {
        float y0, y1;
        gather<kD, 16>(&g_yp[hf * 16 * kD + bj * 128 + t3], target, y0, y1, budget);
        y += y0 + y1;
      }
      const uint32_t ob = key >> 16;
      const float upd = y * sigmoidf(__uint_as_float(((ob & 0x8000u) ? (ob ^ 0x8000u) : (~ob & 0xFFFFu)) << 16));
      const uint32_t a = sb + SM_PHI + (t3 >> 6) * 16384 + (idx & 127) * 128 + ((((t3 >> 3) & 7) ^ (idx & 7)) << 4) + (t3 & 7) * 2;
      mbar_wait(bars + B_XT * 8, 0, budget);
      uint16_t xb;
      asm volatile("ld.shared.u16 %0, [%1];" : "=h"(xb) : "r"(a) : "memory");
      sts16(a, pack2(bf_lo(xb) + upd, 0.f));
      warp_arrive(bars + B_XP * 8, lane);
      if (t3 == 0) TS(11);
    }
  } else if (wg < 2) {
    if ((warp & 3) < EARLY_N && lane < (wg ? 8 : 16)) {
      const int n = warp & 3;
      const __nv_bfloat16* p = wg ? P.w + (size_t)(n * 64 + bi + (lane >> 1) * 16) * (3 * kD) + 1024 + (lane & 1) * 1024 + bj * 128
                                  : P.x + (size_t)(bi * 128 + bj * 16 + lane) * kD + n * 64;
      if (n) __nanosleep(n * EARLY_GAP);
      asm volatile("prefetch.global.L2 [%0];" :: "l"(p));
    }
    __syncwarp();
    asm volatile("setmaxnreg.inc.sync.aligned.u32 208;");
    const int tw = tid & 127, w = warp & 3, g = lane >> 2, t = lane & 3;
    const bool lane0 = lane == 0;
    if (wg == 0) sts128(sb + SM_ONE + (tw & 63) * 16, 0x3f803f80u, 0x3f803f80u, 0x3f803f80u, 0x3f803f80u);
    bar_sync(0, 512);
    if (wg == 1) {
      float sr[4], sg[4];
      zero(sr); zero(sg);
#pragma unroll 1
      for (int c = 0; c < 4; c++) {
        mbar_wait(bars + (B_RX + c) * 8, 0, budget);
        uint32_t rs[4], gs[4], xs[4][4];
        lds128(sb + SM_V + c * 512 + lane * 16, rs);
        lds128(sb + SM_V + 2048 + c * 512 + lane * 16, gs);
#pragma unroll
        for (int r = 0; r < 4; r++) lds128(sb + SM_PHI + c * 8192 + (w * 4 + r) * 512 + lane * 16, xs[r]);
#pragma unroll
        for (int e = 0; e < 4; e++) {
          const float r0 = bf_lo(rs[e]), r1 = bf_hi(rs[e]), g0 = bf_lo(gs[e]), g1 = bf_hi(gs[e]);
#pragma unroll
          for (int r = 0; r < 4; r++) {
            const float x0 = bf_lo(xs[r][e]), x1 = bf_hi(xs[r][e]);
            sr[r] = fma_v(x0, r0, sr[r]); sg[r] = fma_v(x0, g0, sg[r]);
            sr[r] = fma_v(x1, r1, sr[r]); sg[r] = fma_v(x1, g1, sg[r]);
            if (r != 1) yield_slot();
          }
        }
      }
      fence_async_smem();
      __syncwarp();
      if (lane < 3) mbar_arrive(bars + (B_ME + lane) * 8);
      const bool b4 = lane & 16, b3 = lane & 8, b2 = lane & 4;
      const float v = qsum(fold(fold(fold(sr[0], sg[0], b4, 16), fold(sr[2], sg[2], b4, 16), b3, 8),
                                fold(fold(sr[1], sg[1], b4, 16), fold(sr[3], sg[3], b4, 16), b3, 8), b2, 4));
      const int row = bi * 128 + bj * 16 + w * 4 + (g & 3);
      const uint32_t rb = pack2(v + 0.f, 0.f);
      const uint32_t ob = (rb & 0x8000u) ? (~rb & 0xFFFFu) : (rb | 0x8000u);
      const uint32_t best = __reduce_max_sync(0xffffffffu, b4 ? 0u : (ob << 16) | (0xFFFFu - row));
      mbar_wait(bars + B_EPOCH * 8, 0, budget);
      const uint32_t tag = lds32(sb + SM_MISC);
      if (lane0) sts32(sb + SM_MISC + 16 + w * 4, best);
      if (b4 && t == 0) st_tagged(&g_gate[row], __float_as_uint(sigmoidf(v)), tag);
      if (tw == 0) TS(14);
      bar_arrive(6, 256);
      bar_sync(1, 256);
    }

    {
      float acc[2][64];
      if (tw == 0) TS(16 + wg * 16);
      mainloop128(acc, P.da, P.db, wg, wg, 16, lane0, budget, cta, wg * 16);
      bar_sync(1 + wg, 256);
      wg_wait<0>();
      pin(acc[0]); pin(acc[1]);
      if (lane0) mbar_arrive_n(bars + (B_EM + wg) * 8, 2);
      if (tw == 0) TS(17 + wg * 16);
      float p[4][16];
      uint32_t vp[8][4];
      const uint32_t av = sb + SM_V + (w * 16 + g) * 64 + ((t ^ (g >> 1)) << 4);
      {
        uint32_t kf[4][2][4];
#pragma unroll
        for (int u = 0; u < 4; u++)
#pragma unroll
          for (int s = 0; s < 2; s++)
#pragma unroll
            for (int r = 0; r < 4; r++) kf[u][s][r] = pack2(acc[u & 1][16 * (u >> 1) + 8 * s + 2 * r], acc[u & 1][16 * (u >> 1) + 8 * s + 2 * r + 1]);
        mbar_wait(bars + B_WPHI * 8, 0, budget);
        const uint64_t dw = P.dw + wg * 256;
        wg_fence();
#pragma unroll
        for (int u = 0; u < 4; u++) {
          wgmma_m64n32k16_rs<1>(p[u], kf[u][0], dw + (u >> 1) * 128, 0);
          wgmma_m64n32k16_rs<1>(p[u], kf[u][1], dw + (u >> 1) * 128 + 64, 1);
        }
        wg_commit();
#pragma unroll
        for (int u = 0; u < 8; u++) {
          const float* a = &acc[(u >> 1) & 1][32 + 16 * (u >> 2) + 2 * (u & 1)];
          vp[u][0] = pack2(a[0], a[1]); vp[u][1] = pack2(a[4], a[5]); vp[u][2] = pack2(a[8], a[9]); vp[u][3] = pack2(a[12], a[13]);
          if (u < 4) sts128(av + (u >> 1) * 4096 + (u & 1) * 512, vp[u][0], vp[u][1], vp[u][2], vp[u][3]);
        }
        pinr(vp);
        wg_wait<0>();
#pragma unroll
        for (int u = 0; u < 4; u++) pin(p[u]);
      }
      if (tw == 0) TS(18 + wg * 16);
      float kv[2][20];
      {
        const uint32_t sphi = sb + SM_PHI + (w * 16 + (lane & 15)) * 128 + (((lane >> 4) ^ (lane & 7)) << 4);
        uint32_t top = EXP_TOP;
        uint32_t pk[4][2][4];
        float ps[2];
        uint32_t sh[1][4];
        uint32_t redo = 0, redo0 = 0;
        const uint32_t astage = sb + (w * 16 + (lane & 15)) * 64 + (((lane >> 4) ^ ((lane >> 1) & 3)) << 4);
        auto stage_kv = [&](int hh) {
#pragma unroll
          for (int q = 0; q < 2; q++) {
            const float* a = &kv[hh][8 * q];
            stmatrix4((astage ^ (q * 32)) + (hh ? SM_PHI : SM_Z), pack2(a[0], a[1]), pack2(a[2], a[3]), pack2(a[4], a[5]), pack2(a[6], a[7]));
          }
        };
#pragma unroll
        for (int i = 0; i < 11; i++) {
          if (i >= 3) {
            const int j = i - 3;
            const uint32_t s2 = add2(sh[0][2], sh[0][3]);
            top = __vmaxu2(top, s2);
            store_phi((sphi ^ ((j & 1) * 64)) + (j & 2) * 4096, pk[j & 3], rcp2(bf_lo(s2)), rcp2(bf_hi(s2)));
          }
          if (i >= 2 && i <= 9) { sh[0][2] = add2(sh[0][0], sh[0][1]); sh[0][3] = __shfl_xor_sync(0xffffffffu, sh[0][2], 2); }
          if (i >= 1 && i <= 8) { sh[0][0] = pack2(ps[0], ps[1]); sh[0][1] = __shfl_xor_sync(0xffffffffu, sh[0][0], 1); }
          if (i == 1) sh[0][2] = sh[0][3] = 0;
          if (i < 8) {
            pin(p[i >> 1]);
            float e[16];
#pragma unroll
            for (int c = 0; c < 16; c++) e[c] = ex2((i & 1) ? -p[i >> 1][c] : p[i >> 1][c]);
            pack_sums(e, pk[i & 3], ps);
            pinr(pk[i & 3]); pin(ps);
          }
          if (i < 10) yield_slot();
          if (i >= 1 && i <= 9) pinr(sh);
          if (i == 7) { wg_wait<0>(); pin(kv[0]); stage_kv(0); }
          if (i == 2 && wg) mbar_wait(bars + B_RD * 8, 0, budget);
          if (i >= 4 && !(i & 1)) {
            const int u = (i - 4) >> 1;
            fence_async_smem();
            wg_wait<0>();
            if (!(u & 1)) bar_sync(7 + wg, 128);
            else asm volatile("{\n.reg .pred p, q;\nsetp.ne.b32 p, %2, %3;\nbar.red.or.pred q, %1, 128, p;\nselp.u32 %0, 1, 0, q;\n}"
                              : "=r"(redo) : "r"(7 + wg), "r"(top), "n"(EXP_TOP) : "memory");
            if (u == 1) redo0 = redo;
            if (u == 2 && lane0 && !redo0) mbar_arrive(bars + (B_RH + wg) * 8);
            issue_kv(kv[u >> 1], P.dphi + (u & 1) * 512, P.dv - (u & 1) * DV_TILE, u & 1);
            if (u == 1 || u == 2) {
#pragma unroll
              for (int r = 0; r < 2; r++) sts128(av + ((u + 1) & 1) * 4096 + r * 512, vp[2 * u + 2 + r][0], vp[2 * u + 2 + r][1], vp[2 * u + 2 + r][2], vp[2 * u + 2 + r][3]);
            }
            if (u < 3) yield_slot();
          }
        }
        if (tw == 0) TS(19 + wg * 16);
        wg_wait<0>();
        pin(kv[0]); pin(kv[1]);
        if (__builtin_expect(__any_sync(0xffffffffu, redo), 0)) {
#pragma unroll 1
          for (int u = 0; u < 4; u++) {
            bar_sync(7 + wg, 128);
#pragma unroll 1
            for (int sg = 0; sg < 2; sg++) {
              float e[16];
              exp_shifted(p[0], sg ? -1.f : 1.f, e);
              pack_sums(e, pk[0], ps);
              store_phi(sphi ^ (sg * 64), pk[0], rcp2(qsum(ps[0])), rcp2(qsum(ps[1])));
            }
            sts128(av, vp[0][0], vp[0][1], vp[0][2], vp[0][3]);
            sts128(av + 512, vp[1][0], vp[1][1], vp[1][2], vp[1][3]);
            fence_async_smem();
            bar_sync(7 + wg, 128);
            issue_kv(kv[1], P.dphi, P.dv, u & 1);
            wg_wait<0>();
            pin(kv[1]);
#pragma unroll
            for (int c = 0; c < 16; c++) { p[0][c] = p[1][c]; p[1][c] = p[2][c]; p[2][c] = p[3][c]; }
#pragma unroll
            for (int c = 0; c < 24; c++) vp[c >> 2][c & 3] = vp[(c >> 2) + 2][c & 3];
            if (u == 1) {
#pragma unroll
              for (int c = 0; c < 20; c++) kv[0][c] = kv[1][c];
            }
          }
          if (__any_sync(0xffffffffu, redo0)) {
            stage_kv(0);
            fence_async_smem();
            warp_arrive(bars + (B_RH + wg) * 8, lane);
          }
        }
        if (tw == 0) TS(20 + wg * 16);
        bar_sync(7 + wg, 128);
        stage_kv(1);
      }
      {
        const uint32_t z = pack2(t == 0 ? kv[0][16] : t == 1 ? kv[1][16] : t == 2 ? kv[0][18] : kv[1][18], 0.0625f);
        sts128(sb + SM_PHI + 4096 + ((w & 1) * 16 + (t >> 1) * 8 + g) * 64 + ((((w & 2) + (t & 1)) ^ (g >> 1)) << 4), z, z, z, z);
      }
      fence_async_smem();
      warp_arrive(bars + (B_RED + wg) * 8, lane);
      if (tw == 0) TS(51 + wg * 4);
    }

    uint32_t stash = sb + 3 * STAGE + w * 4096 + lane * 16;
    const int rowl = wg * 64 + w * 16 + g;
    mbar_wait(bars + B_INFO * 8, 0, budget);
    const float gA = ldsf(sb + SM_G + rowl * 4), gB = ldsf(sb + SM_G + rowl * 4 + 32);
    __nv_bfloat16* og = P.o + (size_t)(bi * 128 + rowl) * kD + bj * 128 + t * 8;
    uint32_t own = sb + 3 * STAGE + rowl * 128 + ((t ^ g) << 4);
    uint32_t sx = sb + SM_PHI + (wg * 64 + w * 16 + (lane & 15)) * 128 + (((lane >> 4) ^ (lane & 7)) << 4);
    uint32_t routed = (lds32(sb + SM_MISC + 4) >> 4) == (uint32_t)(bi * 8 + warp);
    asm volatile("" : "+l"(og), "+r"(own), "+r"(stash), "+r"(sx), "+r"(routed));
    {
      float p[4][16];
      uint32_t ef[2][4][4];
      uint32_t qf[4][2][4];
      auto pack_q = [&](const float (&a)[64]) {
#pragma unroll
        for (int i = 0; i < 32; i++) qf[i >> 3][(i >> 2) & 1][i & 3] = pack2(a[2 * i], a[2 * i + 1]);
      };
      if (wg == 0) {
        float acc[2][64];
        bar_sync(2, 256);
        if (tw == 0) TS(22);
        mainloop128(acc, P.da, P.db, 32 % NST, (32 / NST) & 1, 12, lane0, budget, cta, 32);
#pragma unroll
        for (int n = 44; n < 48; n++) {
          mbar_wait(bars + (B_FX + n % NST) * 8, (n / NST) & 1, budget);
          kstep64(acc[0], P.da + (n % NST) * (STAGE >> 4), P.db + (n % NST) * (STAGE >> 4), 1);
          if (n == 47) break;
          wg_wait<1>();
          if (n == 44) {
            if (lane0) mbar_arrive_n(bars + (B_EM + 43 % NST) * 8, 2);
            pin(acc[1]);
            bar_sync(7, 128);
          }
          if (n <= 45) {
#pragma unroll
            for (int u = (n - 44) * 4; u < (n - 43) * 4; u++) {
              const float* a = &acc[1][8 * u];
              sts128(stash + u * 512, pack2(a[0], a[1]), pack2(a[2], a[3]), pack2(a[4], a[5]), pack2(a[6], a[7]));
            }
          }
          if (n == 45) warp_arrive(bars + B_QS * 8, lane);
        }
        bar_sync(13, 256);
        wg_wait<0>();
        pin(acc[0]);
        if (tw == 0) TS(15);
        pack_q(acc[0]);
        issue_pq(p, qf, P.dw, 0);
        if (PQ_FIRST) bar_arrive(14, 256);
        wg_wait<0>();
      } else {
        float acc[64];
        mbar_wait(bars + B_QS * 8, 0, budget);
#pragma unroll
        for (int u = 0; u < 8; u++) lds128(stash + u * 512, qf[u >> 1][u & 1]);
        pinr(qf[3]);
        bar_sync(13, 256);
#pragma unroll
        for (int n = 44; n < 48; n++) {
#pragma unroll
          for (int hf = 0; hf < 2; hf++) {
            const uint64_t da = P.da + 512 + (n % NST) * (STAGE >> 4) + hf * 4, db = P.db + (n % NST) * (STAGE >> 4) + hf * 256;
            wg_wait<1>();
            if (hf && n > 44 && lane0) mbar_arrive_n(bars + (B_EM + (n - 1) % NST) * 8, 2);
            wg_fence();
            wgmma_m64n128k16_ss<0, 1>(acc, da, db, n > 44 || hf);
            wgmma_m64n128k16_ss<0, 1>(acc, da + 2, db + 128, 1);
            wg_commit();
          }
          if (PQ_FIRST && n == 44) bar_sync(14, 256);
          if (n == 46) issue_pq(p, qf, P.dw, 0);
        }
        wg_wait<0>();
        pin(acc);
        if (lane0) { mbar_arrive_n(bars + (B_EM + 47 % NST) * 8, 2); mbar_arrive(bars + B_T3 * 8); }
        if (tw == 0) TS(23);
        pack_q(acc);
        issue_pq(p, qf, P.dw, 1);
        wg_wait<0>();
      }
#pragma unroll
      for (int h = 0; h < 4; h++) pin(p[h]);
      if (tw == 0) TS(24 + wg * 16);

      RG(1);
      pair_frags(p[0], p[1], ef);
      if (YIELD_EXP && wg) bar_arrive(11, 256);
#pragma unroll 1
      for (int pr = 0; pr < 2; pr++) {
        float np[2][20], nm[2][20];
        RG(2 + pr * 8);
        mbar_wait(bars + (B_KV + pr) * 8, 0, budget);
        RG(3 + pr * 8);
        wg_fence();
#pragma unroll
        for (int hh = 0; hh < 2; hh++) {
          const uint64_t dk = P.dkv - (uint64_t)pr * ((384ull << 16) - 512ull) - hh * ((255ull << 16) - 256ull);
          wgmma_m64n40k16_rs<1>(np[hh], ef[hh][0], dk, 0);
          wgmma_m64n40k16_rs<1>(np[hh], ef[hh][1], dk + 64, 1);
          wgmma_m64n40k16_rs<1>(nm[hh], ef[hh][2], dk + 128 - (126ull << 16), 0);
          wgmma_m64n40k16_rs<1>(nm[hh], ef[hh][3], dk + 192 - (126ull << 16), 1);
          wg_commit();
        }
        uint32_t o[4][4];
#pragma unroll
        for (int hh = 0; hh < 2; hh++) {
          if (hh == 0) wg_wait<1>(); else wg_wait<0>();
          pin(np[hh]); pin(nm[hh]);
          RG(4 + hh + pr * 8);
#pragma unroll
          for (int r = 0; r < 2; r++) {
            const float dp = np[hh][16 + 2 * r], sp = np[hh][17 + 2 * r], dm = nm[hh][16 + 2 * r], sm = nm[hh][17 + 2 * r];
            const float inv = (r == 0 ? gA : gB) * rcp(fmaf(dp, sm, fmaf(1e-6f, sm, dm) * sp));
            const float cp = sm * inv, cm = sp * inv;
#pragma unroll
            for (int c = 0; c < 4; c++)
              o[hh * 2 + r][c] = pack2(fmaf(np[hh][4 * c + 2 * r], cp, nm[hh][4 * c + 2 * r] * cm), fmaf(np[hh][4 * c + 2 * r + 1], cp, nm[hh][4 * c + 2 * r + 1] * cm));
          }
        }
        pinr(o);
        yield_slot();
#pragma unroll
        for (int i = 0; i < 4; i++) sts128((own ^ ((i >> 1) * 64)) + (i & 1) * 1024, o[i][0], o[i][1], o[i][2], o[i][3]);
        if (PUB_TMA || pr == 1) fence_async_smem();
        if (!PUB_TMA) {
          yield_slot();
#pragma unroll
          for (int i = 0; i < 4; i++)
            asm volatile("st.global.v4.u32 [%0], {%1,%2,%3,%4};" :: "l"(og + (i & 1) * 8 * kD + (i >> 1) * 32), "r"(o[i][0]), "r"(o[i][1]), "r"(o[i][2]), "r"(o[i][3]) : "memory");
        }
        RG(6 + pr * 8);
        warp_arrive(bars + (B_PUB + wg * 2 + pr) * 8, lane);
        RG(7 + pr * 8);
        if (tw == 0) TS(25 + pr + wg * 16);
        if (pr) break;
        og += 64; own += STAGE;
        if (YIELD_EXP && !wg) bar_sync(11, 256);
        RG(9);
        pin(p[2]); pin(p[3]);
        pair_frags(p[2], p[3], ef);
      }
    }
    uint32_t xf[8][4];
    if (!wg) {
      mbar_wait(bars + B_XT * 8, 0, budget);
      load_x(sx, xf);
      mbar_wait(bars + (B_PUB + 3) * 8, 0, budget);
    } else {
#pragma unroll
      for (int i = 0; i < 32; i++) xf[i >> 2][i & 3] = 0;
    }
    bar_sync(7 + wg, 128);

    RG(18);
    float oacc[64];
    {
      const uint64_t dam = P.da + wg * 512;
      mbar_wait2(bars + (B_FX + 3) * 8, bars + (B_FX + 4) * 8, 1, budget);
      kstep64(oacc, dam + 3 * (STAGE >> 4), P.db + 3 * (STAGE >> 4), 0);
      if (tw == 0) TS(27 + wg * 16);
      kstep64(oacc, dam + 4 * (STAGE >> 4), P.db + 4 * (STAGE >> 4), 1);
      wg_wait<1>();
      if (lane0) mbar_arrive(bars + (B_EM + 3) * 8);
      if (wg) {
        wg_wait<0>();
        if (lane0) mbar_arrive(bars + (B_EM + 4) * 8);
        mbar_wait(bars + B_XT * 8, 0, budget);
        load_x(sx, xf);
      }
      const uint32_t fy = (B_FY + wg * NST - B_FX) * 8;
      uint32_t rel = bars + (wg ? B_DUMMY : B_EM + 4) * 8;
#pragma unroll 1
      for (uint32_t ph = 0; ph < 2; ph++) {
#pragma unroll 1
        for (uint32_t slot = 0; slot < NST; slot++) {
          const uint32_t fx = bars + B_FX * 8 + slot * 8;
          mbar_wait2(fx, fx + fy, ph, budget);
          kstep64(oacc, dam + slot * (STAGE >> 4), P.db + slot * (STAGE >> 4), 1);
          wg_wait<1>();
          arrive_one(rel);
          rel = fx + (B_EM - B_FX) * 8;
        }
      }
      if (wg) {
#pragma unroll 1
        for (uint32_t slot = 0; slot < 4; slot++) mbar_wait(bars + (B_FY + NST + slot) * 8, 0, budget);
        bar_sync(12, 256);
      }
#pragma unroll 1
      for (uint32_t slot = 0; slot < 4; slot++) {
        if (!wg) mbar_wait2(bars + (B_FX + slot) * 8, bars + (B_FY + slot) * 8, 0, budget);
        wg_wait<1>();
        kstep64(oacc, dam + slot * (STAGE >> 4), P.db + slot * (STAGE >> 4), 1);
      }
      if (!wg) bar_arrive(12, 256);
    }
    if (__any_sync(0xffffffffu, routed)) { mbar_wait(bars + B_XP * 8, 0, budget); load_x(sx, xf); }
    const float hA = 1.0f - gA, hB = 1.0f - gB;
    float xv[64];
#pragma unroll
    for (int i = 0; i < 32; i++) { xv[2 * i] = bf_lo(xf[i >> 2][i & 3]); xv[2 * i + 1] = bf_hi(xf[i >> 2][i & 3]); }
    pin(xv);
    yield_slot();
    wg_wait<0>();
    pin(oacc);
    if (tw == 0) TS(29 + wg * 16);
#pragma unroll
    for (int hf = 0; hf < 2; hf++) {
#pragma unroll
      for (int u = hf * 4; u < hf * 4 + 4; u++) {
        const float* a = &oacc[8 * u];
        const float* b = &xv[8 * u];
        stmatrix4((sx ^ ((u & 3) * 32)) + hf * 16384,
                  pack2(fmaf(hA, b[0], a[0]), fmaf(hA, b[1], a[1])), pack2(fmaf(hB, b[2], a[2]), fmaf(hB, b[3], a[3])),
                  pack2(fmaf(hA, b[4], a[4]), fmaf(hA, b[5], a[5])), pack2(fmaf(hB, b[6], a[6]), fmaf(hB, b[7], a[7])));
        if (FIN_YIELD) yield_slot();
      }
      fence_async_smem();
      __syncwarp();
      if (elect_one()) tma_store(&mout, sb + SM_PHI + hf * 16384 + warp * 2048, bj * 128 + hf * 64, bi * 128 + warp * 16);
    }
    if (elect_one()) {
      asm volatile("cp.async.bulk.commit_group;" ::: "memory");
      asm volatile("cp.async.bulk.wait_group.read 0;" ::: "memory");
    }
  } else {
    asm volatile("setmaxnreg.dec.sync.aligned.u32 32;");
    if (warp == 8) {
      if (elect_one()) {
        TS(7);
#pragma unroll
        for (int s = 0; s < NST; s++) mbar_init(bars + (B_FX + s) * 8, 1);
        asm volatile("fence.mbarrier_init.release.cluster;" ::: "memory");
        fence_async_smem();
      }
      __syncwarp();
      bar_arrive(0, 512);
      if (elect_one()) {
#pragma unroll 1
        for (int n = 0; n < NST; n++) {
          const uint32_t st = sb + n * STAGE, fb = bars + (B_FX + n) * 8;
          KS(64 + n);
          mbar_expect_tx(fb, STAGE);
          tma_load(st, &mx, fb, n * 64, bi * 128);
          tma_load(st + 16384, &mw, fb, 1024 + bj * 128, n * 64);
          tma_load(st + 24576, &mw, fb, 2048 + bj * 128, n * 64);
        }
      }
      __syncwarp();
      bar_sync(10, 64);
    } else {
      if (warp == 9) {
        if (elect_one()) {
#pragma unroll
          for (int s = B_FY; s < B_NUM; s++) mbar_init(bars + s * 8, s < B_WPHI ? 1 : s < B_EM ? 4 : 8);
          asm volatile("fence.mbarrier_init.release.cluster;" ::: "memory");
          fence_async_smem();
        }
        __syncwarp();
        bar_arrive(10, 64);
      }
      bar_sync(0, 512);
    }
    if (!elect_one()) return;
    if (warp == 8) {
      uint32_t slot = 0, ph = 0;
#pragma unroll 1
      for (int n = NST; n < 48; n++) {
        const int t = n >> 4, k = n & 15;
        const int c0 = t == 2 ? bj * 128 : 1024 + bj * 128 + t * 64, c1 = t == 2 ? c0 + 64 : c0 + 1024;
        const uint32_t st = sb + slot * STAGE, fb = bars + (B_FX + slot) * 8;
        if (n <= NST + 3 * RSTEP && (n - NST) % RSTEP == 0) {
          const int c = (n - NST) / RSTEP;
          mbar_expect_tx(bars + (B_RX + c) * 8, c == 0 ? 8192 + 4096 : 8192);
          tma_load(sb + SM_PHI + c * 8192, &mxr, bars + (B_RX + c) * 8, c * 256, bi * 128 + bj * 16);
          if (c == 0) { bulk_load(sb + SM_V, P.w_r, 2048, bars + B_RX * 8); bulk_load(sb + SM_V + 2048, P.gate_w, 2048, bars + B_RX * 8); }
        }
        mbar_wait(bars + (B_EM + slot) * 8, ph, budget);
        KS(64 + n);
        mbar_expect_tx(fb, STAGE);
        tma_load(st, &mx, fb, k * 64, bi * 128);
        tma_load(st + 16384, &mw, fb, c0, k * 64);
        tma_load(st + 24576, &mw, fb, c1, k * 64);
        {
          const int m = n + WLEAD, tm = m >> 4;
          if ((m & 3) == (bi & 3)) {
            const int d0 = tm >= 2 ? bj * 128 : 1024 + bj * 128 + tm * 64, d1 = tm >= 2 ? d0 + 64 : d0 + 1024;
            tma_prefetch(tm == 3 ? &mwo : &mw, d0, (m & 15) * 64); tma_prefetch(tm == 3 ? &mwo : &mw, d1, (m & 15) * 64);
          }
        }
        if (++slot == NST) { slot = 0; ph ^= 1; }
      }
#pragma unroll 1
      for (int m = WLEAD + ((bi - WLEAD) & 3); m < 16; m += 4) { tma_prefetch(&mwo, bj * 128, m * 64); tma_prefetch(&mwo, bj * 128 + 64, m * 64); }
#pragma unroll 1
      for (int s = 0; s < 16; s++) {
        const int p = s < 2 ? s : (s >= 9), q = s < 9 ? s - 2 : s - 9;
        const int k0 = (s < 2 ? bj : q + (q >= bj)) * 128 + p * 64;
        const uint32_t st = sb + slot * STAGE, fb = bars + (B_FX + slot) * 8;
        mbar_wait(bars + (B_EM + slot) * 8, ph, budget);
        KS(64 + 48 + s);
        mbar_expect_tx(fb, 16384);
        tma_load(st + 16384, &mwo, fb, bj * 128, k0);
        tma_load(st + 24576, &mwo, fb, bj * 128 + 64, k0);
        if (++slot == NST) { slot = 0; ph ^= 1; }
      }
      if (REPF) prefetch_map(&mout);
    } else if (warp == 9) {
      prefetch_map(&mo); prefetch_map(&mout);
      uint32_t old;
      asm volatile("atom.add.release.gpu.global.u32 %0, [%1], 1;" : "=r"(old) : "l"(&g_cnt[C_START]) : "memory");
      sts32(sb + SM_MISC, (old & ~255u) + 256u);
      mbar_arrive(bars + B_EPOCH * 8);
      const CUtensorMap* m = (cta & 8) ? &mu : &mg;
      const int l0 = (cta >> 4) * 14, a0 = (cta & 7) * 64, d1 = (cta >> 2) * 112 - 14 * 16, d2 = (cta & 3) * 4;
      uint32_t buf = 0, ph = 0, tnext;
      asm volatile("mov.u32 %0, %%clock;" : "=r"(tnext));
#pragma unroll 1
      for (int c = 0; c < 21; c++) {
        const uint32_t dst = sb + moe_buf(buf), fb = bars + (B_MF + buf) * 8;
        mbar_wait(bars + (B_ME + buf) * 8, ph, budget);
        mbar_expect_tx(fb, 8192);
        if (c < 14) tma_load(dst, m, fb, a0 + ((l0 + c) >> 4) * 512, ((l0 + c) & 15) * 64); else tma_load3(dst, &md, fb, d1 + c * 16, d2);
        if (MLEAD && c >= 2 && c + MLEAD < 17) {
          const int f = c + MLEAD;
          if (f < 14) tma_prefetch(m, a0 + ((l0 + f) >> 4) * 512, ((l0 + f) & 15) * 64); else tma_prefetch3(&md, d1 + f * 16, d2);
        }
        if (MPACE) { uint32_t now; do { asm volatile("mov.u32 %0, %%clock;" : "=r"(now)); if ((int32_t)(now - tnext) >= 0) break; __nanosleep(20); } while (true); tnext = now + MPACE; }
        if (c == 16) {
#pragma unroll 1
          for (int f = 17; f < 21; f++) { __nanosleep(MGAP); tma_prefetch3(&md, d1 + f * 16, d2); }
        }
        if (c < 2) __nanosleep(MGAP);
        if (c == 17) mbar_arrive(bars + B_M2 * 8);
        if (++buf >= (c >= 14 ? 2 : 3)) { buf = 0; ph ^= 1; }
      }
      mbar_wait(bars + B_MD * 8, 0, budget);
      mbar_wait(bars + (B_RD + 1) * 8, 0, budget);
      mbar_wait(bars + XT_GATE * 8, 0, budget);
      mbar_expect_tx(bars + B_XT * 8, 32768);
      tma_load(sb + SM_PHI, &mx, bars + B_XT * 8, bj * 128, bi * 128);
      tma_load(sb + SM_PHI + 16384, &mx, bars + B_XT * 8, bj * 128 + 64, bi * 128);
      mbar_wait(bars + (B_PUB + 1) * 8, 0, budget);
      if (PUB_TMA) tma_store(&mo, sb + 4 * STAGE, bj * 128 + 64, bi * 128);
      mbar_wait(bars + (B_PUB + 3) * 8, 0, budget);
      if (PUB_TMA) {
        tma_store(&mo, sb + 4 * STAGE + 8192, bj * 128 + 64, bi * 128 + 64);
        asm volatile("cp.async.bulk.commit_group;" ::: "memory");
        asm volatile("cp.async.bulk.wait_group 0;" ::: "memory");
        mbar_arrive(bars + B_PS * 8);
      }
      signal_add(&g_cnt[(C_O + bi * 4 + 1) * 32], 32u);
      TS(57);
      wait_count<POLLF>(&g_cnt[(C_O + bi * 4 + 1) * 32], (old & ~255u) + 256u, budget);
      mbar_arrive(bars + B_P1 * 8);
      TS(3);
    } else {
      const int u = warp - 10, hp = bj * 2 + u;
      mbar_wait(bars + B_EPOCH * 8, 0, budget);
      const uint32_t target = lds32(sb + SM_MISC);
      mbar_wait(bars + B_INFO * 8, 0, budget);
      wait_count<200>(&g_cnt[C_START], target, budget);
      fence_async_global();
#pragma unroll 1
      for (int e = 0; e < 2; e++) {
        uint32_t* cnt = &g_cnt[(e ? C_O + bi * 4 + u * 2 : C_KV + hp) * 32];
        mbar_wait(bars + (e ? B_PUB + u * 2 : B_RH + u) * 8, 0, budget);
        if (e == 0) {
          static_assert(SM_PHI == SM_Z + 4096, "staging is contiguous");
#pragma unroll 1
          for (uint32_t c = 0; c < 10; c++) {
            if (c == 4) mbar_wait(bars + (B_RED + u) * 8, 0, budget);
            bulk_reduce(&g_kvr[hp * 2560 + c * 256], sb + SM_Z + c * 1024, 1024);
            if (c < 9) __nanosleep(u && c >= 3 ? RED_GAP1 : RED_GAP0);
          }
          asm volatile("cp.async.bulk.commit_group;" ::: "memory");
          asm volatile("cp.async.bulk.wait_group 0;" ::: "memory");
          TS(21 + u * 16);
          mbar_arrive(bars + (B_RD + u) * 8);
        }
        if (PUB_TMA && e) {
          tma_store(&mo, sb + 3 * STAGE + u * 8192, bj * 128, bi * 128 + u * 64);
          asm volatile("cp.async.bulk.commit_group;" ::: "memory");
          asm volatile("cp.async.bulk.wait_group 0;" ::: "memory");
        }
        signal_add(cnt, e ? 32u : 16u);
        TS(e ? 56 + u * 2 : 60 + u);
        if (REPF && !e) prefetch_map(&mo);
        if (e == 0) {
          mbar_wait(bars + (u ? B_M2 : B_RD + 1) * 8, 0, budget);
        }
        wait_count<POLLF>(cnt, target, budget);
        fence_async_global();
        if (e == 0) {
          mbar_expect_tx(bars + (B_KV + u) * 8, 10240);
          bulk_load(sb + SM_V + u * 8192, &g_kvr[hp * 2560], 8192, bars + (B_KV + u) * 8);
          bulk_load(sb + SM_Z + u * 2048, &g_kvr[hp * 2560 + 2048], 2048, bars + (B_KV + u) * 8);
          TS(38 + u);
        }
      }
      TS(2 + u * 2);
      if (u == 0) mbar_wait(bars + B_T3 * 8, 0, budget);
      uint32_t slot = 0, ph = 1;
#pragma unroll 1
      for (int s = 2; s < 16; s++) {
        const int p = s >= 9, q = s < 9 ? s - 2 : s - 9;
        if (PUB_TMA && s == 6) mbar_wait(bars + B_PS * 8, 0, budget);
        if (s == 9) { mbar_wait(bars + B_P1 * 8, 0, budget); fence_async_global(); }
        const uint32_t fb = bars + (B_FY + u * NST + slot) * 8;
        mbar_wait(bars + (B_EM + slot) * 8, ph, budget);
        mbar_expect_tx(fb, 8192);
        tma_load(sb + slot * STAGE + u * 8192, &mo, fb, (q + (q >= bj)) * 128 + p * 64, bi * 128 + u * 64);
        if (++slot == NST) { slot = 0; ph ^= 1; }
      }
    }
  }
}

typedef CUresult (*EncodeFn)(CUtensorMap*, CUtensorMapDataType, cuuint32_t, void*, const cuuint64_t*, const cuuint64_t*, const cuuint32_t*,
                             const cuuint32_t*, CUtensorMapInterleave, CUtensorMapSwizzle, CUtensorMapL2promotion, CUtensorMapFloatOOBfill);

void make_map(EncodeFn enc, CUtensorMap* m, const void* ptr, uint64_t cols, uint64_t rows, uint32_t bc, uint32_t br, CUtensorMapSwizzle swz) {
  const cuuint64_t dims[2] = {cols, rows}, strides[1] = {cols * 2};
  const cuuint32_t box[2] = {bc, br}, es[2] = {1, 1};
  enc(m, CU_TENSOR_MAP_DATA_TYPE_BFLOAT16, 2, const_cast<void*>(ptr), dims, strides, box, es, CU_TENSOR_MAP_INTERLEAVE_NONE, swz,
      CU_TENSOR_MAP_L2_PROMOTION_L2_128B, CU_TENSOR_MAP_FLOAT_OOB_FILL_NONE);
}

}

extern "C" void kernel_launch(void* const* d_in, const int* in_sizes, int n_in, void* d_out, int out_size) {
  (void)in_sizes; (void)n_in; (void)out_size;
  void* fn = nullptr;
  cudaDriverEntryPointQueryResult qr;
  cudaGetDriverEntryPoint("cuTensorMapEncodeTiled", &fn, cudaEnableDefault, &qr);
  EncodeFn enc = (EncodeFn)fn;
  void* o_ptr = nullptr;
  cudaGetSymbolAddress(&o_ptr, g_o);
  CUtensorMap mx, mw, mwo, mo, mout, mxr, mg, mu, md;
  make_map(enc, &mx, d_in[0], kD, kS, 64, 128, CU_TENSOR_MAP_SWIZZLE_128B);
  make_map(enc, &mxr, d_in[0], kD, kS, 256, 16, CU_TENSOR_MAP_SWIZZLE_NONE);
  make_map(enc, &mw, d_in[1], 3 * kD, kD, 64, 64, CU_TENSOR_MAP_SWIZZLE_128B);
  make_map(enc, &mwo, d_in[3], kD, kD, 64, 64, CU_TENSOR_MAP_SWIZZLE_128B);
  make_map(enc, &mo, o_ptr, kD, kS, 64, 64, CU_TENSOR_MAP_SWIZZLE_128B);
  make_map(enc, &mout, d_out, kD, kS, 64, 16, CU_TENSOR_MAP_SWIZZLE_128B);
  make_map(enc, &mg, d_in[6], kF, kD, 64, 64, CU_TENSOR_MAP_SWIZZLE_128B);
  make_map(enc, &mu, d_in[7], kF, kD, 64, 64, CU_TENSOR_MAP_SWIZZLE_128B);
  {
    const cuuint64_t dims[3] = {64, kF, 16}, strides[2] = {kD * 2, 128};
    const cuuint32_t box[3] = {64, 16, 4}, es[3] = {1, 1, 1};
    enc(&md, CU_TENSOR_MAP_DATA_TYPE_BFLOAT16, 3, d_in[8], dims, strides, box, es, CU_TENSOR_MAP_INTERLEAVE_NONE, CU_TENSOR_MAP_SWIZZLE_128B,
        CU_TENSOR_MAP_L2_PROMOTION_L2_128B, CU_TENSOR_MAP_FLOAT_OOB_FILL_NONE);
  }
  Params P;
  P.x = (const __nv_bfloat16*)d_in[0];
  P.w = (const __nv_bfloat16*)d_in[1];
  P.o = (__nv_bfloat16*)o_ptr;
  P.w_phi = (const __nv_bfloat16*)d_in[2];
  P.w_r = (const __nv_bfloat16*)d_in[5];
  P.gate_w = (const __nv_bfloat16*)d_in[9];
  P.da = make_desc(sb, 16, 1024, 1);
  P.db = make_desc(sb + 16384, 8192, 1024, 1);
  P.dw = make_desc(sb + SM_WPHI, 16, 512, 2);
  P.dphi = make_desc(sb + SM_PHI, 16, 1024, 1);
  P.dv = make_desc(sb + SM_V, SM_ONE - SM_V, 512, 2);
  P.dkv = make_desc(sb + SM_V, SM_Z - SM_V, 512, 2);
  P.dband = make_desc(sb + SM_BAND, 128, 128, 0);
  P.dxs = make_desc(sb + SM_BAND, 16, 128, 0);
  int dev = 0, sms = 0;
  cudaGetDevice(&dev);
  cudaDeviceGetAttribute(&sms, cudaDevAttrMultiProcessorCount, dev);
  auto kern = sms == 132 ? fused_kernel<true> : fused_kernel<false>;
  cudaFuncSetAttribute(kern, cudaFuncAttributeMaxDynamicSharedMemorySize, SM_ALLOC);
  kern<<<132, 512, SM_ALLOC, cudaStreamPerThread>>>(mx, mw, mwo, mo, mout, mxr, mg, mu, md, P);
}
```

```cpp
#include <cuda_runtime.h>
#include <cuda_bf16.h>
#include <cuda.h>
#include <stdint.h>

namespace {

template<int TA, int TB> __device__ __forceinline__ void wgmma_m64n128k16_ss(float (&d)[64], uint64_t da, uint64_t db, int scale_d) {
  asm volatile("{\n.reg .pred p;\nsetp.ne.b32 p, %66, 0;\n"
    "wgmma.mma_async.sync.aligned.m64n128k16.f32.bf16.bf16 "
    "{%0, %1, %2, %3, %4, %5, %6, %7, %8, %9, %10, %11, %12, %13, %14, %15, "
    "%16, %17, %18, %19, %20, %21, %22, %23, %24, %25, %26, %27, %28, %29, %30, %31, "
    "%32, %33, %34, %35, %36, %37, %38, %39, %40, %41, %42, %43, %44, %45, %46, %47, "
    "%48, %49, %50, %51, %52, %53, %54, %55, %56, %57, %58, %59, %60, %61, %62, %63}, "
    "%64, %65, p, 1, 1, %67, %68;\n}\n"
    : "+f"(d[0]), "+f"(d[1]), "+f"(d[2]), "+f"(d[3]), "+f"(d[4]), "+f"(d[5]), "+f"(d[6]), "+f"(d[7]),
      "+f"(d[8]), "+f"(d[9]), "+f"(d[10]), "+f"(d[11]), "+f"(d[12]), "+f"(d[13]), "+f"(d[14]), "+f"(d[15]),
      "+f"(d[16]), "+f"(d[17]), "+f"(d[18]), "+f"(d[19]), "+f"(d[20]), "+f"(d[21]), "+f"(d[22]), "+f"(d[23]),
      "+f"(d[24]), "+f"(d[25]), "+f"(d[26]), "+f"(d[27]), "+f"(d[28]), "+f"(d[29]), "+f"(d[30]), "+f"(d[31]),
      "+f"(d[32]), "+f"(d[33]), "+f"(d[34]), "+f"(d[35]), "+f"(d[36]), "+f"(d[37]), "+f"(d[38]), "+f"(d[39]),
      "+f"(d[40]), "+f"(d[41]), "+f"(d[42]), "+f"(d[43]), "+f"(d[44]), "+f"(d[45]), "+f"(d[46]), "+f"(d[47]),
      "+f"(d[48]), "+f"(d[49]), "+f"(d[50]), "+f"(d[51]), "+f"(d[52]), "+f"(d[53]), "+f"(d[54]), "+f"(d[55]),
      "+f"(d[56]), "+f"(d[57]), "+f"(d[58]), "+f"(d[59]), "+f"(d[60]), "+f"(d[61]), "+f"(d[62]), "+f"(d[63])
    : "l"(da), "l"(db), "r"(scale_d), "n"(TA), "n"(TB));
}

template<int TB> __device__ __forceinline__ void wgmma_m64n32k16_rs(float (&d)[16], const uint32_t (&a)[4], uint64_t db, int scale_d) {
  asm volatile("{\n.reg .pred p;\nsetp.ne.b32 p, %21, 0;\n"
    "wgmma.mma_async.sync.aligned.m64n32k16.f32.bf16.bf16 "
    "{%0, %1, %2, %3, %4, %5, %6, %7, %8, %9, %10, %11, %12, %13, %14, %15}, "
    "{%16, %17, %18, %19}, %20, p, 1, 1, %22;\n}\n"
    : "+f"(d[0]), "+f"(d[1]), "+f"(d[2]), "+f"(d[3]), "+f"(d[4]), "+f"(d[5]), "+f"(d[6]), "+f"(d[7]),
      "+f"(d[8]), "+f"(d[9]), "+f"(d[10]), "+f"(d[11]), "+f"(d[12]), "+f"(d[13]), "+f"(d[14]), "+f"(d[15])
    : "r"(a[0]), "r"(a[1]), "r"(a[2]), "r"(a[3]), "l"(db), "r"(scale_d), "n"(TB));
}

template<int TA, int TB> __device__ __forceinline__ void wgmma_m64n40k16_ss(float (&d)[20], uint64_t da, uint64_t db, int scale_d) {
  asm volatile("{\n.reg .pred p;\nsetp.ne.b32 p, %22, 0;\n"
    "wgmma.mma_async.sync.aligned.m64n40k16.f32.bf16.bf16 "
    "{%0, %1, %2, %3, %4, %5, %6, %7, %8, %9, %10, %11, %12, %13, %14, %15, "
    "%16, %17, %18, %19}, "
    "%20, %21, p, 1, 1, %23, %24;\n}\n"
    : "+f"(d[0]), "+f"(d[1]), "+f"(d[2]), "+f"(d[3]), "+f"(d[4]), "+f"(d[5]), "+f"(d[6]), "+f"(d[7]),
      "+f"(d[8]), "+f"(d[9]), "+f"(d[10]), "+f"(d[11]), "+f"(d[12]), "+f"(d[13]), "+f"(d[14]), "+f"(d[15]),
      "+f"(d[16]), "+f"(d[17]), "+f"(d[18]), "+f"(d[19])
    : "l"(da), "l"(db), "r"(scale_d), "n"(TA), "n"(TB));
}

template<int TB> __device__ __forceinline__ void wgmma_m64n40k16_rs(float (&d)[20], const uint32_t (&a)[4], uint64_t db, int scale_d) {
  asm volatile("{\n.reg .pred p;\nsetp.ne.b32 p, %25, 0;\n"
    "wgmma.mma_async.sync.aligned.m64n40k16.f32.bf16.bf16 "
    "{%0, %1, %2, %3, %4, %5, %6, %7, %8, %9, %10, %11, %12, %13, %14, %15, "
    "%16, %17, %18, %19}, "
    "{%20, %21, %22, %23}, %24, p, 1, 1, %26;\n}\n"
    : "+f"(d[0]), "+f"(d[1]), "+f"(d[2]), "+f"(d[3]), "+f"(d[4]), "+f"(d[5]), "+f"(d[6]), "+f"(d[7]),
      "+f"(d[8]), "+f"(d[9]), "+f"(d[10]), "+f"(d[11]), "+f"(d[12]), "+f"(d[13]), "+f"(d[14]), "+f"(d[15]),
      "+f"(d[16]), "+f"(d[17]), "+f"(d[18]), "+f"(d[19])
    : "r"(a[0]), "r"(a[1]), "r"(a[2]), "r"(a[3]), "l"(db), "r"(scale_d), "n"(TB));
}

template<int TA, int TB> __device__ __forceinline__ void wgmma_m64n8k16_ss(float (&d)[4], uint64_t da, uint64_t db, int scale_d) {
  asm volatile("{\n.reg .pred p;\nsetp.ne.b32 p, %6, 0;\n"
    "wgmma.mma_async.sync.aligned.m64n8k16.f32.bf16.bf16 "
    "{%0, %1, %2, %3}, "
    "%4, %5, p, 1, 1, %7, %8;\n}\n"
    : "+f"(d[0]), "+f"(d[1]), "+f"(d[2]), "+f"(d[3])
    : "l"(da), "l"(db), "r"(scale_d), "n"(TA), "n"(TB));
}

constexpr int kS = 2048, kD = 1024, kF = 3584;
constexpr int NST = 5, STAGE = 32768;
constexpr uint32_t sb = 1024;
constexpr int SM_V    = NST * STAGE;
constexpr int SM_Z    = SM_V + 16384;
constexpr int SM_PHI  = SM_Z + 4096;
constexpr int SM_MOE  = SM_PHI + 16384;
constexpr int SM_WPHI = SM_MOE + 16384;
constexpr int SM_ONE  = SM_WPHI + 8192;
constexpr int SM_BAND = SM_ONE + 1024;
constexpr int SM_G    = SM_BAND + 2176;
constexpr int SM_BAR  = SM_G + 512;
constexpr int SM_MISC = SM_BAR + 448;
constexpr int SM_TOTAL = SM_MISC + 64;
static_assert(SM_TOTAL <= 232448, "smem");
constexpr uint32_t bars = sb + SM_BAR;
constexpr int B_FX = 0  , B_FY = 5  , B_EPOCH = 16, B_RX = 17  , B_MF = 21  , B_RD = 24  , B_KV = 26  , B_M2 = 28, B_P1 = 29, B_PS = 15, B_XT = 30  ;
constexpr int B_WPHI = 32, B_INFO = 33, B_QS = 34, B_XP = 35, B_RED = 36  , B_PUB = 38  , B_ME = 42  , B_MD = 45, B_T3 = 46, B_RH = 47  , B_XR = 49;
constexpr int B_EM = 50  , B_DUMMY = 55, B_NUM = 56;
constexpr int C_START = 0, C_O = 1, C_KV = C_O + 64;

__device__ uint2 g_gate[kS];
__device__ uint2 g_key[128];
__device__ uint2 g_pre[4 * kF];
__device__ uint2 g_yp[32 * kD];
__device__ __align__(128) uint32_t g_kvr[16 * 2560];
__device__ __align__(128) uint32_t g_cnt[(C_KV + 32) * 32];
__device__ __align__(1024) __nv_bfloat16 g_o[kS * kD];
#define KS(id)
#define RG(id)
#define TS(id)
#define TSG(id)
constexpr int SM_ALLOC = SM_TOTAL;

#define POLL0 500
#define POLL1 150
#define RSTEP 1
#define POLLR 400
#define EARLY_N 2
#define EARLY_GAP 200
#define POLLF 50
#define RED_GAP0 250
#define RED_GAP1 0
#define YIELD_EXP 1
#define XS0 1
#define XS1 3
#define FIN_YIELD 0
#define MLEAD 0
#define MPACE 0
#define REPF 1
#define PQ_FIRST 1
#define PUB_TMA 1
#define WLEAD 11
#define MGAP 300

struct Params {
  const __nv_bfloat16 *x, *w, *w_phi, *w_r, *gate_w;
  __nv_bfloat16* o;
  uint64_t da, db, dw, dphi, dv, dkv, dband, dxs;
};

__device__ __forceinline__ uint32_t smem_u32(const void* p) { return (uint32_t)__cvta_generic_to_shared(p); }
__device__ __forceinline__ void mbar_init(uint32_t bar, uint32_t cnt) { asm volatile("mbarrier.init.shared::cta.b64 [%0], %1;" :: "r"(bar), "r"(cnt) : "memory"); }
__device__ __forceinline__ void mbar_expect_tx(uint32_t bar, uint32_t bytes) { asm volatile("mbarrier.arrive.expect_tx.shared::cta.b64 _, [%0], %1;" :: "r"(bar), "r"(bytes) : "memory"); }
__device__ __forceinline__ void mbar_arrive(uint32_t bar) { asm volatile("mbarrier.arrive.shared::cta.b64 _, [%0];" :: "r"(bar) : "memory"); }
__device__ __forceinline__ void mbar_arrive_n(uint32_t bar, uint32_t n) { asm volatile("mbarrier.arrive.shared::cta.b64 _, [%0], %1;" :: "r"(bar), "r"(n) : "memory"); }
constexpr int BUDGET = 1 << 20;
__device__ __forceinline__ void mbar_wait(uint32_t bar, uint32_t parity, int& budget) {
  asm volatile("{\n.reg .pred p;\n"
               "WAIT_L:\nmbarrier.try_wait.parity.shared::cta.b64 p, [%1], %2;\n@p bra WAIT_D;\n"
               "add.s32 %0, %0, -1;\nsetp.gt.s32 p, %0, 0;\n@p bra WAIT_L;\nWAIT_D:\n}"
               : "+r"(budget) : "r"(bar), "r"(parity) : "memory");
}
__device__ __forceinline__ void mbar_wait2(uint32_t bar0, uint32_t bar1, uint32_t parity, int& budget) {
  asm volatile("{\n.reg .pred p, q;\n"
               "WAIT_L:\nmbarrier.try_wait.parity.shared::cta.b64 p, [%1], %3;\nmbarrier.try_wait.parity.shared::cta.b64 q, [%2], %3;\n"
               "and.pred p, p, q;\n@p bra WAIT_D;\n"
               "add.s32 %0, %0, -1;\nsetp.gt.s32 p, %0, 0;\n@p bra WAIT_L;\nWAIT_D:\n}"
               : "+r"(budget) : "r"(bar0), "r"(bar1), "r"(parity) : "memory");
}
template <int SLEEP>
__device__ __forceinline__ void wait_count(const uint32_t* p, uint32_t target, int& budget) {
  asm volatile("{\n.reg .pred p;\n.reg .s32 v;\n"
               "WAIT_L:\nld.acquire.gpu.global.s32 v, [%1];\nsub.s32 v, v, %2;\nsetp.ge.s32 p, v, 0;\n@p bra WAIT_D;\n"
               "nanosleep.u32 %3;\nadd.s32 %0, %0, -4;\nsetp.gt.s32 p, %0, 0;\n@p bra WAIT_L;\nWAIT_D:\n}"
               : "+r"(budget) : "l"(p), "r"(target), "n"(SLEEP) : "memory");
}
__device__ __forceinline__ void tma_load(uint32_t dst, const CUtensorMap* m, uint32_t bar, int c0, int c1) {
  asm volatile("cp.async.bulk.tensor.2d.shared::cluster.global.mbarrier::complete_tx::bytes [%0], [%1, {%3, %4}], [%2];"
    :: "r"(dst), "l"(m), "r"(bar), "r"(c0), "r"(c1) : "memory");
}
__device__ __forceinline__ void tma_load3(uint32_t dst, const CUtensorMap* m, uint32_t bar, int c1, int c2) {
  asm volatile("cp.async.bulk.tensor.3d.shared::cluster.global.mbarrier::complete_tx::bytes [%0], [%1, {%5, %3, %4}], [%2];"
    :: "r"(dst), "l"(m), "r"(bar), "r"(c1), "r"(c2), "r"(0) : "memory");
}
__device__ __forceinline__ void tma_prefetch3(const CUtensorMap* m, int c1, int c2) {
  asm volatile("cp.async.bulk.prefetch.tensor.3d.L2.global [%0, {%3, %1, %2}];" :: "l"(m), "r"(c1), "r"(c2), "r"(0) : "memory");
}
__device__ __forceinline__ void tma_prefetch(const CUtensorMap* m, int c0, int c1) {
  asm volatile("cp.async.bulk.prefetch.tensor.2d.L2.global [%0, {%1, %2}];" :: "l"(m), "r"(c0), "r"(c1) : "memory");
}
__device__ __forceinline__ void tma_store(const CUtensorMap* m, uint32_t src, int c0, int c1) {
  asm volatile("cp.async.bulk.tensor.2d.global.shared::cta.bulk_group [%0, {%2, %3}], [%1];" :: "l"(m), "r"(src), "r"(c0), "r"(c1) : "memory");
}
__device__ __forceinline__ void bulk_load(uint32_t dst, const void* src, uint32_t bytes, uint32_t bar) {
  asm volatile("cp.async.bulk.shared::cluster.global.mbarrier::complete_tx::bytes [%0], [%1], %2, [%3];" :: "r"(dst), "l"(src), "r"(bytes), "r"(bar) : "memory");
}
__device__ __forceinline__ void bulk_reduce(void* dst, uint32_t src, uint32_t bytes) {
  asm volatile("cp.reduce.async.bulk.global.shared::cta.bulk_group.add.noftz.bf16 [%0], [%1], %2;" :: "l"(dst), "r"(src), "r"(bytes) : "memory");
}
__device__ __forceinline__ void prefetch_map(const CUtensorMap* m) { asm volatile("prefetch.tensormap [%0];" :: "l"(m) : "memory"); }
__device__ __forceinline__ bool elect_one() {
  uint32_t p;
  asm volatile("{\n.reg .pred P;\nelect.sync _|P, 0xffffffff;\nselp.u32 %0, 1, 0, P;\n}" : "=r"(p));
  return p;
}
__device__ __forceinline__ void wg_fence() { asm volatile("wgmma.fence.sync.aligned;" ::: "memory"); }
__device__ __forceinline__ void wg_commit() { asm volatile("wgmma.commit_group.sync.aligned;" ::: "memory"); }
template <int N> __device__ __forceinline__ void wg_wait() { asm volatile("wgmma.wait_group.sync.aligned %0;" :: "n"(N) : "memory"); }
template <int N> __device__ __forceinline__ void zero(float (&r)[N]) {
#pragma unroll
  for (int i = 0; i < N; i++) r[i] = 0.f;
}
template <int N> __device__ __forceinline__ void pin(float (&r)[N]) {
#pragma unroll
  for (int i = 0; i < N; i++) asm volatile("" : "+f"(r[i]) :: "memory");
}
template <int N> __device__ __forceinline__ void pinr(uint32_t (&r)[N][4]) {
#pragma unroll
  for (int i = 0; i < N; i++) asm volatile("" : "+r"(r[i][0]), "+r"(r[i][1]), "+r"(r[i][2]), "+r"(r[i][3]) :: "memory");
}
__device__ __forceinline__ void fence_async_smem() { asm volatile("fence.proxy.async.shared::cta;" ::: "memory"); }
__device__ __forceinline__ void fence_async_global() { asm volatile("fence.proxy.async.global;" ::: "memory"); }
__device__ __forceinline__ void bar_sync(int id, int n) { asm volatile("bar.sync %0, %1;" :: "r"(id), "r"(n) : "memory"); }
__device__ __forceinline__ void bar_arrive(int id, int n) { asm volatile("bar.arrive %0, %1;" :: "r"(id), "r"(n) : "memory"); }
__device__ __forceinline__ void arrive_one(uint32_t bar) {
  asm volatile("{\n.reg .pred p;\nelect.sync _|p, 0xffffffff;\n@p mbarrier.arrive.shared::cta.b64 _, [%0];\n}" :: "r"(bar) : "memory");
}
__device__ __forceinline__ void warp_arrive(uint32_t bar, int lane) { __syncwarp(); if (lane == 0) mbar_arrive(bar); }
__host__ __device__ constexpr uint64_t make_desc(uint32_t addr, uint32_t lbo, uint32_t sbo, uint32_t swz) {
  return (uint64_t)((addr & 0x3FFFF) >> 4) | ((uint64_t)((lbo & 0x3FFFF) >> 4) << 16) | ((uint64_t)(sbo >> 4) << 32) | ((uint64_t)swz << 62);
}
__device__ __forceinline__ uint32_t pack2(float lo, float hi) {
  uint32_t r; asm("cvt.rn.bf16x2.f32 %0, %1, %2;" : "=r"(r) : "f"(hi), "f"(lo)); return r;
}
__device__ __forceinline__ float bf_lo(uint32_t v) { return __uint_as_float(v << 16); }
__device__ __forceinline__ float bf_hi(uint32_t v) { return __uint_as_float(v & 0xffff0000u); }
__device__ __forceinline__ float ex2(float x) { float r; asm("ex2.approx.ftz.f32 %0, %1;" : "=f"(r) : "f"(x)); return r; }
__device__ __forceinline__ float rcp(float x) { float r; asm("rcp.approx.ftz.f32 %0, %1;" : "=f"(r) : "f"(x)); return r; }
constexpr float LOG2E = 1.4426950408889634f;
__device__ __forceinline__ float sigmoidf(float x) { return rcp(1.0f + ex2(-LOG2E * x)); }
__device__ __forceinline__ void sts128(uint32_t a, uint32_t x, uint32_t y, uint32_t z, uint32_t w) {
  asm volatile("st.shared.v4.u32 [%0], {%1,%2,%3,%4};" :: "r"(a), "r"(x), "r"(y), "r"(z), "r"(w) : "memory");
}
__device__ __forceinline__ void lds128(uint32_t a, uint32_t (&r)[4]) {
  asm volatile("ld.shared.v4.u32 {%0,%1,%2,%3}, [%4];" : "=r"(r[0]), "=r"(r[1]), "=r"(r[2]), "=r"(r[3]) : "r"(a) : "memory");
}
__device__ __forceinline__ void sts32(uint32_t a, uint32_t v) { asm volatile("st.shared.u32 [%0], %1;" :: "r"(a), "r"(v) : "memory"); }
__device__ __forceinline__ uint32_t lds32(uint32_t a) { uint32_t v; asm volatile("ld.shared.u32 %0, [%1];" : "=r"(v) : "r"(a) : "memory"); return v; }
__device__ __forceinline__ float ldsf(uint32_t a) { return __uint_as_float(lds32(a)); }
__device__ __forceinline__ void stmatrix4(uint32_t a, uint32_t r0, uint32_t r1, uint32_t r2, uint32_t r3) {
  asm volatile("stmatrix.sync.aligned.m8n8.x4.shared.b16 [%0], {%1,%2,%3,%4};" :: "r"(a), "r"(r0), "r"(r1), "r"(r2), "r"(r3) : "memory");
}
__device__ __forceinline__ void ldmatrix4(uint32_t a, uint32_t (&r)[4]) {
  asm volatile("ldmatrix.sync.aligned.m8n8.x4.shared.b16 {%0,%1,%2,%3}, [%4];" : "=r"(r[0]), "=r"(r[1]), "=r"(r[2]), "=r"(r[3]) : "r"(a) : "memory");
}
__device__ __forceinline__ uint4 ldg_nc(const void* p) {
  uint4 v; asm volatile("ld.global.nc.L1::no_allocate.v4.u32 {%0,%1,%2,%3}, [%4];" : "=r"(v.x), "=r"(v.y), "=r"(v.z), "=r"(v.w) : "l"(p)); return v;
}
__device__ __forceinline__ void st_tagged(uint2* p, uint32_t v, uint32_t tag) {
  asm volatile("{\n.reg .b64 x;\nmov.b64 x, {%1, %2};\nst.relaxed.gpu.global.b64 [%0], x;\n}" :: "l"(p), "r"(v), "r"(tag) : "memory");
}
__device__ __forceinline__ uint2 ld_tagged(const uint2* p) {
  uint2 v; asm volatile("{\n.reg .b64 x;\nld.relaxed.gpu.global.b64 x, [%2];\nmov.b64 {%0, %1}, x;\n}" : "=r"(v.x), "=r"(v.y) : "l"(p) : "memory"); return v;
}
__device__ __forceinline__ void probe(const uint2* p, uint32_t tag, int& budget) {
  do { __nanosleep(POLL0); budget -= 16; } while (!__all_sync(0xffffffffu, ld_tagged(p).y == tag) && budget > 0);
}
template <int STRIDE, int N>
__device__ __forceinline__ void gather(const uint2* p, uint32_t tag, float& s0, float& s1, int& budget) {
  uint32_t pause = 0;
  bool again;
#pragma unroll 1
  do {
    __nanosleep(pause);
    pause = POLL0;
    uint32_t bad = 0;
    s0 = s1 = 0.f;
#pragma unroll
    for (int i = 0; i < N; i++) {
      const uint2 w = ld_tagged(p + i * STRIDE);
      bad |= w.y ^ tag;
      if (i < N / 2) s0 += __uint_as_float(w.x); else s1 += __uint_as_float(w.x);
    }
    budget -= 16;
    again = __any_sync(0xffffffffu, bad != 0) && budget > 0;
  } while (again);
}
__device__ __forceinline__ void sts16(uint32_t a, uint32_t v) { asm volatile("st.shared.u16 [%0], %1;" :: "r"(a), "h"((uint16_t)v) : "memory"); }
__device__ __forceinline__ void signal_add(uint32_t* p, uint32_t v) { asm volatile("red.release.gpu.global.add.u32 [%0], %1;" :: "l"(p), "r"(v) : "memory"); }
__device__ __forceinline__ float qmax(float v) { v = fmaxf(v, __shfl_xor_sync(0xffffffffu, v, 1)); return fmaxf(v, __shfl_xor_sync(0xffffffffu, v, 2)); }
__device__ __forceinline__ float qsum(float v) { v += __shfl_xor_sync(0xffffffffu, v, 1); return v + __shfl_xor_sync(0xffffffffu, v, 2); }
__device__ __forceinline__ float fold(float a, float b, bool hi, int m) { return (hi ? b : a) + __shfl_xor_sync(0xffffffffu, hi ? a : b, m); }

__device__ __forceinline__ void yield_slot() { asm volatile("pmevent 0;" ::: "memory"); }
__device__ __forceinline__ float fma_v(float a, float b, float c) { float r; asm volatile("fma.rn.f32 %0, %1, %2, %3;" : "=f"(r) : "f"(a), "f"(b), "f"(c)); return r; }
constexpr uint32_t EXP_TOP = 0x58805880u;
__device__ __forceinline__ void exp_plain(const float (&p)[16], float (&ep)[16], float (&em)[16]) {
#pragma unroll
  for (int i = 0; i < 16; i++) { ep[i] = ex2(p[i]); em[i] = ex2(-p[i]); }
}
__device__ __forceinline__ void exp_shifted(const float (&p)[16], float sgn, float (&e)[16]) {
#pragma unroll
  for (int i = 0; i < 16; i++) e[i] = sgn * p[i];
#pragma unroll
  for (int o = 0; o < 4; o += 2) {
    const float mx = qmax(fmaxf(fmaxf(fmaxf(e[o], e[o + 1]), fmaxf(e[o + 4], e[o + 5])), fmaxf(fmaxf(e[o + 8], e[o + 9]), fmaxf(e[o + 12], e[o + 13]))));
#pragma unroll
    for (int c = 0; c < 4; c++) { e[4 * c + o] = ex2(e[4 * c + o] - mx); e[4 * c + o + 1] = ex2(e[4 * c + o + 1] - mx); }
  }
}
__device__ __forceinline__ void pack_sums(const float (&e)[16], uint32_t (&pk)[2][4], float (&s)[2]) {
#pragma unroll
  for (int i = 0; i < 8; i++) pk[i >> 2][i & 3] = pack2(e[2 * i], e[2 * i + 1]);
#pragma unroll
  for (int o = 0; o < 4; o += 2) s[o >> 1] = ((e[o] + e[o + 1]) + (e[o + 4] + e[o + 5])) + ((e[o + 8] + e[o + 9]) + (e[o + 12] + e[o + 13]));
}
__device__ __forceinline__ uint32_t rcp2(float s) { const float r = rcp(s); return pack2(r, r); }
__device__ __forceinline__ uint32_t add2(uint32_t a, uint32_t b) { uint32_t r; asm("add.rn.bf16x2 %0, %1, %2;" : "=r"(r) : "r"(a), "r"(b)); return r; }
__device__ __forceinline__ uint32_t mul2(uint32_t a, uint32_t b) { uint32_t r; asm("mul.rn.bf16x2 %0, %1, %2;" : "=r"(r) : "r"(a), "r"(b)); return r; }
__device__ __forceinline__ void store_phi(uint32_t a, const uint32_t (&pk)[2][4], uint32_t r0, uint32_t r1) {
#pragma unroll
  for (int h = 0; h < 2; h++) stmatrix4(a ^ (h * 32), mul2(pk[h][0], r0), mul2(pk[h][1], r1), mul2(pk[h][2], r0), mul2(pk[h][3], r1));
}
__device__ __forceinline__ uint32_t exp_frags(const float (&p)[16], uint32_t (&ef)[4][4], uint32_t top) {
  float ep[16], em[16];
  exp_plain(p, ep, em);
#pragma unroll
  for (int s = 0; s < 2; s++)
#pragma unroll
    for (int r = 0; r < 4; r++) {
      ef[s][r] = pack2(ep[8 * s + 2 * r], ep[8 * s + 2 * r + 1]);
      ef[2 + s][r] = pack2(em[8 * s + 2 * r], em[8 * s + 2 * r + 1]);
    }
#pragma unroll
  for (int s = 0; s < 4; s++) top = __vimax3_u16x2(__vimax3_u16x2(top, ef[s][0], ef[s][1]), ef[s][2], ef[s][3]);
  return top;
}
__device__ __forceinline__ void pair_frags(float (&p0)[16], const float (&p1)[16], uint32_t (&ef)[2][4][4]) {
  const uint32_t top = exp_frags(p1, ef[1], exp_frags(p0, ef[0], EXP_TOP));
  if (__builtin_expect(__any_sync(0xffffffffu, top != EXP_TOP), 0)) {
#pragma unroll 1
    for (int u = 0; u < 4; u++) {
      float e[16];
      exp_shifted(p0, (u & 1) ? -1.f : 1.f, e);
#pragma unroll
      for (int r = 0; r < 4; r++) {
#pragma unroll
        for (int s = 0; s < 6; s++) ef[s >> 2][s & 3][r] = ef[(s + 2) >> 2][(s + 2) & 3][r];
        ef[1][2][r] = pack2(e[2 * r], e[2 * r + 1]);
        ef[1][3][r] = pack2(e[8 + 2 * r], e[8 + 2 * r + 1]);
      }
      if (u & 1) {
#pragma unroll
        for (int c = 0; c < 16; c++) p0[c] = p1[c];
      }
    }
  }
}
__device__ __forceinline__ void issue_pq(float (&p)[4][16], const uint32_t (&qf)[4][2][4], uint64_t dw, int accumulate) {
  wg_fence();
#pragma unroll
  for (int h = 0; h < 4; h++) {
    wgmma_m64n32k16_rs<1>(p[h], qf[h][0], dw + h * 128, accumulate);
    wgmma_m64n32k16_rs<1>(p[h], qf[h][1], dw + h * 128 + 64, 1);
  }
  wg_commit();
}

#define SPLIT_BATCH 2
__device__ __forceinline__ void mainloop128(float (&acc)[2][64], uint64_t da0, uint64_t db0, uint32_t slot, uint32_t ph, int steps, bool lane0, int& budget, int cta, int n0) {
  uint32_t prev = 0;
#pragma unroll 1
  for (int k = 0; k < steps; k++) {
    mbar_wait(bars + B_FX * 8 + slot * 8, ph, budget);
    const uint64_t da = da0 + slot * (STAGE >> 4), db = db0 + slot * (STAGE >> 4);
#pragma unroll
    for (int kk = 0; kk < 4; kk++) {
      if (SPLIT_BATCH == 2 || !(kk & 1)) {
        wg_wait<1>();
        if (kk == 3 - SPLIT_BATCH && k > 0 && lane0) mbar_arrive_n(bars + B_EM * 8 + prev * 8, 2);
        wg_fence();
      }
      wgmma_m64n128k16_ss<0, 1>(acc[0], da + kk * 2, db + kk * 128, kk ? 1 : k);
      wgmma_m64n128k16_ss<0, 1>(acc[1], da + 512 + kk * 2, db + kk * 128, kk ? 1 : k);
      if (SPLIT_BATCH == 2 || (kk & 1)) wg_commit();
    }
    prev = slot;
    if (++slot == NST) { slot = 0; ph ^= 1; }
  }
}
__device__ __forceinline__ void kstep64(float (&acc)[64], uint64_t da, uint64_t db, int accumulate) {
  wg_fence();
#pragma unroll
  for (int kk = 0; kk < 4; kk++) wgmma_m64n128k16_ss<0, 1>(acc, da + kk * 2, db + kk * 128, kk ? 1 : accumulate);
  wg_commit();
}
__device__ __forceinline__ void issue_kv(float (&kv)[20], uint64_t dphi, uint64_t dv, int accumulate) {
  wg_fence();
#pragma unroll
  for (int ks = 0; ks < 4; ks++)
    wgmma_m64n40k16_ss<1, 1>(kv, dphi + ks * 128, dv - (uint64_t)ks * ((64ull << 16) - 64ull), ks ? 1 : accumulate);
  wg_commit();
}
template <int HALF>
__device__ __forceinline__ void load_x(uint32_t sx, uint32_t (&xf)[8][4]) {
#pragma unroll
  for (int u = 0; u < 8; u++) ldmatrix4((sx ^ ((u & 3) * 32)) + (u >> 2) * HALF, xf[u]);
}
__device__ __forceinline__ uint32_t moe_buf(uint32_t b) { return b == 2 ? SM_V + 8192 : SM_MOE + b * 8192; }
template <bool DOWN>
__device__ __forceinline__ void moe_chunks(float (&a)[4], int n, uint32_t& buf, uint32_t& ph, uint64_t da0, uint64_t db, bool lane0) {
  int budget = BUDGET;
  zero(a);
#pragma unroll 1
  for (int c = 0; c < n; c++) {
    mbar_wait(bars + B_MF * 8 + buf * 8, ph, budget);
    const uint64_t da = da0 + (moe_buf(buf) >> 4);
    wg_fence();
#pragma unroll
    for (int j = 0; j < 4; j++) wgmma_m64n8k16_ss<1, 0>(a, da + j * 128, DOWN ? db - j : db + j * 2, 1);
    wg_commit();
    wg_wait<0>();
    if (lane0) mbar_arrive(bars + B_ME * 8 + buf * 8);
    db += DOWN ? 16 : 8;
    if (++buf >= (DOWN ? 2 : 3)) { buf = 0; ph ^= 1; }
  }
  pin(a);
}
constexpr uint64_t DV_TILE = 4 * ((64ull << 16) - 64ull);

template <bool BY_SM>
__global__ void __launch_bounds__(512, 1)
fused_kernel(const __grid_constant__ CUtensorMap mx, const __grid_constant__ CUtensorMap mw, const __grid_constant__ CUtensorMap mwo,
             const __grid_constant__ CUtensorMap mo, const __grid_constant__ CUtensorMap mout, const __grid_constant__ CUtensorMap mxr,
             const __grid_constant__ CUtensorMap mg, const __grid_constant__ CUtensorMap mu, const __grid_constant__ CUtensorMap md,
             const __grid_constant__ CUtensorMap mx64, const Params P) {
  extern __shared__ __align__(1024) uint8_t smem_raw[];
  if (smem_u32(smem_raw) != sb) return;
  const int tid = threadIdx.x, lane = tid & 31;
  if (tid == 256) TS(1);
  const int warp = __shfl_sync(0xffffffffu, tid >> 5, 0), wg = warp >> 2;
  int budget = BUDGET;
  if (warp == 10 && elect_one()) { prefetch_map(&mx); prefetch_map(&mw); }
  int cta;
  {
    uint32_t smid;
    asm volatile("mov.u32 %0, %%smid;" : "=r"(smid));
    if (!BY_SM) cta = blockIdx.x;
    else if (smid < 64) cta = ((smid >> 1) & 7) * 16 + (smid >> 4) * 2 + (smid & 1);
    else if (smid < 120) { const int t = (smid - 64) >> 1, d = (t * 37) >> 8; cta = (1 + t - d * 7) * 16 + 8 + d * 2 + (smid & 1); }
    else cta = smid < 124 ? smid + 8 : smid - 116;
  }
  if (cta >= 128) {
    if (tid == 0) {
      const uint32_t old = atomicAdd(&g_cnt[C_START], 32u);
      wait_count<500>(&g_cnt[C_START], (old & ~255u) + 256u, budget);
    }
    return;
  }
  const int bi = (cta >> 5) * 4 + ((cta >> 2) & 3);
  const int bj = ((cta >> 4) & 1) * 4 + (cta & 3);

  if (wg == 3) {
    asm volatile("setmaxnreg.dec.sync.aligned.u32 64;");
    const int t3 = tid - 384, w3 = warp - 12;
    if (t3 == 0) TSG(0);
    if (t3 < 80) *reinterpret_cast<uint4*>(&g_kvr[cta * 320 + t3 * 4]) = make_uint4(0, 0, 0, 0);
    if (t3 < 17) st_tagged(t3 < 16 ? &g_gate[bi * 128 + bj * 16 + t3] : &g_key[cta], 0, 1);
    bar_sync(0, 512);
#pragma unroll 1
    for (int u = 0; u < 4; u++) {
      const uint4 v = ldg_nc(P.w_phi + bj * 4096 + (u * 128 + t3) * 8);
      sts128(sb + SM_WPHI + u * 2048 + (t3 >> 2) * 64 + (((t3 & 3) ^ ((t3 >> 3) & 3)) << 4),
             pack2(LOG2E * bf_lo(v.x), LOG2E * bf_hi(v.x)), pack2(LOG2E * bf_lo(v.y), LOG2E * bf_hi(v.y)),
             pack2(LOG2E * bf_lo(v.z), LOG2E * bf_hi(v.z)), pack2(LOG2E * bf_lo(v.w), LOG2E * bf_hi(v.w)));
    }
    fence_async_smem();
    warp_arrive(bars + B_WPHI * 8, lane);
    bar_sync(6, 256);
    const uint32_t target = lds32(sb + SM_MISC);
    uint32_t key;
    {
      uint32_t kk[4];
      lds128(sb + SM_MISC + 16, kk);
      if (t3 == 0) st_tagged(&g_key[cta], max(max(kk[0], kk[1]), max(kk[2], kk[3])), target);
      uint2 k, gv;
      __nanosleep(POLLR);
      do {
        __nanosleep(POLL1);
        k = ld_tagged(&g_key[t3]);
        gv = ld_tagged(&g_gate[bi * 128 + t3]);
        budget -= 4;
      } while (!__all_sync(0xffffffffu, k.y == target && gv.y == target) && budget > 0);
      key = __reduce_max_sync(0xffffffffu, k.x);
      if (lane == 0) sts32(sb + SM_MISC + 32 + w3 * 4, key);
      sts32(sb + SM_G + t3 * 4, gv.x);
      bar_sync(5, 128);
      lds128(sb + SM_MISC + 32, kk);
      key = max(max(kk[0], kk[1]), max(kk[2], kk[3]));
    }
    const int idx = (0xFFFF - (key & 0xFFFF)) & (kS - 1);
    if (t3 == 0) { sts32(sb + SM_MISC + 4, idx); TS(8); }
    warp_arrive(bars + B_INFO * 8, lane);
    {
      const uint4 v = ldg_nc(P.x + (size_t)idx * kD + t3 * 8);
      sts128(sb + SM_BAND + t3 * 16, v.x, v.y, v.z, v.w);
    }
    const int t2 = (lane & 3) * 2, row = w3 * 16 + (lane >> 2);
    float a[4];
    uint32_t buf = 0, ph = 0;
    fence_async_smem();
    bar_sync(5, 128);
    {
      const int r = cta >> 4;
#pragma unroll 1
      for (int part = 0; part < 2; part++) {
        const int n = part ? 14 - 2 * r : 2 * r;
        moe_chunks<false>(a, n, buf, ph, P.da, P.dxs + (part ? 0 : (16 - n) * 8), lane == 0);
        uint2* dst = &g_pre[(((cta >> 2) & 2) + 1 - part) * kF + ((r - 1 + part) * 8 + (cta & 7)) * 64 + row];
        if (t2 == 0 && n) { st_tagged(dst, __float_as_uint(a[0]), target); st_tagged(dst + 8, __float_as_uint(a[2]), target); }
      }
    }
    if (t3 == 0) TS(9);
    bar_sync(5, 128);
    sts128(sb + SM_BAND + t3 * 16, 0, 0, 0, 0);
    {
      __nanosleep(POLL0);
      float gs, us;
      gather<kF, 4>(&g_pre[(cta >> 2) * 112 + min(t3, 111)], target, gs, us, budget);
      bar_sync(5, 128);
      if (t3 < 112) sts16(sb + SM_BAND + 112 + (t3 >> 3) * 128 + (t3 & 7) * 2, pack2(gs * sigmoidf(gs) * us, 0.f));
    }
    fence_async_smem();
    bar_sync(5, 128);
    if (t3 == 0) TS(12);
    moe_chunks<true>(a, 7, buf, ph, P.da, P.dband + 7, lane == 0);
    if (t3 == 0) TS(10);
    if (t2 < 4) {
      uint2* dst = &g_yp[(cta >> 2) * kD + (cta & 3) * 256 + t2 * 64 + row];
      st_tagged(dst, __float_as_uint(a[0]), target); st_tagged(dst + 8, __float_as_uint(a[2]), target);
      st_tagged(dst + 64, __float_as_uint(a[1]), target); st_tagged(dst + 72, __float_as_uint(a[3]), target);
    }
    if (lane == 0) mbar_arrive(bars + B_MD * 8);
    if ((idx >> 7) == bi) {
      mbar_wait(bars + (B_PUB + 3) * 8, 0, budget);
      if (w3 == 0) probe(&g_yp[lane * kD + bj * 128], target, budget);
      bar_sync(5, 128);
      float y = 0.f;
#pragma unroll 1
      for (int hf = 0; hf < 2; hf++) {
        float y0, y1;
        gather<kD, 16>(&g_yp[hf * 16 * kD + bj * 128 + t3], target, y0, y1, budget);
        y += y0 + y1;
      }
      const uint32_t ob = key >> 16;
      const float upd = y * sigmoidf(__uint_as_float(((ob & 0x8000u) ? (ob ^ 0x8000u) : (~ob & 0xFFFFu)) << 16));
      const float xv = __bfloat162float(P.x[(size_t)idx * kD + bj * 128 + t3]);
      mbar_wait(bars + (B_XT + 1) * 8, 0, budget);
      sts16(sb + ((idx & 64) ? SM_PHI : SM_MOE) + (t3 >> 6) * 8192 + (idx & 63) * 128 + ((((t3 >> 3) & 7) ^ (idx & 7)) << 4) + (t3 & 7) * 2, pack2(xv + upd, 0.f));
      warp_arrive(bars + B_XP * 8, lane);
      if (t3 == 0) TS(11);
    }
  } else if (wg < 2) {
    if ((warp & 3) < EARLY_N && lane < (wg ? 8 : 16)) {
      const int n = warp & 3;
      const __nv_bfloat16* p = wg ? P.w + (size_t)(n * 64 + bi + (lane >> 1) * 16) * (3 * kD) + 1024 + (lane & 1) * 1024 + bj * 128
                                  : P.x + (size_t)(bi * 128 + bj * 16 + lane) * kD + n * 64;
      if (n) __nanosleep(n * EARLY_GAP);
      asm volatile("prefetch.global.L2 [%0];" :: "l"(p));
    }
    __syncwarp();
    asm volatile("setmaxnreg.inc.sync.aligned.u32 208;");
    const int tw = tid & 127, w = warp & 3, g = lane >> 2, t = lane & 3;
    const bool lane0 = lane == 0;
    if (wg == 0) sts128(sb + SM_ONE + (tw & 63) * 16, 0x3f803f80u, 0x3f803f80u, 0x3f803f80u, 0x3f803f80u);
    bar_sync(0, 512);
    if (wg == 1) {
      float sr[4], sg[4];
      zero(sr); zero(sg);
#pragma unroll 1
      for (int c = 0; c < 4; c++) {
        mbar_wait(bars + (B_RX + c) * 8, 0, budget);
        uint32_t rs[4], gs[4], xs[4][4];
        lds128(sb + SM_V + c * 512 + lane * 16, rs);
        lds128(sb + SM_V + 2048 + c * 512 + lane * 16, gs);
#pragma unroll
        for (int r = 0; r < 4; r++) lds128(sb + SM_PHI + c * 8192 + (w * 4 + r) * 512 + lane * 16, xs[r]);
#pragma unroll
        for (int e = 0; e < 4; e++) {
          const float r0 = bf_lo(rs[e]), r1 = bf_hi(rs[e]), g0 = bf_lo(gs[e]), g1 = bf_hi(gs[e]);
#pragma unroll
          for (int r = 0; r < 4; r++) {
            const float x0 = bf_lo(xs[r][e]), x1 = bf_hi(xs[r][e]);
            sr[r] = fma_v(x0, r0, sr[r]); sg[r] = fma_v(x0, g0, sg[r]);
            sr[r] = fma_v(x1, r1, sr[r]); sg[r] = fma_v(x1, g1, sg[r]);
            if (r != 1) yield_slot();
          }
        }
      }
      fence_async_smem();
      __syncwarp();
      if (lane < 3) mbar_arrive(bars + (B_ME + lane) * 8);
      const bool b4 = lane & 16, b3 = lane & 8, b2 = lane & 4;
      const float v = qsum(fold(fold(fold(sr[0], sg[0], b4, 16), fold(sr[2], sg[2], b4, 16), b3, 8),
                                fold(fold(sr[1], sg[1], b4, 16), fold(sr[3], sg[3], b4, 16), b3, 8), b2, 4));
      const int row = bi * 128 + bj * 16 + w * 4 + (g & 3);
      const uint32_t rb = pack2(v + 0.f, 0.f);
      const uint32_t ob = (rb & 0x8000u) ? (~rb & 0xFFFFu) : (rb | 0x8000u);
      const uint32_t best = __reduce_max_sync(0xffffffffu, b4 ? 0u : (ob << 16) | (0xFFFFu - row));
      mbar_wait(bars + B_EPOCH * 8, 0, budget);
      const uint32_t tag = lds32(sb + SM_MISC);
      if (lane0) sts32(sb + SM_MISC + 16 + w * 4, best);
      if (b4 && t == 0) st_tagged(&g_gate[row], __float_as_uint(sigmoidf(v)), tag);
      if (tw == 0) TS(14);
      bar_arrive(6, 256);
      bar_sync(1, 256);
    }

    {
      float acc[2][64];
      if (tw == 0) TS(16 + wg * 16);
      mainloop128(acc, P.da, P.db, wg, wg, 16, lane0, budget, cta, wg * 16);
      bar_sync(1 + wg, 256);
      wg_wait<0>();
      pin(acc[0]); pin(acc[1]);
      if (lane0) mbar_arrive_n(bars + (B_EM + wg) * 8, 2);
      if (tw == 0) TS(17 + wg * 16);
      float p[4][16];
      uint32_t vp[8][4];
      const uint32_t av = sb + SM_V + (w * 16 + g) * 64 + ((t ^ (g >> 1)) << 4);
      {
        uint32_t kf[4][2][4];
#pragma unroll
        for (int u = 0; u < 4; u++)
#pragma unroll
          for (int s = 0; s < 2; s++)
#pragma unroll
            for (int r = 0; r < 4; r++) kf[u][s][r] = pack2(acc[u & 1][16 * (u >> 1) + 8 * s + 2 * r], acc[u & 1][16 * (u >> 1) + 8 * s + 2 * r + 1]);
        mbar_wait(bars + B_WPHI * 8, 0, budget);
        const uint64_t dw = P.dw + wg * 256;
        wg_fence();
#pragma unroll
        for (int u = 0; u < 4; u++) {
          wgmma_m64n32k16_rs<1>(p[u], kf[u][0], dw + (u >> 1) * 128, 0);
          wgmma_m64n32k16_rs<1>(p[u], kf[u][1], dw + (u >> 1) * 128 + 64, 1);
        }
        wg_commit();
#pragma unroll
        for (int u = 0; u < 8; u++) {
          const float* a = &acc[(u >> 1) & 1][32 + 16 * (u >> 2) + 2 * (u & 1)];
          vp[u][0] = pack2(a[0], a[1]); vp[u][1] = pack2(a[4], a[5]); vp[u][2] = pack2(a[8], a[9]); vp[u][3] = pack2(a[12], a[13]);
          if (u < 4) sts128(av + (u >> 1) * 4096 + (u & 1) * 512, vp[u][0], vp[u][1], vp[u][2], vp[u][3]);
        }
        pinr(vp);
        wg_wait<0>();
#pragma unroll
        for (int u = 0; u < 4; u++) pin(p[u]);
      }
      if (tw == 0) TS(18 + wg * 16);
      float kv[2][20];
      {
        const uint32_t sphi = sb + SM_PHI + (w * 16 + (lane & 15)) * 128 + (((lane >> 4) ^ (lane & 7)) << 4);
        uint32_t top = EXP_TOP;
        uint32_t pk[4][2][4];
        float ps[2];
        uint32_t sh[1][4];
        uint32_t redo = 0, redo0 = 0;
        const uint32_t astage = sb + (w * 16 + (lane & 15)) * 64 + (((lane >> 4) ^ ((lane >> 1) & 3)) << 4);
        auto stage_kv = [&](int hh) {
#pragma unroll
          for (int q = 0; q < 2; q++) {
            const float* a = &kv[hh][8 * q];
            stmatrix4((astage ^ (q * 32)) + (hh ? SM_PHI : SM_Z), pack2(a[0], a[1]), pack2(a[2], a[3]), pack2(a[4], a[5]), pack2(a[6], a[7]));
          }
        };
#pragma unroll
        for (int i = 0; i < 11; i++) {
          if (i >= 3) {
            const int j = i - 3;
            const uint32_t s2 = add2(sh[0][2], sh[0][3]);
            top = __vmaxu2(top, s2);
            store_phi((sphi ^ ((j & 1) * 64)) + (j & 2) * 4096, pk[j & 3], rcp2(bf_lo(s2)), rcp2(bf_hi(s2)));
          }
          if (i >= 2 && i <= 9) { sh[0][2] = add2(sh[0][0], sh[0][1]); sh[0][3] = __shfl_xor_sync(0xffffffffu, sh[0][2], 2); }
          if (i >= 1 && i <= 8) { sh[0][0] = pack2(ps[0], ps[1]); sh[0][1] = __shfl_xor_sync(0xffffffffu, sh[0][0], 1); }
          if (i == 1) sh[0][2] = sh[0][3] = 0;
          if (i < 8) {
            pin(p[i >> 1]);
            float e[16];
#pragma unroll
            for (int c = 0; c < 16; c++) e[c] = ex2((i & 1) ? -p[i >> 1][c] : p[i >> 1][c]);
            pack_sums(e, pk[i & 3], ps);
            pinr(pk[i & 3]); pin(ps);
          }
          if (i < 10) yield_slot();
          if (i >= 1 && i <= 9) pinr(sh);
          if (i == 7) { wg_wait<0>(); pin(kv[0]); stage_kv(0); }
          if (i == 2 && wg) mbar_wait(bars + B_RD * 8, 0, budget);
          if (i >= 4 && !(i & 1)) {
            const int u = (i - 4) >> 1;
            fence_async_smem();
            wg_wait<0>();
            if (!(u & 1)) bar_sync(7 + wg, 128);
            else asm volatile("{\n.reg .pred p, q;\nsetp.ne.b32 p, %2, %3;\nbar.red.or.pred q, %1, 128, p;\nselp.u32 %0, 1, 0, q;\n}"
                              : "=r"(redo) : "r"(7 + wg), "r"(top), "n"(EXP_TOP) : "memory");
            if (u == 1) redo0 = redo;
            if (u == 2 && lane0 && !redo0) mbar_arrive(bars + (B_RH + wg) * 8);
            issue_kv(kv[u >> 1], P.dphi + (u & 1) * 512, P.dv - (u & 1) * DV_TILE, u & 1);
            if (u == 1 || u == 2) {
#pragma unroll
              for (int r = 0; r < 2; r++) sts128(av + ((u + 1) & 1) * 4096 + r * 512, vp[2 * u + 2 + r][0], vp[2 * u + 2 + r][1], vp[2 * u + 2 + r][2], vp[2 * u + 2 + r][3]);
            }
            if (u < 3) yield_slot();
          }
        }
        if (tw == 0) TS(19 + wg * 16);
        wg_wait<0>();
        pin(kv[0]); pin(kv[1]);
        if (__builtin_expect(__any_sync(0xffffffffu, redo), 0)) {
#pragma unroll 1
          for (int u = 0; u < 4; u++) {
            bar_sync(7 + wg, 128);
#pragma unroll 1
            for (int sg = 0; sg < 2; sg++) {
              float e[16];
              exp_shifted(p[0], sg ? -1.f : 1.f, e);
              pack_sums(e, pk[0], ps);
              store_phi(sphi ^ (sg * 64), pk[0], rcp2(qsum(ps[0])), rcp2(qsum(ps[1])));
            }
            sts128(av, vp[0][0], vp[0][1], vp[0][2], vp[0][3]);
            sts128(av + 512, vp[1][0], vp[1][1], vp[1][2], vp[1][3]);
            fence_async_smem();
            bar_sync(7 + wg, 128);
            issue_kv(kv[1], P.dphi, P.dv, u & 1);
            wg_wait<0>();
            pin(kv[1]);
#pragma unroll
            for (int c = 0; c < 16; c++) { p[0][c] = p[1][c]; p[1][c] = p[2][c]; p[2][c] = p[3][c]; }
#pragma unroll
            for (int c = 0; c < 24; c++) vp[c >> 2][c & 3] = vp[(c >> 2) + 2][c & 3];
            if (u == 1) {
#pragma unroll
              for (int c = 0; c < 20; c++) kv[0][c] = kv[1][c];
            }
          }
          if (__any_sync(0xffffffffu, redo0)) {
            stage_kv(0);
            fence_async_smem();
            warp_arrive(bars + (B_RH + wg) * 8, lane);
          }
        }
        if (tw == 0) TS(20 + wg * 16);
        bar_sync(7 + wg, 128);
        stage_kv(1);
      }
      {
        const uint32_t z = pack2(t == 0 ? kv[0][16] : t == 1 ? kv[1][16] : t == 2 ? kv[0][18] : kv[1][18], 0.0625f);
        sts128(sb + SM_PHI + 4096 + ((w & 1) * 16 + (t >> 1) * 8 + g) * 64 + ((((w & 2) + (t & 1)) ^ (g >> 1)) << 4), z, z, z, z);
      }
      fence_async_smem();
      warp_arrive(bars + (B_RED + wg) * 8, lane);
      if (tw == 0) TS(51 + wg * 4);
    }

    uint32_t stash = sb + 3 * STAGE + w * 4096 + lane * 16;
    const int rowl = wg * 64 + w * 16 + g;
    mbar_wait(bars + B_INFO * 8, 0, budget);
    const float gA = ldsf(sb + SM_G + rowl * 4), gB = ldsf(sb + SM_G + rowl * 4 + 32);
    __nv_bfloat16* og = P.o + (size_t)(bi * 128 + rowl) * kD + bj * 128 + t * 8;
    uint32_t own = sb + 3 * STAGE + rowl * 128 + ((t ^ g) << 4);
    uint32_t sx = sb + (wg ? SM_PHI : SM_MOE) + (w * 16 + (lane & 15)) * 128 + (((lane >> 4) ^ (lane & 7)) << 4);
    uint32_t routed = lds32(sb + SM_MISC + 4) - (bi * 128 + rowl);
    asm volatile("" : "+l"(og), "+r"(own), "+r"(stash), "+r"(sx), "+r"(routed));
    {
      float p[4][16];
      uint32_t ef[2][4][4];
      uint32_t qf[4][2][4];
      auto pack_q = [&](const float (&a)[64]) {
#pragma unroll
        for (int i = 0; i < 32; i++) qf[i >> 3][(i >> 2) & 1][i & 3] = pack2(a[2 * i], a[2 * i + 1]);
      };
      if (wg == 0) {
        float acc[2][64];
        bar_sync(2, 256);
        if (tw == 0) TS(22);
        mainloop128(acc, P.da, P.db, 32 % NST, (32 / NST) & 1, 12, lane0, budget, cta, 32);
#pragma unroll
        for (int n = 44; n < 48; n++) {
          mbar_wait(bars + (B_FX + n % NST) * 8, (n / NST) & 1, budget);
          kstep64(acc[0], P.da + (n % NST) * (STAGE >> 4), P.db + (n % NST) * (STAGE >> 4), 1);
          if (n == 47) break;
          wg_wait<1>();
          if (n == 44) {
            if (lane0) mbar_arrive_n(bars + (B_EM + 43 % NST) * 8, 2);
            pin(acc[1]);
            bar_sync(7, 128);
          }
          if (n <= 45) {
#pragma unroll
            for (int u = (n - 44) * 4; u < (n - 43) * 4; u++) {
              const float* a = &acc[1][8 * u];
              sts128(stash + u * 512, pack2(a[0], a[1]), pack2(a[2], a[3]), pack2(a[4], a[5]), pack2(a[6], a[7]));
            }
          }
          if (n == 45) warp_arrive(bars + B_QS * 8, lane);
        }
        bar_sync(13, 256);
        wg_wait<0>();
        pin(acc[0]);
        if (tw == 0) TS(15);
        pack_q(acc[0]);
        issue_pq(p, qf, P.dw, 0);
        if (PQ_FIRST) bar_arrive(14, 256);
        wg_wait<0>();
      } else {
        float acc[64];
        mbar_wait(bars + B_QS * 8, 0, budget);
#pragma unroll
        for (int u = 0; u < 8; u++) lds128(stash + u * 512, qf[u >> 1][u & 1]);
        pinr(qf[3]);
        bar_sync(13, 256);
#pragma unroll
        for (int n = 44; n < 48; n++) {
#pragma unroll
          for (int hf = 0; hf < 2; hf++) {
            const uint64_t da = P.da + 512 + (n % NST) * (STAGE >> 4) + hf * 4, db = P.db + (n % NST) * (STAGE >> 4) + hf * 256;
            wg_wait<1>();
            if (hf && n > 44 && lane0) mbar_arrive_n(bars + (B_EM + (n - 1) % NST) * 8, 2);
            wg_fence();
            wgmma_m64n128k16_ss<0, 1>(acc, da, db, n > 44 || hf);
            wgmma_m64n128k16_ss<0, 1>(acc, da + 2, db + 128, 1);
            wg_commit();
          }
          if (PQ_FIRST && n == 44) bar_sync(14, 256);
          if (n == 46) issue_pq(p, qf, P.dw, 0);
        }
        wg_wait<0>();
        pin(acc);
        if (lane0) { mbar_arrive_n(bars + (B_EM + 47 % NST) * 8, 2); mbar_arrive(bars + B_T3 * 8); }
        if (tw == 0) TS(23);
        pack_q(acc);
        issue_pq(p, qf, P.dw, 1);
        wg_wait<0>();
      }
#pragma unroll
      for (int h = 0; h < 4; h++) pin(p[h]);
      if (tw == 0) TS(24 + wg * 16);

      RG(1);
      pair_frags(p[0], p[1], ef);
      if (YIELD_EXP && wg) bar_arrive(11, 256);
#pragma unroll 1
      for (int pr = 0; pr < 2; pr++) {
        float np[2][20], nm[2][20];
        RG(2 + pr * 8);
        mbar_wait(bars + (B_KV + pr) * 8, 0, budget);
        RG(3 + pr * 8);
        wg_fence();
#pragma unroll
        for (int hh = 0; hh < 2; hh++) {
          const uint64_t dk = P.dkv - (uint64_t)pr * ((384ull << 16) - 512ull) - hh * ((255ull << 16) - 256ull);
          wgmma_m64n40k16_rs<1>(np[hh], ef[hh][0], dk, 0);
          wgmma_m64n40k16_rs<1>(np[hh], ef[hh][1], dk + 64, 1);
          wgmma_m64n40k16_rs<1>(nm[hh], ef[hh][2], dk + 128 - (126ull << 16), 0);
          wgmma_m64n40k16_rs<1>(nm[hh], ef[hh][3], dk + 192 - (126ull << 16), 1);
          wg_commit();
        }
        uint32_t o[4][4];
#pragma unroll
        for (int hh = 0; hh < 2; hh++) {
          if (hh == 0) wg_wait<1>(); else wg_wait<0>();
          pin(np[hh]); pin(nm[hh]);
          RG(4 + hh + pr * 8);
#pragma unroll
          for (int r = 0; r < 2; r++) {
            const float dp = np[hh][16 + 2 * r], sp = np[hh][17 + 2 * r], dm = nm[hh][16 + 2 * r], sm = nm[hh][17 + 2 * r];
            const float inv = (r == 0 ? gA : gB) * rcp(fmaf(dp, sm, fmaf(1e-6f, sm, dm) * sp));
            const float cp = sm * inv, cm = sp * inv;
#pragma unroll
            for (int c = 0; c < 4; c++)
              o[hh * 2 + r][c] = pack2(fmaf(np[hh][4 * c + 2 * r], cp, nm[hh][4 * c + 2 * r] * cm), fmaf(np[hh][4 * c + 2 * r + 1], cp, nm[hh][4 * c + 2 * r + 1] * cm));
          }
        }
        pinr(o);
        yield_slot();
#pragma unroll
        for (int i = 0; i < 4; i++) sts128((own ^ ((i >> 1) * 64)) + (i & 1) * 1024, o[i][0], o[i][1], o[i][2], o[i][3]);
        if (PUB_TMA || pr == 1) fence_async_smem();
        if (!PUB_TMA) {
          yield_slot();
#pragma unroll
          for (int i = 0; i < 4; i++)
            asm volatile("st.global.v4.u32 [%0], {%1,%2,%3,%4};" :: "l"(og + (i & 1) * 8 * kD + (i >> 1) * 32), "r"(o[i][0]), "r"(o[i][1]), "r"(o[i][2]), "r"(o[i][3]) : "memory");
        }
        RG(6 + pr * 8);
        warp_arrive(bars + (B_PUB + wg * 2 + pr) * 8, lane);
        RG(7 + pr * 8);
        if (tw == 0) TS(25 + pr + wg * 16);
        if (pr) break;
        og += 64; own += STAGE;
        if (YIELD_EXP && !wg) bar_sync(11, 256);
        RG(9);
        pin(p[2]); pin(p[3]);
        pair_frags(p[2], p[3], ef);
      }
    }
    uint32_t xf[8][4];
    if (!wg) {
      mbar_wait(bars + B_XT * 8, 0, budget);
      load_x<STAGE>(sx - SM_MOE, xf);
      pinr(xf);
      fence_async_smem();
      warp_arrive(bars + B_XR * 8, lane);
      mbar_wait(bars + (B_PUB + 3) * 8, 0, budget);
    } else {
#pragma unroll
      for (int i = 0; i < 32; i++) xf[i >> 2][i & 3] = 0;
    }
    bar_sync(7 + wg, 128);

    RG(18);
    float oacc[64];
    {
      const uint64_t dam = P.da + wg * 512;
      mbar_wait2(bars + (B_FX + 3) * 8, bars + (B_FX + 4) * 8, 1, budget);
      kstep64(oacc, dam + 3 * (STAGE >> 4), P.db + 3 * (STAGE >> 4), 0);
      if (tw == 0) TS(27 + wg * 16);
      kstep64(oacc, dam + 4 * (STAGE >> 4), P.db + 4 * (STAGE >> 4), 1);
      wg_wait<1>();
      if (lane0) mbar_arrive(bars + (B_EM + 3) * 8);
      if (wg) {
        wg_wait<0>();
        if (lane0) mbar_arrive(bars + (B_EM + 4) * 8);
        mbar_wait(bars + (B_XT + 1) * 8, 0, budget);
        load_x<8192>(sx, xf);
      }
      const uint32_t fy = (B_FY + wg * NST - B_FX) * 8;
      uint32_t rel = bars + (wg ? B_DUMMY : B_EM + 4) * 8;
#pragma unroll 1
      for (uint32_t ph = 0; ph < 2; ph++) {
#pragma unroll 1
        for (uint32_t slot = 0; slot < NST; slot++) {
          const uint32_t fx = bars + B_FX * 8 + slot * 8;
          mbar_wait2(fx, fx + fy, ph, budget);
          kstep64(oacc, dam + slot * (STAGE >> 4), P.db + slot * (STAGE >> 4), 1);
          wg_wait<1>();
          arrive_one(rel);
          rel = fx + (B_EM - B_FX) * 8;
        }
      }
      if (wg) {
#pragma unroll 1
        for (uint32_t slot = 0; slot < 4; slot++) mbar_wait(bars + (B_FY + NST + slot) * 8, 0, budget);
        bar_sync(12, 256);
      }
#pragma unroll 1
      for (uint32_t slot = 0; slot < 4; slot++) {
        if (!wg) mbar_wait2(bars + (B_FX + slot) * 8, bars + (B_FY + slot) * 8, 0, budget);
        wg_wait<1>();
        kstep64(oacc, dam + slot * (STAGE >> 4), P.db + slot * (STAGE >> 4), 1);
      }
      if (!wg) bar_arrive(12, 256);
    }
    if (!wg) mbar_wait(bars + B_MD * 8, 0, budget);
    if (__any_sync(0xffffffffu, (routed & ~8u) == 0)) {
      uint32_t xu[8][4];
      mbar_wait(bars + B_XP * 8, 0, budget);
      load_x<8192>(sx, xu);
#pragma unroll
      for (int i = 0; i < 32; i++) if (routed == (i & 1) * 8u) xf[i >> 2][i & 3] = xu[i >> 2][i & 3];
    }
    const float hA = 1.0f - gA, hB = 1.0f - gB;
    float xv[64];
#pragma unroll
    for (int i = 0; i < 32; i++) { xv[2 * i] = bf_lo(xf[i >> 2][i & 3]); xv[2 * i + 1] = bf_hi(xf[i >> 2][i & 3]); }
    pin(xv);
    yield_slot();
    wg_wait<0>();
    pin(oacc);
    if (tw == 0) TS(29 + wg * 16);
#pragma unroll
    for (int hf = 0; hf < 2; hf++) {
#pragma unroll
      for (int u = hf * 4; u < hf * 4 + 4; u++) {
        const float* a = &oacc[8 * u];
        const float* b = &xv[8 * u];
        stmatrix4((sx ^ ((u & 3) * 32)) + hf * 8192,
                  pack2(fmaf(hA, b[0], a[0]), fmaf(hA, b[1], a[1])), pack2(fmaf(hB, b[2], a[2]), fmaf(hB, b[3], a[3])),
                  pack2(fmaf(hA, b[4], a[4]), fmaf(hA, b[5], a[5])), pack2(fmaf(hB, b[6], a[6]), fmaf(hB, b[7], a[7])));
        if (FIN_YIELD) yield_slot();
      }
      fence_async_smem();
      __syncwarp();
      if (elect_one()) tma_store(&mout, sb + (wg ? SM_PHI : SM_MOE) + hf * 8192 + w * 2048, bj * 128 + hf * 64, bi * 128 + warp * 16);
    }
    if (elect_one()) {
      asm volatile("cp.async.bulk.commit_group;" ::: "memory");
      asm volatile("cp.async.bulk.wait_group.read 0;" ::: "memory");
    }
  } else {
    asm volatile("setmaxnreg.dec.sync.aligned.u32 32;");
    if (warp == 8) {
      if (elect_one()) {
        TS(7);
#pragma unroll
        for (int s = 0; s < NST; s++) mbar_init(bars + (B_FX + s) * 8, 1);
        asm volatile("fence.mbarrier_init.release.cluster;" ::: "memory");
        fence_async_smem();
      }
      __syncwarp();
      bar_arrive(0, 512);
      if (elect_one()) {
#pragma unroll 1
        for (int n = 0; n < NST; n++) {
          const uint32_t st = sb + n * STAGE, fb = bars + (B_FX + n) * 8;
          KS(64 + n);
          mbar_expect_tx(fb, STAGE);
          tma_load(st, &mx, fb, n * 64, bi * 128);
          tma_load(st + 16384, &mw, fb, 1024 + bj * 128, n * 64);
          tma_load(st + 24576, &mw, fb, 2048 + bj * 128, n * 64);
        }
      }
      __syncwarp();
      bar_sync(10, 64);
    } else {
      if (warp == 9) {
        if (elect_one()) {
#pragma unroll
          for (int s = B_FY; s < B_NUM; s++) mbar_init(bars + s * 8, s < B_WPHI ? 1 : s < B_EM ? 4 : 8);
          asm volatile("fence.mbarrier_init.release.cluster;" ::: "memory");
          fence_async_smem();
        }
        __syncwarp();
        bar_arrive(10, 64);
      }
      bar_sync(0, 512);
    }
    if (!elect_one()) return;
    if (warp == 8) {
      uint32_t slot = 0, ph = 0;
#pragma unroll 1
      for (int n = NST; n < 48; n++) {
        const int t = n >> 4, k = n & 15;
        const int c0 = t == 2 ? bj * 128 : 1024 + bj * 128 + t * 64, c1 = t == 2 ? c0 + 64 : c0 + 1024;
        const uint32_t st = sb + slot * STAGE, fb = bars + (B_FX + slot) * 8;
        if (n <= NST + 3 * RSTEP && (n - NST) % RSTEP == 0) {
          const int c = (n - NST) / RSTEP;
          mbar_expect_tx(bars + (B_RX + c) * 8, c == 0 ? 8192 + 4096 : 8192);
          tma_load(sb + SM_PHI + c * 8192, &mxr, bars + (B_RX + c) * 8, c * 256, bi * 128 + bj * 16);
          if (c == 0) { bulk_load(sb + SM_V, P.w_r, 2048, bars + B_RX * 8); bulk_load(sb + SM_V + 2048, P.gate_w, 2048, bars + B_RX * 8); }
        }
        mbar_wait(bars + (B_EM + slot) * 8, ph, budget);
        KS(64 + n);
        mbar_expect_tx(fb, STAGE);
        tma_load(st, &mx, fb, k * 64, bi * 128);
        tma_load(st + 16384, &mw, fb, c0, k * 64);
        tma_load(st + 24576, &mw, fb, c1, k * 64);
        {
          const int m = n + WLEAD, tm = m >> 4;
          if ((m & 3) == (bi & 3)) {
            const int d0 = tm >= 2 ? bj * 128 : 1024 + bj * 128 + tm * 64, d1 = tm >= 2 ? d0 + 64 : d0 + 1024;
            tma_prefetch(tm == 3 ? &mwo : &mw, d0, (m & 15) * 64); tma_prefetch(tm == 3 ? &mwo : &mw, d1, (m & 15) * 64);
          }
        }
        if (++slot == NST) { slot = 0; ph ^= 1; }
      }
#pragma unroll 1
      for (int m = WLEAD + ((bi - WLEAD) & 3); m < 16; m += 4) { tma_prefetch(&mwo, bj * 128, m * 64); tma_prefetch(&mwo, bj * 128 + 64, m * 64); }
#pragma unroll 1
      for (int s = 0; s < 16; s++) {
        const int p = s < 2 ? s : (s >= 9), q = s < 9 ? s - 2 : s - 9;
        const int k0 = (s < 2 ? bj : q + (q >= bj)) * 128 + p * 64;
        const uint32_t st = sb + slot * STAGE, fb = bars + (B_FX + slot) * 8;
        mbar_wait(bars + (B_EM + slot) * 8, ph, budget);
        KS(64 + 48 + s);
        mbar_expect_tx(fb, 16384);
        tma_load(st + 16384, &mwo, fb, bj * 128, k0);
        tma_load(st + 24576, &mwo, fb, bj * 128 + 64, k0);
        if (s == XS1 || s == XS0) {
#pragma unroll 1
          for (int m = s == XS1; m >= (s != XS0); m--) {
            if (m) mbar_wait(bars + (B_RD + 1) * 8, 0, budget);
            mbar_expect_tx(bars + (B_XT + m) * 8, 16384);
            tma_load(sb + (m ? SM_PHI : 0), &mx64, bars + (B_XT + m) * 8, bj * 128, bi * 128 + m * 64);
            tma_load(sb + (m ? SM_PHI + 8192 : STAGE), &mx64, bars + (B_XT + m) * 8, bj * 128 + 64, bi * 128 + m * 64);
          }
        }
        if (++slot == NST) { slot = 0; ph ^= 1; }
      }
      if (REPF) prefetch_map(&mout);
    } else if (warp == 9) {
      prefetch_map(&mo); prefetch_map(&mout);
      uint32_t old;
      asm volatile("atom.add.release.gpu.global.u32 %0, [%1], 1;" : "=r"(old) : "l"(&g_cnt[C_START]) : "memory");
      sts32(sb + SM_MISC, (old & ~255u) + 256u);
      mbar_arrive(bars + B_EPOCH * 8);
      const CUtensorMap* m = (cta & 8) ? &mu : &mg;
      const int l0 = (cta >> 4) * 14, a0 = (cta & 7) * 64, d1 = (cta >> 2) * 112 - 14 * 16, d2 = (cta & 3) * 4;
      uint32_t buf = 0, ph = 0, tnext;
      asm volatile("mov.u32 %0, %%clock;" : "=r"(tnext));
#pragma unroll 1
      for (int c = 0; c < 21; c++) {
        const uint32_t dst = sb + moe_buf(buf), fb = bars + (B_MF + buf) * 8;
        mbar_wait(bars + (B_ME + buf) * 8, ph, budget);
        mbar_expect_tx(fb, 8192);
        if (c < 14) tma_load(dst, m, fb, a0 + ((l0 + c) >> 4) * 512, ((l0 + c) & 15) * 64); else tma_load3(dst, &md, fb, d1 + c * 16, d2);
        if (MLEAD && c >= 2 && c + MLEAD < 17) {
          const int f = c + MLEAD;
          if (f < 14) tma_prefetch(m, a0 + ((l0 + f) >> 4) * 512, ((l0 + f) & 15) * 64); else tma_prefetch3(&md, d1 + f * 16, d2);
        }
        if (MPACE) { uint32_t now; do { asm volatile("mov.u32 %0, %%clock;" : "=r"(now)); if ((int32_t)(now - tnext) >= 0) break; __nanosleep(20); } while (true); tnext = now + MPACE; }
        if (c == 16) {
#pragma unroll 1
          for (int f = 17; f < 21; f++) { __nanosleep(MGAP); tma_prefetch3(&md, d1 + f * 16, d2); }
        }
        if (c < 2) __nanosleep(MGAP);
        if (c == 17) mbar_arrive(bars + B_M2 * 8);
        if (++buf >= (c >= 14 ? 2 : 3)) { buf = 0; ph ^= 1; }
      }
      mbar_wait(bars + (B_PUB + 1) * 8, 0, budget);
      if (PUB_TMA) tma_store(&mo, sb + 4 * STAGE, bj * 128 + 64, bi * 128);
      mbar_wait(bars + (B_PUB + 3) * 8, 0, budget);
      if (PUB_TMA) {
        tma_store(&mo, sb + 4 * STAGE + 8192, bj * 128 + 64, bi * 128 + 64);
        asm volatile("cp.async.bulk.commit_group;" ::: "memory");
        asm volatile("cp.async.bulk.wait_group 0;" ::: "memory");
        mbar_arrive(bars + B_PS * 8);
      }
      signal_add(&g_cnt[(C_O + bi * 4 + 1) * 32], 32u);
      TS(57);
      wait_count<POLLF>(&g_cnt[(C_O + bi * 4 + 1) * 32], (old & ~255u) + 256u, budget);
      mbar_arrive(bars + B_P1 * 8);
      TS(3);
    } else {
      const int u = warp - 10, hp = bj * 2 + u;
      mbar_wait(bars + B_EPOCH * 8, 0, budget);
      const uint32_t target = lds32(sb + SM_MISC);
      mbar_wait(bars + B_INFO * 8, 0, budget);
      wait_count<200>(&g_cnt[C_START], target, budget);
      fence_async_global();
#pragma unroll 1
      for (int e = 0; e < 2; e++) {
        uint32_t* cnt = &g_cnt[(e ? C_O + bi * 4 + u * 2 : C_KV + hp) * 32];
        mbar_wait(bars + (e ? B_PUB + u * 2 : B_RH + u) * 8, 0, budget);
        if (e == 0) {
          static_assert(SM_PHI == SM_Z + 4096, "staging is contiguous");
#pragma unroll 1
          for (uint32_t c = 0; c < 10; c++) {
            if (c == 4) mbar_wait(bars + (B_RED + u) * 8, 0, budget);
            bulk_reduce(&g_kvr[hp * 2560 + c * 256], sb + SM_Z + c * 1024, 1024);
            if (c < 9) __nanosleep(u && c >= 3 ? RED_GAP1 : RED_GAP0);
          }
          asm volatile("cp.async.bulk.commit_group;" ::: "memory");
          asm volatile("cp.async.bulk.wait_group 0;" ::: "memory");
          TS(21 + u * 16);
          mbar_arrive(bars + (B_RD + u) * 8);
        }
        if (PUB_TMA && e) {
          tma_store(&mo, sb + 3 * STAGE + u * 8192, bj * 128, bi * 128 + u * 64);
          asm volatile("cp.async.bulk.commit_group;" ::: "memory");
          asm volatile("cp.async.bulk.wait_group 0;" ::: "memory");
        }
        signal_add(cnt, e ? 32u : 16u);
        TS(e ? 56 + u * 2 : 60 + u);
        if (REPF && !e) prefetch_map(&mo);
        if (e == 0) {
          mbar_wait(bars + (u ? B_M2 : B_RD + 1) * 8, 0, budget);
        }
        wait_count<POLLF>(cnt, target, budget);
        fence_async_global();
        if (e == 0) {
          mbar_expect_tx(bars + (B_KV + u) * 8, 10240);
          bulk_load(sb + SM_V + u * 8192, &g_kvr[hp * 2560], 8192, bars + (B_KV + u) * 8);
          bulk_load(sb + SM_Z + u * 2048, &g_kvr[hp * 2560 + 2048], 2048, bars + (B_KV + u) * 8);
          TS(38 + u);
        }
      }
      TS(2 + u * 2);
      if (u == 0) mbar_wait2(bars + B_T3 * 8, bars + B_XR * 8, 0, budget);
      uint32_t slot = 0, ph = 1;
#pragma unroll 1
      for (int s = 2; s < 16; s++) {
        const int p = s >= 9, q = s < 9 ? s - 2 : s - 9;
        if (PUB_TMA && s == 6) mbar_wait(bars + B_PS * 8, 0, budget);
        if (s == 9) { mbar_wait(bars + B_P1 * 8, 0, budget); fence_async_global(); }
        const uint32_t fb = bars + (B_FY + u * NST + slot) * 8;
        mbar_wait(bars + (B_EM + slot) * 8, ph, budget);
        mbar_expect_tx(fb, 8192);
        tma_load(sb + slot * STAGE + u * 8192, &mo, fb, (q + (q >= bj)) * 128 + p * 64, bi * 128 + u * 64);
        if (++slot == NST) { slot = 0; ph ^= 1; }
      }
    }
  }
}

typedef CUresult (*EncodeFn)(CUtensorMap*, CUtensorMapDataType, cuuint32_t, void*, const cuuint64_t*, const cuuint64_t*, const cuuint32_t*,
                             const cuuint32_t*, CUtensorMapInterleave, CUtensorMapSwizzle, CUtensorMapL2promotion, CUtensorMapFloatOOBfill);

void make_map(EncodeFn enc, CUtensorMap* m, const void* ptr, uint64_t cols, uint64_t rows, uint32_t bc, uint32_t br, CUtensorMapSwizzle swz) {
  const cuuint64_t dims[2] = {cols, rows}, strides[1] = {cols * 2};
  const cuuint32_t box[2] = {bc, br}, es[2] = {1, 1};
  enc(m, CU_TENSOR_MAP_DATA_TYPE_BFLOAT16, 2, const_cast<void*>(ptr), dims, strides, box, es, CU_TENSOR_MAP_INTERLEAVE_NONE, swz,
      CU_TENSOR_MAP_L2_PROMOTION_L2_128B, CU_TENSOR_MAP_FLOAT_OOB_FILL_NONE);
}

}

extern "C" void kernel_launch(void* const* d_in, const int* in_sizes, int n_in, void* d_out, int out_size) {
  (void)in_sizes; (void)n_in; (void)out_size;
  void* fn = nullptr;
  cudaDriverEntryPointQueryResult qr;
  cudaGetDriverEntryPoint("cuTensorMapEncodeTiled", &fn, cudaEnableDefault, &qr);
  EncodeFn enc = (EncodeFn)fn;
  void* o_ptr = nullptr;
  cudaGetSymbolAddress(&o_ptr, g_o);
  CUtensorMap mx, mw, mwo, mo, mout, mxr, mg, mu, md, mx64;
  make_map(enc, &mx, d_in[0], kD, kS, 64, 128, CU_TENSOR_MAP_SWIZZLE_128B);
  make_map(enc, &mx64, d_in[0], kD, kS, 64, 64, CU_TENSOR_MAP_SWIZZLE_128B);
  make_map(enc, &mxr, d_in[0], kD, kS, 256, 16, CU_TENSOR_MAP_SWIZZLE_NONE);
  make_map(enc, &mw, d_in[1], 3 * kD, kD, 64, 64, CU_TENSOR_MAP_SWIZZLE_128B);
  make_map(enc, &mwo, d_in[3], kD, kD, 64, 64, CU_TENSOR_MAP_SWIZZLE_128B);
  make_map(enc, &mo, o_ptr, kD, kS, 64, 64, CU_TENSOR_MAP_SWIZZLE_128B);
  make_map(enc, &mout, d_out, kD, kS, 64, 16, CU_TENSOR_MAP_SWIZZLE_128B);
  make_map(enc, &mg, d_in[6], kF, kD, 64, 64, CU_TENSOR_MAP_SWIZZLE_128B);
  make_map(enc, &mu, d_in[7], kF, kD, 64, 64, CU_TENSOR_MAP_SWIZZLE_128B);
  {
    const cuuint64_t dims[3] = {64, kF, 16}, strides[2] = {kD * 2, 128};
    const cuuint32_t box[3] = {64, 16, 4}, es[3] = {1, 1, 1};
    enc(&md, CU_TENSOR_MAP_DATA_TYPE_BFLOAT16, 3, d_in[8], dims, strides, box, es, CU_TENSOR_MAP_INTERLEAVE_NONE, CU_TENSOR_MAP_SWIZZLE_128B,
        CU_TENSOR_MAP_L2_PROMOTION_L2_128B, CU_TENSOR_MAP_FLOAT_OOB_FILL_NONE);
  }
  Params P;
  P.x = (const __nv_bfloat16*)d_in[0];
  P.w = (const __nv_bfloat16*)d_in[1];
  P.o = (__nv_bfloat16*)o_ptr;
  P.w_phi = (const __nv_bfloat16*)d_in[2];
  P.w_r = (const __nv_bfloat16*)d_in[5];
  P.gate_w = (const __nv_bfloat16*)d_in[9];
  P.da = make_desc(sb, 16, 1024, 1);
  P.db = make_desc(sb + 16384, 8192, 1024, 1);
  P.dw = make_desc(sb + SM_WPHI, 16, 512, 2);
  P.dphi = make_desc(sb + SM_PHI, 16, 1024, 1);
  P.dv = make_desc(sb + SM_V, SM_ONE - SM_V, 512, 2);
  P.dkv = make_desc(sb + SM_V, SM_Z - SM_V, 512, 2);
  P.dband = make_desc(sb + SM_BAND, 128, 128, 0);
  P.dxs = make_desc(sb + SM_BAND, 16, 128, 0);
  int dev = 0, sms = 0;
  cudaGetDevice(&dev);
  cudaDeviceGetAttribute(&sms, cudaDevAttrMultiProcessorCount, dev);
  auto kern = sms == 132 ? fused_kernel<true> : fused_kernel<false>;
  cudaFuncSetAttribute(kern, cudaFuncAttributeMaxDynamicSharedMemorySize, SM_ALLOC);
  kern<<<132, 512, SM_ALLOC, cudaStreamPerThread>>>(mx, mw, mwo, mo, mout, mxr, mg, mu, md, mx64, P);
}
```

```cpp
#include <cuda_runtime.h>
#include <cuda_bf16.h>
#include <cuda.h>
#include <stdint.h>

namespace {

template<int TA, int TB> __device__ __forceinline__ void wgmma_m64n128k16_ss(float (&d)[64], uint64_t da, uint64_t db, int scale_d) {
  asm volatile("{\n.reg .pred p;\nsetp.ne.b32 p, %66, 0;\n"
    "wgmma.mma_async.sync.aligned.m64n128k16.f32.bf16.bf16 "
    "{%0, %1, %2, %3, %4, %5, %6, %7, %8, %9, %10, %11, %12, %13, %14, %15, "
    "%16, %17, %18, %19, %20, %21, %22, %23, %24, %25, %26, %27, %28, %29, %30, %31, "
    "%32, %33, %34, %35, %36, %37, %38, %39, %40, %41, %42, %43, %44, %45, %46, %47, "
    "%48, %49, %50, %51, %52, %53, %54, %55, %56, %57, %58, %59, %60, %61, %62, %63}, "
    "%64, %65, p, 1, 1, %67, %68;\n}\n"
    : "+f"(d[0]), "+f"(d[1]), "+f"(d[2]), "+f"(d[3]), "+f"(d[4]), "+f"(d[5]), "+f"(d[6]), "+f"(d[7]),
      "+f"(d[8]), "+f"(d[9]), "+f"(d[10]), "+f"(d[11]), "+f"(d[12]), "+f"(d[13]), "+f"(d[14]), "+f"(d[15]),
      "+f"(d[16]), "+f"(d[17]), "+f"(d[18]), "+f"(d[19]), "+f"(d[20]), "+f"(d[21]), "+f"(d[22]), "+f"(d[23]),
      "+f"(d[24]), "+f"(d[25]), "+f"(d[26]), "+f"(d[27]), "+f"(d[28]), "+f"(d[29]), "+f"(d[30]), "+f"(d[31]),
      "+f"(d[32]), "+f"(d[33]), "+f"(d[34]), "+f"(d[35]), "+f"(d[36]), "+f"(d[37]), "+f"(d[38]), "+f"(d[39]),
      "+f"(d[40]), "+f"(d[41]), "+f"(d[42]), "+f"(d[43]), "+f"(d[44]), "+f"(d[45]), "+f"(d[46]), "+f"(d[47]),
      "+f"(d[48]), "+f"(d[49]), "+f"(d[50]), "+f"(d[51]), "+f"(d[52]), "+f"(d[53]), "+f"(d[54]), "+f"(d[55]),
      "+f"(d[56]), "+f"(d[57]), "+f"(d[58]), "+f"(d[59]), "+f"(d[60]), "+f"(d[61]), "+f"(d[62]), "+f"(d[63])
    : "l"(da), "l"(db), "r"(scale_d), "n"(TA), "n"(TB));
}

template<int TB> __device__ __forceinline__ void wgmma_m64n32k16_rs(float (&d)[16], const uint32_t (&a)[4], uint64_t db, int scale_d) {
  asm volatile("{\n.reg .pred p;\nsetp.ne.b32 p, %21, 0;\n"
    "wgmma.mma_async.sync.aligned.m64n32k16.f32.bf16.bf16 "
    "{%0, %1, %2, %3, %4, %5, %6, %7, %8, %9, %10, %11, %12, %13, %14, %15}, "
    "{%16, %17, %18, %19}, %20, p, 1, 1, %22;\n}\n"
    : "+f"(d[0]), "+f"(d[1]), "+f"(d[2]), "+f"(d[3]), "+f"(d[4]), "+f"(d[5]), "+f"(d[6]), "+f"(d[7]),
      "+f"(d[8]), "+f"(d[9]), "+f"(d[10]), "+f"(d[11]), "+f"(d[12]), "+f"(d[13]), "+f"(d[14]), "+f"(d[15])
    : "r"(a[0]), "r"(a[1]), "r"(a[2]), "r"(a[3]), "l"(db), "r"(scale_d), "n"(TB));
}

template<int TA, int TB> __device__ __forceinline__ void wgmma_m64n40k16_ss(float (&d)[20], uint64_t da, uint64_t db, int scale_d) {
  asm volatile("{\n.reg .pred p;\nsetp.ne.b32 p, %22, 0;\n"
    "wgmma.mma_async.sync.aligned.m64n40k16.f32.bf16.bf16 "
    "{%0, %1, %2, %3, %4, %5, %6, %7, %8, %9, %10, %11, %12, %13, %14, %15, "
    "%16, %17, %18, %19}, "
    "%20, %21, p, 1, 1, %23, %24;\n}\n"
    : "+f"(d[0]), "+f"(d[1]), "+f"(d[2]), "+f"(d[3]), "+f"(d[4]), "+f"(d[5]), "+f"(d[6]), "+f"(d[7]),
      "+f"(d[8]), "+f"(d[9]), "+f"(d[10]), "+f"(d[11]), "+f"(d[12]), "+f"(d[13]), "+f"(d[14]), "+f"(d[15]),
      "+f"(d[16]), "+f"(d[17]), "+f"(d[18]), "+f"(d[19])
    : "l"(da), "l"(db), "r"(scale_d), "n"(TA), "n"(TB));
}

template<int TB> __device__ __forceinline__ void wgmma_m64n40k16_rs(float (&d)[20], const uint32_t (&a)[4], uint64_t db, int scale_d) {
  asm volatile("{\n.reg .pred p;\nsetp.ne.b32 p, %25, 0;\n"
    "wgmma.mma_async.sync.aligned.m64n40k16.f32.bf16.bf16 "
    "{%0, %1, %2, %3, %4, %5, %6, %7, %8, %9, %10, %11, %12, %13, %14, %15, "
    "%16, %17, %18, %19}, "
    "{%20, %21, %22, %23}, %24, p, 1, 1, %26;\n}\n"
    : "+f"(d[0]), "+f"(d[1]), "+f"(d[2]), "+f"(d[3]), "+f"(d[4]), "+f"(d[5]), "+f"(d[6]), "+f"(d[7]),
      "+f"(d[8]), "+f"(d[9]), "+f"(d[10]), "+f"(d[11]), "+f"(d[12]), "+f"(d[13]), "+f"(d[14]), "+f"(d[15]),
      "+f"(d[16]), "+f"(d[17]), "+f"(d[18]), "+f"(d[19])
    : "r"(a[0]), "r"(a[1]), "r"(a[2]), "r"(a[3]), "l"(db), "r"(scale_d), "n"(TB));
}

template<int TA, int TB> __device__ __forceinline__ void wgmma_m64n8k16_ss(float (&d)[4], uint64_t da, uint64_t db, int scale_d) {
  asm volatile("{\n.reg .pred p;\nsetp.ne.b32 p, %6, 0;\n"
    "wgmma.mma_async.sync.aligned.m64n8k16.f32.bf16.bf16 "
    "{%0, %1, %2, %3}, "
    "%4, %5, p, 1, 1, %7, %8;\n}\n"
    : "+f"(d[0]), "+f"(d[1]), "+f"(d[2]), "+f"(d[3])
    : "l"(da), "l"(db), "r"(scale_d), "n"(TA), "n"(TB));
}

constexpr int kS = 2048, kD = 1024, kF = 3584;
constexpr int NST = 5, STAGE = 32768;
constexpr uint32_t sb = 1024;
constexpr int SM_V    = NST * STAGE;
constexpr int SM_Z    = SM_V + 16384;
constexpr int SM_PHI  = SM_Z + 4096;
constexpr int SM_MOE  = SM_PHI + 16384;
constexpr int SM_WPHI = SM_MOE + 16384;
constexpr int SM_ONE  = SM_WPHI + 8192;
constexpr int SM_BAND = SM_ONE + 1024;
constexpr int SM_G    = SM_BAND + 2176;
constexpr int SM_BAR  = SM_G + 512;
constexpr int SM_MISC = SM_BAR + 512;
constexpr int SM_TOTAL = SM_MISC + 64;
static_assert(SM_TOTAL <= 232448, "smem");
constexpr uint32_t bars = sb + SM_BAR;
constexpr int B_FX = 0  , B_FY = 5  , B_EPOCH = 16, B_RX = 17  , B_MF = 21  , B_RD = 24  , B_KV = 26  , B_M2 = 28, B_P1 = 29, B_PS = 15, B_XT = 30  , B_AF = 32;
constexpr int B_WPHI = 33, B_INFO = 34, B_QS = 35, B_XP = 36, B_RED = 37  , B_PUB = 39  , B_ME = 43  , B_MD = 46, B_T3 = 47, B_RH = 48  , B_XR = 50;
constexpr int B_EM = 51  , B_DUMMY = 56, B_NUM = 57;
constexpr int C_START = 0, C_O = 1, C_KV = C_O + 64;

__device__ uint2 g_gate[kS];
__device__ uint2 g_key[128];
__device__ uint2 g_pre[4 * kF];
__device__ uint2 g_yp[32 * kD];
__device__ __align__(128) uint32_t g_kvr[16 * 2560];
__device__ __align__(128) uint32_t g_cnt[(C_KV + 32) * 32];
__device__ __align__(1024) __nv_bfloat16 g_o[kS * kD];
#define KS(id)
#define RG(id)
#define TS(id)
#define TSG(id)
constexpr int SM_ALLOC = SM_TOTAL;

#define POLL0 500
#define POLL1 150
#define RSTEP 1
#define POLLR 400
#define EARLY_N 2
#define EARLY_GAP 200
#define POLLF 50
#define RED_GAP0 250
#define RED_GAP1 0
#define YIELD_EXP 1
#define XS0 1
#define XS1 3
#define REPF 1
#define WOPF 1
#define MGAP 300

struct Params {
  const __nv_bfloat16 *x, *w, *w_phi, *w_r, *gate_w;
  uint64_t da, db, dw, dphi, dv, dkv, dband, dxs;
};

__device__ __forceinline__ uint32_t smem_u32(const void* p) { return (uint32_t)__cvta_generic_to_shared(p); }
__device__ __forceinline__ void mbar_init(uint32_t bar, uint32_t cnt) { asm volatile("mbarrier.init.shared::cta.b64 [%0], %1;" :: "r"(bar), "r"(cnt) : "memory"); }
__device__ __forceinline__ void mbar_expect_tx(uint32_t bar, uint32_t bytes) { asm volatile("mbarrier.arrive.expect_tx.shared::cta.b64 _, [%0], %1;" :: "r"(bar), "r"(bytes) : "memory"); }
__device__ __forceinline__ void mbar_arrive(uint32_t bar) { asm volatile("mbarrier.arrive.shared::cta.b64 _, [%0];" :: "r"(bar) : "memory"); }
__device__ __forceinline__ void mbar_arrive_n(uint32_t bar, uint32_t n) { asm volatile("mbarrier.arrive.shared::cta.b64 _, [%0], %1;" :: "r"(bar), "r"(n) : "memory"); }
constexpr int BUDGET = 1 << 20;
__device__ __forceinline__ void mbar_wait(uint32_t bar, uint32_t parity, int& budget) {
  asm volatile("{\n.reg .pred p;\n"
               "WAIT_L:\nmbarrier.try_wait.parity.shared::cta.b64 p, [%1], %2;\n@p bra WAIT_D;\n"
               "add.s32 %0, %0, -1;\nsetp.gt.s32 p, %0, 0;\n@p bra WAIT_L;\nWAIT_D:\n}"
               : "+r"(budget) : "r"(bar), "r"(parity) : "memory");
}
__device__ __forceinline__ void mbar_wait2(uint32_t bar0, uint32_t bar1, uint32_t parity, int& budget) {
  asm volatile("{\n.reg .pred p, q;\n"
               "WAIT_L:\nmbarrier.try_wait.parity.shared::cta.b64 p, [%1], %3;\nmbarrier.try_wait.parity.shared::cta.b64 q, [%2], %3;\n"
               "and.pred p, p, q;\n@p bra WAIT_D;\n"
               "add.s32 %0, %0, -1;\nsetp.gt.s32 p, %0, 0;\n@p bra WAIT_L;\nWAIT_D:\n}"
               : "+r"(budget) : "r"(bar0), "r"(bar1), "r"(parity) : "memory");
}
template <int SLEEP>
__device__ __forceinline__ void wait_count(const uint32_t* p, uint32_t target, int& budget) {
  asm volatile("{\n.reg .pred p;\n.reg .s32 v;\n"
               "WAIT_L:\nld.acquire.gpu.global.s32 v, [%1];\nsub.s32 v, v, %2;\nsetp.ge.s32 p, v, 0;\n@p bra WAIT_D;\n"
               "nanosleep.u32 %3;\nadd.s32 %0, %0, -4;\nsetp.gt.s32 p, %0, 0;\n@p bra WAIT_L;\nWAIT_D:\n}"
               : "+r"(budget) : "l"(p), "r"(target), "n"(SLEEP) : "memory");
}
__device__ __forceinline__ void tma_load(uint32_t dst, const CUtensorMap* m, uint32_t bar, int c0, int c1) {
  asm volatile("cp.async.bulk.tensor.2d.shared::cluster.global.mbarrier::complete_tx::bytes [%0], [%1, {%3, %4}], [%2];"
    :: "r"(dst), "l"(m), "r"(bar), "r"(c0), "r"(c1) : "memory");
}
__device__ __forceinline__ void tma_load3(uint32_t dst, const CUtensorMap* m, uint32_t bar, int c1, int c2) {
  asm volatile("cp.async.bulk.tensor.3d.shared::cluster.global.mbarrier::complete_tx::bytes [%0], [%1, {%5, %3, %4}], [%2];"
    :: "r"(dst), "l"(m), "r"(bar), "r"(c1), "r"(c2), "r"(0) : "memory");
}
__device__ __forceinline__ void tma_prefetch3(const CUtensorMap* m, int c1, int c2) {
  asm volatile("cp.async.bulk.prefetch.tensor.3d.L2.global [%0, {%3, %1, %2}];" :: "l"(m), "r"(c1), "r"(c2), "r"(0) : "memory");
}
__device__ __forceinline__ void tma_prefetch(const CUtensorMap* m, int c0, int c1) {
  asm volatile("cp.async.bulk.prefetch.tensor.2d.L2.global [%0, {%1, %2}];" :: "l"(m), "r"(c0), "r"(c1) : "memory");
}
__device__ __forceinline__ void tma_store(const CUtensorMap* m, uint32_t src, int c0, int c1) {
  asm volatile("cp.async.bulk.tensor.2d.global.shared::cta.bulk_group [%0, {%2, %3}], [%1];" :: "l"(m), "r"(src), "r"(c0), "r"(c1) : "memory");
}
__device__ __forceinline__ void bulk_load(uint32_t dst, const void* src, uint32_t bytes, uint32_t bar) {
  asm volatile("cp.async.bulk.shared::cluster.global.mbarrier::complete_tx::bytes [%0], [%1], %2, [%3];" :: "r"(dst), "l"(src), "r"(bytes), "r"(bar) : "memory");
}
__device__ __forceinline__ void bulk_reduce(void* dst, uint32_t src, uint32_t bytes) {
  asm volatile("cp.reduce.async.bulk.global.shared::cta.bulk_group.add.noftz.bf16 [%0], [%1], %2;" :: "l"(dst), "r"(src), "r"(bytes) : "memory");
}
__device__ __forceinline__ void prefetch_map(const CUtensorMap* m) { asm volatile("prefetch.tensormap [%0];" :: "l"(m) : "memory"); }
__device__ __forceinline__ bool elect_one() {
  uint32_t p;
  asm volatile("{\n.reg .pred P;\nelect.sync _|P, 0xffffffff;\nselp.u32 %0, 1, 0, P;\n}" : "=r"(p));
  return p;
}
__device__ __forceinline__ void wg_fence() { asm volatile("wgmma.fence.sync.aligned;" ::: "memory"); }
__device__ __forceinline__ void wg_commit() { asm volatile("wgmma.commit_group.sync.aligned;" ::: "memory"); }
template <int N> __device__ __forceinline__ void wg_wait() { asm volatile("wgmma.wait_group.sync.aligned %0;" :: "n"(N) : "memory"); }
template <int N> __device__ __forceinline__ void zero(float (&r)[N]) {
#pragma unroll
  for (int i = 0; i < N; i++) r[i] = 0.f;
}
template <int N> __device__ __forceinline__ void pin(float (&r)[N]) {
#pragma unroll
  for (int i = 0; i < N; i++) asm volatile("" : "+f"(r[i]) :: "memory");
}
template <int N> __device__ __forceinline__ void pinr(uint32_t (&r)[N][4]) {
#pragma unroll
  for (int i = 0; i < N; i++) asm volatile("" : "+r"(r[i][0]), "+r"(r[i][1]), "+r"(r[i][2]), "+r"(r[i][3]) :: "memory");
}
__device__ __forceinline__ void fence_async_smem() { asm volatile("fence.proxy.async.shared::cta;" ::: "memory"); }
__device__ __forceinline__ void fence_async_global() { asm volatile("fence.proxy.async.global;" ::: "memory"); }
__device__ __forceinline__ void bar_sync(int id, int n) { asm volatile("bar.sync %0, %1;" :: "r"(id), "r"(n) : "memory"); }
__device__ __forceinline__ void bar_arrive(int id, int n) { asm volatile("bar.arrive %0, %1;" :: "r"(id), "r"(n) : "memory"); }
__device__ __forceinline__ void arrive_one(uint32_t bar) {
  asm volatile("{\n.reg .pred p;\nelect.sync _|p, 0xffffffff;\n@p mbarrier.arrive.shared::cta.b64 _, [%0];\n}" :: "r"(bar) : "memory");
}
__device__ __forceinline__ void warp_arrive(uint32_t bar, int lane) { __syncwarp(); if (lane == 0) mbar_arrive(bar); }
__host__ __device__ constexpr uint64_t make_desc(uint32_t addr, uint32_t lbo, uint32_t sbo, uint32_t swz) {
  return (uint64_t)((addr & 0x3FFFF) >> 4) | ((uint64_t)((lbo & 0x3FFFF) >> 4) << 16) | ((uint64_t)(sbo >> 4) << 32) | ((uint64_t)swz << 62);
}
__device__ __forceinline__ uint32_t pack2(float lo, float hi) {
  uint32_t r; asm("cvt.rn.bf16x2.f32 %0, %1, %2;" : "=r"(r) : "f"(hi), "f"(lo)); return r;
}
__device__ __forceinline__ float bf_lo(uint32_t v) { return __uint_as_float(v << 16); }
__device__ __forceinline__ float bf_hi(uint32_t v) { return __uint_as_float(v & 0xffff0000u); }
__device__ __forceinline__ float ex2(float x) { float r; asm("ex2.approx.ftz.f32 %0, %1;" : "=f"(r) : "f"(x)); return r; }
__device__ __forceinline__ float rcp(float x) { float r; asm("rcp.approx.ftz.f32 %0, %1;" : "=f"(r) : "f"(x)); return r; }
constexpr float LOG2E = 1.4426950408889634f;
__device__ __forceinline__ float sigmoidf(float x) { return rcp(1.0f + ex2(-LOG2E * x)); }
__device__ __forceinline__ void sts128(uint32_t a, uint32_t x, uint32_t y, uint32_t z, uint32_t w) {
  asm volatile("st.shared.v4.u32 [%0], {%1,%2,%3,%4};" :: "r"(a), "r"(x), "r"(y), "r"(z), "r"(w) : "memory");
}
__device__ __forceinline__ void lds128(uint32_t a, uint32_t (&r)[4]) {
  asm volatile("ld.shared.v4.u32 {%0,%1,%2,%3}, [%4];" : "=r"(r[0]), "=r"(r[1]), "=r"(r[2]), "=r"(r[3]) : "r"(a) : "memory");
}
__device__ __forceinline__ void sts32(uint32_t a, uint32_t v) { asm volatile("st.shared.u32 [%0], %1;" :: "r"(a), "r"(v) : "memory"); }
__device__ __forceinline__ uint32_t lds32(uint32_t a) { uint32_t v; asm volatile("ld.shared.u32 %0, [%1];" : "=r"(v) : "r"(a) : "memory"); return v; }
__device__ __forceinline__ float ldsf(uint32_t a) { return __uint_as_float(lds32(a)); }
__device__ __forceinline__ void stmatrix4(uint32_t a, uint32_t r0, uint32_t r1, uint32_t r2, uint32_t r3) {
  asm volatile("stmatrix.sync.aligned.m8n8.x4.shared.b16 [%0], {%1,%2,%3,%4};" :: "r"(a), "r"(r0), "r"(r1), "r"(r2), "r"(r3) : "memory");
}
__device__ __forceinline__ void ldmatrix4(uint32_t a, uint32_t (&r)[4]) {
  asm volatile("ldmatrix.sync.aligned.m8n8.x4.shared.b16 {%0,%1,%2,%3}, [%4];" : "=r"(r[0]), "=r"(r[1]), "=r"(r[2]), "=r"(r[3]) : "r"(a) : "memory");
}
__device__ __forceinline__ uint4 ldg_nc(const void* p) {
  uint4 v; asm volatile("ld.global.nc.L1::no_allocate.v4.u32 {%0,%1,%2,%3}, [%4];" : "=r"(v.x), "=r"(v.y), "=r"(v.z), "=r"(v.w) : "l"(p)); return v;
}
__device__ __forceinline__ void st_tagged(uint2* p, uint32_t v, uint32_t tag) {
  asm volatile("{\n.reg .b64 x;\nmov.b64 x, {%1, %2};\nst.relaxed.gpu.global.b64 [%0], x;\n}" :: "l"(p), "r"(v), "r"(tag) : "memory");
}
__device__ __forceinline__ uint2 ld_tagged(const uint2* p) {
  uint2 v; asm volatile("{\n.reg .b64 x;\nld.relaxed.gpu.global.b64 x, [%2];\nmov.b64 {%0, %1}, x;\n}" : "=r"(v.x), "=r"(v.y) : "l"(p) : "memory"); return v;
}
__device__ __forceinline__ void probe(const uint2* p, uint32_t tag, int& budget) {
  do { __nanosleep(POLL0); budget -= 16; } while (!__all_sync(0xffffffffu, ld_tagged(p).y == tag) && budget > 0);
}
template <int STRIDE, int N>
__device__ __forceinline__ void gather(const uint2* p, uint32_t tag, float& s0, float& s1, int& budget) {
  uint32_t pause = 0;
  bool again;
#pragma unroll 1
  do {
    __nanosleep(pause);
    pause = POLL0;
    uint32_t bad = 0;
    s0 = s1 = 0.f;
#pragma unroll
    for (int i = 0; i < N; i++) {
      const uint2 w = ld_tagged(p + i * STRIDE);
      bad |= w.y ^ tag;
      if (i < N / 2) s0 += __uint_as_float(w.x); else s1 += __uint_as_float(w.x);
    }
    budget -= 16;
    again = __any_sync(0xffffffffu, bad != 0) && budget > 0;
  } while (again);
}
__device__ __forceinline__ void sts16(uint32_t a, uint32_t v) { asm volatile("st.shared.u16 [%0], %1;" :: "r"(a), "h"((uint16_t)v) : "memory"); }
__device__ __forceinline__ void signal_add(uint32_t* p, uint32_t v) { asm volatile("red.release.gpu.global.add.u32 [%0], %1;" :: "l"(p), "r"(v) : "memory"); }
__device__ __forceinline__ float qmax(float v) { v = fmaxf(v, __shfl_xor_sync(0xffffffffu, v, 1)); return fmaxf(v, __shfl_xor_sync(0xffffffffu, v, 2)); }
__device__ __forceinline__ float qsum(float v) { v += __shfl_xor_sync(0xffffffffu, v, 1); return v + __shfl_xor_sync(0xffffffffu, v, 2); }
__device__ __forceinline__ float fold(float a, float b, bool hi, int m) { return (hi ? b : a) + __shfl_xor_sync(0xffffffffu, hi ? a : b, m); }

__device__ __forceinline__ void yield_slot() { asm volatile("pmevent 0;" ::: "memory"); }
__device__ __forceinline__ float fma_v(float a, float b, float c) { float r; asm volatile("fma.rn.f32 %0, %1, %2, %3;" : "=f"(r) : "f"(a), "f"(b), "f"(c)); return r; }
constexpr uint32_t EXP_TOP = 0x58805880u;
__device__ __forceinline__ void exp_plain(const float (&p)[16], float (&ep)[16], float (&em)[16]) {
#pragma unroll
  for (int i = 0; i < 16; i++) { ep[i] = ex2(p[i]); em[i] = ex2(-p[i]); }
}
__device__ __forceinline__ void exp_shifted(const float (&p)[16], float sgn, float (&e)[16]) {
#pragma unroll
  for (int i = 0; i < 16; i++) e[i] = sgn * p[i];
#pragma unroll
  for (int o = 0; o < 4; o += 2) {
    const float mx = qmax(fmaxf(fmaxf(fmaxf(e[o], e[o + 1]), fmaxf(e[o + 4], e[o + 5])), fmaxf(fmaxf(e[o + 8], e[o + 9]), fmaxf(e[o + 12], e[o + 13]))));
#pragma unroll
    for (int c = 0; c < 4; c++) { e[4 * c + o] = ex2(e[4 * c + o] - mx); e[4 * c + o + 1] = ex2(e[4 * c + o + 1] - mx); }
  }
}
__device__ __forceinline__ void pack_sums(const float (&e)[16], uint32_t (&pk)[2][4], float (&s)[2]) {
#pragma unroll
  for (int i = 0; i < 8; i++) pk[i >> 2][i & 3] = pack2(e[2 * i], e[2 * i + 1]);
#pragma unroll
  for (int o = 0; o < 4; o += 2) s[o >> 1] = ((e[o] + e[o + 1]) + (e[o + 4] + e[o + 5])) + ((e[o + 8] + e[o + 9]) + (e[o + 12] + e[o + 13]));
}
__device__ __forceinline__ uint32_t rcp2(float s) { const float r = rcp(s); return pack2(r, r); }
__device__ __forceinline__ uint32_t add2(uint32_t a, uint32_t b) { uint32_t r; asm("add.rn.bf16x2 %0, %1, %2;" : "=r"(r) : "r"(a), "r"(b)); return r; }
__device__ __forceinline__ uint32_t mul2(uint32_t a, uint32_t b) { uint32_t r; asm("mul.rn.bf16x2 %0, %1, %2;" : "=r"(r) : "r"(a), "r"(b)); return r; }
__device__ __forceinline__ void store_phi(uint32_t a, const uint32_t (&pk)[2][4], uint32_t r0, uint32_t r1) {
#pragma unroll
  for (int h = 0; h < 2; h++) stmatrix4(a ^ (h * 32), mul2(pk[h][0], r0), mul2(pk[h][1], r1), mul2(pk[h][2], r0), mul2(pk[h][3], r1));
}
__device__ __forceinline__ uint32_t exp_frags(const float (&p)[16], uint32_t (&ef)[4][4], uint32_t top) {
  float ep[16], em[16];
  exp_plain(p, ep, em);
#pragma unroll
  for (int s = 0; s < 2; s++)
#pragma unroll
    for (int r = 0; r < 4; r++) {
      ef[s][r] = pack2(ep[8 * s + 2 * r], ep[8 * s + 2 * r + 1]);
      ef[2 + s][r] = pack2(em[8 * s + 2 * r], em[8 * s + 2 * r + 1]);
    }
#pragma unroll
  for (int s = 0; s < 4; s++) top = __vimax3_u16x2(__vimax3_u16x2(top, ef[s][0], ef[s][1]), ef[s][2], ef[s][3]);
  return top;
}
__device__ __forceinline__ void pair_frags(float (&p0)[16], const float (&p1)[16], uint32_t (&ef)[2][4][4]) {
  const uint32_t top = exp_frags(p1, ef[1], exp_frags(p0, ef[0], EXP_TOP));
  if (__builtin_expect(__any_sync(0xffffffffu, top != EXP_TOP), 0)) {
#pragma unroll 1
    for (int u = 0; u < 4; u++) {
      float e[16];
      exp_shifted(p0, (u & 1) ? -1.f : 1.f, e);
#pragma unroll
      for (int r = 0; r < 4; r++) {
#pragma unroll
        for (int s = 0; s < 6; s++) ef[s >> 2][s & 3][r] = ef[(s + 2) >> 2][(s + 2) & 3][r];
        ef[1][2][r] = pack2(e[2 * r], e[2 * r + 1]);
        ef[1][3][r] = pack2(e[8 + 2 * r], e[8 + 2 * r + 1]);
      }
      if (u & 1) {
#pragma unroll
        for (int c = 0; c < 16; c++) p0[c] = p1[c];
      }
    }
  }
}
__device__ __forceinline__ void issue_pq(float (&p)[4][16], const uint32_t (&qf)[4][2][4], uint64_t dw, int accumulate) {
  wg_fence();
#pragma unroll
  for (int h = 0; h < 4; h++) {
    wgmma_m64n32k16_rs<1>(p[h], qf[h][0], dw + h * 128, accumulate);
    wgmma_m64n32k16_rs<1>(p[h], qf[h][1], dw + h * 128 + 64, 1);
  }
  wg_commit();
}

#define SPLIT_BATCH 2
__device__ __forceinline__ void mainloop128(float (&acc)[2][64], uint64_t da0, uint64_t db0, uint32_t slot, uint32_t ph, int steps, bool lane0, int& budget, int cta, int n0) {
  uint32_t prev = 0;
#pragma unroll 1
  for (int k = 0; k < steps; k++) {
    mbar_wait(bars + B_FX * 8 + slot * 8, ph, budget);
    const uint64_t da = da0 + slot * (STAGE >> 4), db = db0 + slot * (STAGE >> 4);
#pragma unroll
    for (int kk = 0; kk < 4; kk++) {
      if (SPLIT_BATCH == 2 || !(kk & 1)) {
        wg_wait<1>();
        if (kk == 3 - SPLIT_BATCH && k > 0 && lane0) mbar_arrive_n(bars + B_EM * 8 + prev * 8, 2);
        wg_fence();
      }
      wgmma_m64n128k16_ss<0, 1>(acc[0], da + kk * 2, db + kk * 128, kk ? 1 : k);
      wgmma_m64n128k16_ss<0, 1>(acc[1], da + 512 + kk * 2, db + kk * 128, kk ? 1 : k);
      if (SPLIT_BATCH == 2 || (kk & 1)) wg_commit();
    }
    prev = slot;
    if (++slot == NST) { slot = 0; ph ^= 1; }
  }
}
__device__ __forceinline__ void kstep64(float (&acc)[64], uint64_t da, uint64_t db, int accumulate) {
  wg_fence();
#pragma unroll
  for (int kk = 0; kk < 4; kk++) wgmma_m64n128k16_ss<0, 1>(acc, da + kk * 2, db + kk * 128, kk ? 1 : accumulate);
  wg_commit();
}
__device__ __forceinline__ void issue_kv(float (&kv)[20], uint64_t dphi, uint64_t dv, int accumulate) {
  wg_fence();
#pragma unroll
  for (int ks = 0; ks < 4; ks++)
    wgmma_m64n40k16_ss<1, 1>(kv, dphi + ks * 128, dv - (uint64_t)ks * ((64ull << 16) - 64ull), ks ? 1 : accumulate);
  wg_commit();
}
template <int HALF>
__device__ __forceinline__ void load_x(uint32_t sx, uint32_t (&xf)[8][4]) {
#pragma unroll
  for (int u = 0; u < 8; u++) ldmatrix4((sx ^ ((u & 3) * 32)) + (u >> 2) * HALF, xf[u]);
}
__device__ __forceinline__ uint32_t moe_buf(uint32_t b) { return b == 2 ? SM_V + 8192 : SM_MOE + b * 8192; }
template <bool DOWN>
__device__ __forceinline__ void moe_chunks(float (&a)[4], int n, uint32_t& buf, uint32_t& ph, uint64_t da0, uint64_t db, bool lane0) {
  int budget = BUDGET;
  zero(a);
#pragma unroll 1
  for (int c = 0; c < n; c++) {
    mbar_wait(bars + B_MF * 8 + buf * 8, ph, budget);
    const uint64_t da = da0 + (moe_buf(buf) >> 4);
    wg_fence();
#pragma unroll
    for (int j = 0; j < 4; j++) wgmma_m64n8k16_ss<1, 0>(a, da + j * 128, DOWN ? db - j : db + j * 2, 1);
    wg_commit();
    wg_wait<0>();
    if (lane0) mbar_arrive(bars + B_ME * 8 + buf * 8);
    db += DOWN ? 16 : 8;
    if (++buf >= (DOWN ? 2 : 3)) { buf = 0; ph ^= 1; }
  }
  pin(a);
}
constexpr uint64_t DV_TILE = 4 * ((64ull << 16) - 64ull);

template <bool BY_SM>
__global__ void __launch_bounds__(512, 1)
fused_kernel(const Params P, const __grid_constant__ CUtensorMap mx, const __grid_constant__ CUtensorMap mw, const __grid_constant__ CUtensorMap mwo,
             const __grid_constant__ CUtensorMap mo, const __grid_constant__ CUtensorMap mout, const __grid_constant__ CUtensorMap mxr,
             const __grid_constant__ CUtensorMap mg, const __grid_constant__ CUtensorMap mu, const __grid_constant__ CUtensorMap md,
             const __grid_constant__ CUtensorMap mx64) {
  extern __shared__ __align__(1024) uint8_t smem_raw[];
  if (smem_u32(smem_raw) != sb) return;
  const int tid = threadIdx.x, lane = tid & 31;
  if (tid == 256) TS(1);
  const int warp = __shfl_sync(0xffffffffu, tid >> 5, 0), wg = warp >> 2;
  int budget = BUDGET;
  if (warp == 10 && elect_one()) { prefetch_map(&mx); prefetch_map(&mw); }
  int cta;
  {
    uint32_t smid;
    asm volatile("mov.u32 %0, %%smid;" : "=r"(smid));
    if (!BY_SM) cta = blockIdx.x;
    else if (smid < 64) cta = ((smid >> 1) & 7) * 16 + (smid >> 4) * 2 + (smid & 1);
    else if (smid < 120) { const int t = (smid - 64) >> 1, d = (t * 37) >> 8; cta = (1 + t - d * 7) * 16 + 8 + d * 2 + (smid & 1); }
    else cta = smid < 124 ? smid + 8 : smid - 116;
  }
  if (cta >= 128) {
    if (tid == 0) {
      const uint32_t old = atomicAdd(&g_cnt[C_START], 32u);
      wait_count<500>(&g_cnt[C_START], (old & ~255u) + 256u, budget);
    }
    return;
  }
  const int bi = (cta >> 5) * 4 + ((cta >> 2) & 3);
  const int bj = ((cta >> 4) & 1) * 4 + (cta & 3);

  if (wg < 2 && (warp & 3) < EARLY_N && lane < (wg ? 8 : 16)) {
    const int n = warp & 3;
    const __nv_bfloat16* p = wg ? P.w + (size_t)(n * 64 + bi + (lane >> 1) * 16) * (3 * kD) + 1024 + (lane & 1) * 1024 + bj * 128
                                : P.x + (size_t)(bi * 128 + bj * 16 + lane) * kD + n * 64;
    if (n) __nanosleep(n * EARLY_GAP);
    asm volatile("prefetch.global.L2 [%0];" :: "l"(p));
  }
  __syncwarp();

  if (wg == 3) {
    asm volatile("setmaxnreg.dec.sync.aligned.u32 64;");
    const int t3 = tid - 384, w3 = warp - 12;
    if (t3 == 0) TSG(0);
    if (t3 < 80) *reinterpret_cast<uint4*>(&g_kvr[cta * 320 + t3 * 4]) = make_uint4(0, 0, 0, 0);
    if (t3 < 17) st_tagged(t3 < 16 ? &g_gate[bi * 128 + bj * 16 + t3] : &g_key[cta], 0, 1);
    bar_sync(0, 512);
#pragma unroll 1
    for (int u = 0; u < 4; u++) {
      const uint4 v = ldg_nc(P.w_phi + bj * 4096 + (u * 128 + t3) * 8);
      sts128(sb + SM_WPHI + u * 2048 + (t3 >> 2) * 64 + (((t3 & 3) ^ ((t3 >> 3) & 3)) << 4),
             pack2(LOG2E * bf_lo(v.x), LOG2E * bf_hi(v.x)), pack2(LOG2E * bf_lo(v.y), LOG2E * bf_hi(v.y)),
             pack2(LOG2E * bf_lo(v.z), LOG2E * bf_hi(v.z)), pack2(LOG2E * bf_lo(v.w), LOG2E * bf_hi(v.w)));
    }
    fence_async_smem();
    warp_arrive(bars + B_WPHI * 8, lane);
    bar_sync(6, 256);
    const uint32_t target = lds32(sb + SM_MISC);
    uint32_t key;
    {
      uint32_t kk[4];
      lds128(sb + SM_MISC + 16, kk);
      if (t3 == 0) st_tagged(&g_key[cta], max(max(kk[0], kk[1]), max(kk[2], kk[3])), target);
      uint2 k, gv;
      __nanosleep(POLLR);
      do {
        __nanosleep(POLL1);
        k = ld_tagged(&g_key[t3]);
        gv = ld_tagged(&g_gate[bi * 128 + t3]);
        budget -= 4;
      } while (!__all_sync(0xffffffffu, k.y == target && gv.y == target) && budget > 0);
      key = __reduce_max_sync(0xffffffffu, k.x);
      if (lane == 0) sts32(sb + SM_MISC + 32 + w3 * 4, key);
      sts32(sb + SM_G + t3 * 4, gv.x);
      bar_sync(5, 128);
      lds128(sb + SM_MISC + 32, kk);
      key = max(max(kk[0], kk[1]), max(kk[2], kk[3]));
    }
    const int idx = (0xFFFF - (key & 0xFFFF)) & (kS - 1);
    if (t3 == 0) { sts32(sb + SM_MISC + 4, idx); TS(8); }
    warp_arrive(bars + B_INFO * 8, lane);
    {
      const uint4 v = ldg_nc(P.x + (size_t)idx * kD + t3 * 8);
      sts128(sb + SM_BAND + t3 * 16, v.x, v.y, v.z, v.w);
    }
    const int t2 = (lane & 3) * 2, row = w3 * 16 + (lane >> 2);
    float a[4];
    uint32_t buf = 0, ph = 0;
    fence_async_smem();
    bar_sync(5, 128);
    {
      const int r = cta >> 4;
#pragma unroll 1
      for (int part = 0; part < 2; part++) {
        const int n = part ? 14 - 2 * r : 2 * r;
        moe_chunks<false>(a, n, buf, ph, P.da, P.dxs + (part ? 0 : (16 - n) * 8), lane == 0);
        uint2* dst = &g_pre[(((cta >> 2) & 2) + 1 - part) * kF + ((r - 1 + part) * 8 + (cta & 7)) * 64 + row];
        if (t2 == 0 && n) { st_tagged(dst, __float_as_uint(a[0]), target); st_tagged(dst + 8, __float_as_uint(a[2]), target); }
      }
    }
    if (t3 == 0) TS(9);
    bar_sync(5, 128);
    sts128(sb + SM_BAND + t3 * 16, 0, 0, 0, 0);
    {
      __nanosleep(POLL0);
      float gs, us;
      gather<kF, 4>(&g_pre[(cta >> 2) * 112 + min(t3, 111)], target, gs, us, budget);
      bar_sync(5, 128);
      if (t3 < 112) sts16(sb + SM_BAND + 112 + (t3 >> 3) * 128 + (t3 & 7) * 2, pack2(gs * sigmoidf(gs) * us, 0.f));
    }
    fence_async_smem();
    bar_sync(5, 128);
    if (t3 == 0) TS(12);
    moe_chunks<true>(a, 7, buf, ph, P.da, P.dband + 7, lane == 0);
    if (t3 == 0) TS(10);
    if (t2 < 4) {
      uint2* dst = &g_yp[(cta >> 2) * kD + (cta & 3) * 256 + t2 * 64 + row];
      st_tagged(dst, __float_as_uint(a[0]), target); st_tagged(dst + 8, __float_as_uint(a[2]), target);
      st_tagged(dst + 64, __float_as_uint(a[1]), target); st_tagged(dst + 72, __float_as_uint(a[3]), target);
    }
    if (lane == 0) mbar_arrive(bars + B_MD * 8);
    if ((idx >> 7) == bi) {
      mbar_wait(bars + (B_PUB + 3) * 8, 0, budget);
      if (w3 == 0) probe(&g_yp[lane * kD + bj * 128], target, budget);
      bar_sync(5, 128);
      float y = 0.f;
#pragma unroll 1
      for (int hf = 0; hf < 2; hf++) {
        float y0, y1;
        gather<kD, 16>(&g_yp[hf * 16 * kD + bj * 128 + t3], target, y0, y1, budget);
        y += y0 + y1;
      }
      const uint32_t ob = key >> 16;
      const float upd = y * sigmoidf(__uint_as_float(((ob & 0x8000u) ? (ob ^ 0x8000u) : (~ob & 0xFFFFu)) << 16));
      const float xv = __bfloat162float(P.x[(size_t)idx * kD + bj * 128 + t3]);
      mbar_wait(bars + (B_XT + 1) * 8, 0, budget);
      sts16(sb + ((idx & 64) ? SM_PHI : SM_MOE) + (t3 >> 6) * 8192 + (idx & 63) * 128 + ((((t3 >> 3) & 7) ^ (idx & 7)) << 4) + (t3 & 7) * 2, pack2(xv + upd, 0.f));
      warp_arrive(bars + B_XP * 8, lane);
      if (t3 == 0) TS(11);
    }
  } else if (wg < 2) {
    asm volatile("setmaxnreg.inc.sync.aligned.u32 208;");
    const int tw = tid & 127, w = warp & 3, g = lane >> 2, t = lane & 3;
    const bool lane0 = lane == 0;
    if (wg == 0) sts128(sb + SM_ONE + (tw & 63) * 16, 0x3f803f80u, 0x3f803f80u, 0x3f803f80u, 0x3f803f80u);
    bar_sync(0, 512);
    if (wg == 1) {
      float sr[4], sg[4];
      zero(sr); zero(sg);
#pragma unroll 1
      for (int c = 0; c < 4; c++) {
        mbar_wait(bars + (B_RX + c) * 8, 0, budget);
        uint32_t rs[4], gs[4], xs[4][4];
        lds128(sb + SM_V + c * 512 + lane * 16, rs);
        lds128(sb + SM_V + 2048 + c * 512 + lane * 16, gs);
#pragma unroll
        for (int r = 0; r < 4; r++) lds128(sb + SM_PHI + c * 8192 + (w * 4 + r) * 512 + lane * 16, xs[r]);
#pragma unroll
        for (int e = 0; e < 4; e++) {
          const float r0 = bf_lo(rs[e]), r1 = bf_hi(rs[e]), g0 = bf_lo(gs[e]), g1 = bf_hi(gs[e]);
#pragma unroll
          for (int r = 0; r < 4; r++) {
            const float x0 = bf_lo(xs[r][e]), x1 = bf_hi(xs[r][e]);
            sr[r] = fma_v(x0, r0, sr[r]); sg[r] = fma_v(x0, g0, sg[r]);
            sr[r] = fma_v(x1, r1, sr[r]); sg[r] = fma_v(x1, g1, sg[r]);
            if (r != 1) yield_slot();
          }
        }
      }
      fence_async_smem();
      __syncwarp();
      if (lane < 3) mbar_arrive(bars + (B_ME + lane) * 8);
      const bool b4 = lane & 16, b3 = lane & 8, b2 = lane & 4;
      const float v = qsum(fold(fold(fold(sr[0], sg[0], b4, 16), fold(sr[2], sg[2], b4, 16), b3, 8),
                                fold(fold(sr[1], sg[1], b4, 16), fold(sr[3], sg[3], b4, 16), b3, 8), b2, 4));
      const int row = bi * 128 + bj * 16 + w * 4 + (g & 3);
      const uint32_t rb = pack2(v + 0.f, 0.f);
      const uint32_t ob = (rb & 0x8000u) ? (~rb & 0xFFFFu) : (rb | 0x8000u);
      const uint32_t best = __reduce_max_sync(0xffffffffu, b4 ? 0u : (ob << 16) | (0xFFFFu - row));
      mbar_wait(bars + B_EPOCH * 8, 0, budget);
      const uint32_t tag = lds32(sb + SM_MISC);
      if (lane0) sts32(sb + SM_MISC + 16 + w * 4, best);
      if (b4 && t == 0) st_tagged(&g_gate[row], __float_as_uint(sigmoidf(v)), tag);
      if (tw == 0) TS(14);
      bar_arrive(6, 256);
      bar_sync(1, 256);
    }

    {
      float acc[2][64];
      if (tw == 0) TS(16 + wg * 16);
      mainloop128(acc, P.da, P.db, wg, wg, 16, lane0, budget, cta, wg * 16);
      bar_sync(1 + wg, 256);
      wg_wait<0>();
      pin(acc[0]); pin(acc[1]);
      if (lane0) mbar_arrive_n(bars + (B_EM + wg) * 8, 2);
      if (tw == 0) TS(17 + wg * 16);
      float p[4][16];
      uint32_t vp[8][4];
      const uint32_t av = sb + SM_V + (w * 16 + g) * 64 + ((t ^ (g >> 1)) << 4);
      {
        uint32_t kf[4][2][4];
#pragma unroll
        for (int u = 0; u < 4; u++)
#pragma unroll
          for (int s = 0; s < 2; s++)
#pragma unroll
            for (int r = 0; r < 4; r++) kf[u][s][r] = pack2(acc[u & 1][16 * (u >> 1) + 8 * s + 2 * r], acc[u & 1][16 * (u >> 1) + 8 * s + 2 * r + 1]);
        mbar_wait(bars + B_WPHI * 8, 0, budget);
        const uint64_t dw = P.dw + wg * 256;
        wg_fence();
#pragma unroll
        for (int u = 0; u < 4; u++) {
          wgmma_m64n32k16_rs<1>(p[u], kf[u][0], dw + (u >> 1) * 128, 0);
          wgmma_m64n32k16_rs<1>(p[u], kf[u][1], dw + (u >> 1) * 128 + 64, 1);
        }
        wg_commit();
#pragma unroll
        for (int u = 0; u < 8; u++) {
          const float* a = &acc[(u >> 1) & 1][32 + 16 * (u >> 2) + 2 * (u & 1)];
          vp[u][0] = pack2(a[0], a[1]); vp[u][1] = pack2(a[4], a[5]); vp[u][2] = pack2(a[8], a[9]); vp[u][3] = pack2(a[12], a[13]);
          if (u < 4) sts128(av + (u >> 1) * 4096 + (u & 1) * 512, vp[u][0], vp[u][1], vp[u][2], vp[u][3]);
        }
        pinr(vp);
        wg_wait<0>();
#pragma unroll
        for (int u = 0; u < 4; u++) pin(p[u]);
      }
      if (tw == 0) TS(18 + wg * 16);
      float kv[2][20];
      {
        const uint32_t sphi = sb + SM_PHI + (w * 16 + (lane & 15)) * 128 + (((lane >> 4) ^ (lane & 7)) << 4);
        uint32_t top = EXP_TOP;
        uint32_t pk[4][2][4];
        float ps[2];
        uint32_t sh[1][4];
        uint32_t redo = 0, redo0 = 0;
        const uint32_t astage = sb + (w * 16 + (lane & 15)) * 64 + (((lane >> 4) ^ ((lane >> 1) & 3)) << 4);
        auto stage_kv = [&](int hh) {
#pragma unroll
          for (int q = 0; q < 2; q++) {
            const float* a = &kv[hh][8 * q];
            stmatrix4((astage ^ (q * 32)) + (hh ? SM_PHI : SM_Z), pack2(a[0], a[1]), pack2(a[2], a[3]), pack2(a[4], a[5]), pack2(a[6], a[7]));
          }
        };
#pragma unroll
        for (int i = 0; i < 11; i++) {
          if (i >= 3) {
            const int j = i - 3;
            const uint32_t s2 = add2(sh[0][2], sh[0][3]);
            top = __vmaxu2(top, s2);
            store_phi((sphi ^ ((j & 1) * 64)) + (j & 2) * 4096, pk[j & 3], rcp2(bf_lo(s2)), rcp2(bf_hi(s2)));
          }
          if (i >= 2 && i <= 9) { sh[0][2] = add2(sh[0][0], sh[0][1]); sh[0][3] = __shfl_xor_sync(0xffffffffu, sh[0][2], 2); }
          if (i >= 1 && i <= 8) { sh[0][0] = pack2(ps[0], ps[1]); sh[0][1] = __shfl_xor_sync(0xffffffffu, sh[0][0], 1); }
          if (i == 1) sh[0][2] = sh[0][3] = 0;
          if (i < 8) {
            pin(p[i >> 1]);
            float e[16];
#pragma unroll
            for (int c = 0; c < 16; c++) e[c] = ex2((i & 1) ? -p[i >> 1][c] : p[i >> 1][c]);
            pack_sums(e, pk[i & 3], ps);
            pinr(pk[i & 3]); pin(ps);
          }
          if (i < 10) yield_slot();
          if (i >= 1 && i <= 9) pinr(sh);
          if (i == 7) { wg_wait<0>(); pin(kv[0]); stage_kv(0); }
          if (i == 2 && wg) mbar_wait(bars + B_RD * 8, 0, budget);
          if (i >= 4 && !(i & 1)) {
            const int u = (i - 4) >> 1;
            fence_async_smem();
            wg_wait<0>();
            if (!(u & 1)) bar_sync(7 + wg, 128);
            else asm volatile("{\n.reg .pred p, q;\nsetp.ne.b32 p, %2, %3;\nbar.red.or.pred q, %1, 128, p;\nselp.u32 %0, 1, 0, q;\n}"
                              : "=r"(redo) : "r"(7 + wg), "r"(top), "n"(EXP_TOP) : "memory");
            if (u == 1) redo0 = redo;
            if (u == 2 && lane0 && !redo0) mbar_arrive(bars + (B_RH + wg) * 8);
            issue_kv(kv[u >> 1], P.dphi + (u & 1) * 512, P.dv - (u & 1) * DV_TILE, u & 1);
            if (u == 1 || u == 2) {
#pragma unroll
              for (int r = 0; r < 2; r++) sts128(av + ((u + 1) & 1) * 4096 + r * 512, vp[2 * u + 2 + r][0], vp[2 * u + 2 + r][1], vp[2 * u + 2 + r][2], vp[2 * u + 2 + r][3]);
            }
            if (u < 3) yield_slot();
          }
        }
        if (tw == 0) TS(19 + wg * 16);
        wg_wait<0>();
        pin(kv[0]); pin(kv[1]);
        if (__builtin_expect(__any_sync(0xffffffffu, redo), 0)) {
#pragma unroll 1
          for (int u = 0; u < 4; u++) {
            bar_sync(7 + wg, 128);
#pragma unroll 1
            for (int sg = 0; sg < 2; sg++) {
              float e[16];
              exp_shifted(p[0], sg ? -1.f : 1.f, e);
              pack_sums(e, pk[0], ps);
              store_phi(sphi ^ (sg * 64), pk[0], rcp2(qsum(ps[0])), rcp2(qsum(ps[1])));
            }
            sts128(av, vp[0][0], vp[0][1], vp[0][2], vp[0][3]);
            sts128(av + 512, vp[1][0], vp[1][1], vp[1][2], vp[1][3]);
            fence_async_smem();
            bar_sync(7 + wg, 128);
            issue_kv(kv[1], P.dphi, P.dv, u & 1);
            wg_wait<0>();
            pin(kv[1]);
#pragma unroll
            for (int c = 0; c < 16; c++) { p[0][c] = p[1][c]; p[1][c] = p[2][c]; p[2][c] = p[3][c]; }
#pragma unroll
            for (int c = 0; c < 24; c++) vp[c >> 2][c & 3] = vp[(c >> 2) + 2][c & 3];
            if (u == 1) {
#pragma unroll
              for (int c = 0; c < 20; c++) kv[0][c] = kv[1][c];
            }
          }
          if (__any_sync(0xffffffffu, redo0)) {
            stage_kv(0);
            fence_async_smem();
            warp_arrive(bars + (B_RH + wg) * 8, lane);
          }
        }
        if (tw == 0) TS(20 + wg * 16);
        bar_sync(7 + wg, 128);
        stage_kv(1);
      }
      {
        const uint32_t z = pack2(t == 0 ? kv[0][16] : t == 1 ? kv[1][16] : t == 2 ? kv[0][18] : kv[1][18], 0.0625f);
        sts128(sb + SM_PHI + 4096 + ((w & 1) * 16 + (t >> 1) * 8 + g) * 64 + ((((w & 2) + (t & 1)) ^ (g >> 1)) << 4), z, z, z, z);
      }
      fence_async_smem();
      warp_arrive(bars + (B_RED + wg) * 8, lane);
      if (tw == 0) TS(51 + wg * 4);
    }

    uint32_t stash = sb + 3 * STAGE + w * 4096 + lane * 16;
    const int rowl = wg * 64 + w * 16 + g;
    mbar_wait(bars + B_INFO * 8, 0, budget);
    const float gA = ldsf(sb + SM_G + rowl * 4), gB = ldsf(sb + SM_G + rowl * 4 + 32);
    uint32_t own = sb + 3 * STAGE + rowl * 128 + ((t ^ g) << 4);
    uint32_t sx = sb + (wg ? SM_PHI : SM_MOE) + (w * 16 + (lane & 15)) * 128 + (((lane >> 4) ^ (lane & 7)) << 4);
    uint32_t routed = lds32(sb + SM_MISC + 4) - (bi * 128 + rowl);
    asm volatile("" : "+r"(own), "+r"(stash), "+r"(sx), "+r"(routed));
    {
      float p[4][16];
      uint32_t ef[2][4][4];
      uint32_t qf[4][2][4];
      auto pack_q = [&](const float (&a)[64]) {
#pragma unroll
        for (int i = 0; i < 32; i++) qf[i >> 3][(i >> 2) & 1][i & 3] = pack2(a[2 * i], a[2 * i + 1]);
      };
      if (wg == 0) {
        float acc[2][64];
        bar_sync(2, 256);
        if (tw == 0) TS(22);
        mainloop128(acc, P.da, P.db, 32 % NST, (32 / NST) & 1, 12, lane0, budget, cta, 32);
#pragma unroll
        for (int n = 44; n < 48; n++) {
          mbar_wait(bars + (B_FX + n % NST) * 8, (n / NST) & 1, budget);
          kstep64(acc[0], P.da + (n % NST) * (STAGE >> 4), P.db + (n % NST) * (STAGE >> 4), 1);
          if (n == 47) break;
          wg_wait<1>();
          if (n == 44) {
            if (lane0) mbar_arrive_n(bars + (B_EM + 43 % NST) * 8, 2);
            pin(acc[1]);
            bar_sync(7, 128);
          }
          if (n <= 45) {
#pragma unroll
            for (int u = (n - 44) * 4; u < (n - 43) * 4; u++) {
              const float* a = &acc[1][8 * u];
              sts128(stash + u * 512, pack2(a[0], a[1]), pack2(a[2], a[3]), pack2(a[4], a[5]), pack2(a[6], a[7]));
            }
          }
          if (n == 45) warp_arrive(bars + B_QS * 8, lane);
        }
        bar_sync(13, 256);
        wg_wait<0>();
        pin(acc[0]);
        if (tw == 0) TS(15);
        pack_q(acc[0]);
        issue_pq(p, qf, P.dw, 0);
        bar_arrive(14, 256);
        wg_wait<0>();
      } else {
        float acc[64];
        mbar_wait(bars + B_QS * 8, 0, budget);
#pragma unroll
        for (int u = 0; u < 8; u++) lds128(stash + u * 512, qf[u >> 1][u & 1]);
        pinr(qf[3]);
        bar_sync(13, 256);
#pragma unroll
        for (int n = 44; n < 48; n++) {
#pragma unroll
          for (int hf = 0; hf < 2; hf++) {
            const uint64_t da = P.da + 512 + (n % NST) * (STAGE >> 4) + hf * 4, db = P.db + (n % NST) * (STAGE >> 4) + hf * 256;
            wg_wait<1>();
            if (hf && n > 44 && lane0) mbar_arrive_n(bars + (B_EM + (n - 1) % NST) * 8, 2);
            wg_fence();
            wgmma_m64n128k16_ss<0, 1>(acc, da, db, n > 44 || hf);
            wgmma_m64n128k16_ss<0, 1>(acc, da + 2, db + 128, 1);
            wg_commit();
          }
          if (n == 44) bar_sync(14, 256);
          if (n == 46) issue_pq(p, qf, P.dw, 0);
        }
        wg_wait<0>();
        pin(acc);
        if (lane0) { mbar_arrive_n(bars + (B_EM + 47 % NST) * 8, 2); mbar_arrive(bars + B_T3 * 8); }
        if (tw == 0) TS(23);
        pack_q(acc);
        issue_pq(p, qf, P.dw, 1);
        wg_wait<0>();
      }
#pragma unroll
      for (int h = 0; h < 4; h++) pin(p[h]);
      if (tw == 0) TS(24 + wg * 16);

      RG(1);
      pair_frags(p[0], p[1], ef);
      if (YIELD_EXP && wg) bar_arrive(11, 256);
#pragma unroll 1
      for (int pr = 0; pr < 2; pr++) {
        float np[2][20], nm[2][20];
        RG(2 + pr * 8);
        mbar_wait(bars + (B_KV + pr) * 8, 0, budget);
        RG(3 + pr * 8);
        wg_fence();
#pragma unroll
        for (int hh = 0; hh < 2; hh++) {
          const uint64_t dk = P.dkv - (uint64_t)pr * ((384ull << 16) - 512ull) - hh * ((255ull << 16) - 256ull);
          wgmma_m64n40k16_rs<1>(np[hh], ef[hh][0], dk, 0);
          wgmma_m64n40k16_rs<1>(np[hh], ef[hh][1], dk + 64, 1);
          wgmma_m64n40k16_rs<1>(nm[hh], ef[hh][2], dk + 128 - (126ull << 16), 0);
          wgmma_m64n40k16_rs<1>(nm[hh], ef[hh][3], dk + 192 - (126ull << 16), 1);
          wg_commit();
        }
        uint32_t o[4][4];
#pragma unroll
        for (int hh = 0; hh < 2; hh++) {
          if (hh == 0) wg_wait<1>(); else wg_wait<0>();
          pin(np[hh]); pin(nm[hh]);
          RG(4 + hh + pr * 8);
#pragma unroll
          for (int r = 0; r < 2; r++) {
            const float dp = np[hh][16 + 2 * r], sp = np[hh][17 + 2 * r], dm = nm[hh][16 + 2 * r], sm = nm[hh][17 + 2 * r];
            const float inv = (r == 0 ? gA : gB) * rcp(fmaf(dp, sm, fmaf(1e-6f, sm, dm) * sp));
            const float cp = sm * inv, cm = sp * inv;
#pragma unroll
            for (int c = 0; c < 4; c++)
              o[hh * 2 + r][c] = pack2(fmaf(np[hh][4 * c + 2 * r], cp, nm[hh][4 * c + 2 * r] * cm), fmaf(np[hh][4 * c + 2 * r + 1], cp, nm[hh][4 * c + 2 * r + 1] * cm));
          }
        }
        pinr(o);
        yield_slot();
#pragma unroll
        for (int i = 0; i < 4; i++) sts128((own ^ ((i >> 1) * 64)) + (i & 1) * 1024, o[i][0], o[i][1], o[i][2], o[i][3]);
        fence_async_smem();
        RG(6 + pr * 8);
        warp_arrive(bars + (B_PUB + wg * 2 + pr) * 8, lane);
        RG(7 + pr * 8);
        if (tw == 0) TS(25 + pr + wg * 16);
        if (pr) break;
        own += STAGE;
        if (YIELD_EXP && !wg) bar_sync(11, 256);
        RG(9);
        pin(p[2]); pin(p[3]);
        pair_frags(p[2], p[3], ef);
      }
    }
    uint32_t xf[8][4];
    if (!wg) {
      mbar_wait(bars + B_XT * 8, 0, budget);
      load_x<STAGE>(sx - SM_MOE, xf);
      pinr(xf);
      fence_async_smem();
      warp_arrive(bars + B_XR * 8, lane);
      mbar_wait(bars + (B_PUB + 3) * 8, 0, budget);
    } else {
#pragma unroll
      for (int i = 0; i < 32; i++) xf[i >> 2][i & 3] = 0;
    }
    bar_sync(7 + wg, 128);

    RG(18);
    float oacc[64];
    {
      const uint64_t dam = P.da + wg * 512;
      mbar_wait2(bars + (B_FX + 3) * 8, bars + (B_FX + 4) * 8, 1, budget);
      kstep64(oacc, dam + 3 * (STAGE >> 4), P.db + 3 * (STAGE >> 4), 0);
      if (tw == 0) TS(27 + wg * 16);
      kstep64(oacc, dam + 4 * (STAGE >> 4), P.db + 4 * (STAGE >> 4), 1);
      wg_wait<1>();
      if (lane0) mbar_arrive(bars + (B_EM + 3) * 8);
      if (wg) {
        wg_wait<0>();
        if (lane0) mbar_arrive(bars + (B_EM + 4) * 8);
        mbar_wait(bars + (B_XT + 1) * 8, 0, budget);
        load_x<8192>(sx, xf);
      }
      const uint32_t fy = (B_FY + wg * NST - B_FX) * 8;
      uint32_t rel = bars + (wg ? B_DUMMY : B_EM + 4) * 8;
#pragma unroll 1
      for (uint32_t ph = 0; ph < 2; ph++) {
#pragma unroll 1
        for (uint32_t slot = 0; slot < NST; slot++) {
          const uint32_t fx = bars + B_FX * 8 + slot * 8;
          mbar_wait2(fx, fx + fy, ph, budget);
          kstep64(oacc, dam + slot * (STAGE >> 4), P.db + slot * (STAGE >> 4), 1);
          wg_wait<1>();
          arrive_one(rel);
          rel = fx + (B_EM - B_FX) * 8;
        }
      }
      if (wg) {
#pragma unroll 1
        for (uint32_t slot = 0; slot < 4; slot++) mbar_wait(bars + (B_FY + NST + slot) * 8, 0, budget);
        bar_sync(12, 256);
      }
#pragma unroll 1
      for (uint32_t slot = 0; slot < 4; slot++) {
        if (!wg) mbar_wait2(bars + (B_FX + slot) * 8, bars + (B_FY + slot) * 8, 0, budget);
        wg_wait<1>();
        kstep64(oacc, dam + slot * (STAGE >> 4), P.db + slot * (STAGE >> 4), 1);
      }
      if (!wg) bar_arrive(12, 256);
    }
    if (!wg) mbar_wait(bars + B_MD * 8, 0, budget);
    if (__any_sync(0xffffffffu, (routed & ~8u) == 0)) {
      uint32_t xu[8][4];
      mbar_wait(bars + B_XP * 8, 0, budget);
      load_x<8192>(sx, xu);
#pragma unroll
      for (int i = 0; i < 32; i++) if (routed == (i & 1) * 8u) xf[i >> 2][i & 3] = xu[i >> 2][i & 3];
    }
    const float hA = 1.0f - gA, hB = 1.0f - gB;
    float xv[64];
#pragma unroll
    for (int i = 0; i < 32; i++) { xv[2 * i] = bf_lo(xf[i >> 2][i & 3]); xv[2 * i + 1] = bf_hi(xf[i >> 2][i & 3]); }
    pin(xv);
    yield_slot();
    wg_wait<0>();
    pin(oacc);
    if (tw == 0) TS(29 + wg * 16);
#pragma unroll
    for (int hf = 0; hf < 2; hf++) {
#pragma unroll
      for (int u = hf * 4; u < hf * 4 + 4; u++) {
        const float* a = &oacc[8 * u];
        const float* b = &xv[8 * u];
        stmatrix4((sx ^ ((u & 3) * 32)) + hf * 8192,
                  pack2(fmaf(hA, b[0], a[0]), fmaf(hA, b[1], a[1])), pack2(fmaf(hB, b[2], a[2]), fmaf(hB, b[3], a[3])),
                  pack2(fmaf(hA, b[4], a[4]), fmaf(hA, b[5], a[5])), pack2(fmaf(hB, b[6], a[6]), fmaf(hB, b[7], a[7])));
      }
      fence_async_smem();
      __syncwarp();
      if (elect_one()) tma_store(&mout, sb + (wg ? SM_PHI : SM_MOE) + hf * 8192 + w * 2048, bj * 128 + hf * 64, bi * 128 + warp * 16);
    }
    if (elect_one()) {
      asm volatile("cp.async.bulk.commit_group;" ::: "memory");
      asm volatile("cp.async.bulk.wait_group.read 0;" ::: "memory");
    }
  } else {
    asm volatile("setmaxnreg.dec.sync.aligned.u32 32;");
    if (warp == 8) {
      if (elect_one()) {
        TS(7);
#pragma unroll
        for (int s = 0; s < NST; s++) mbar_init(bars + (B_FX + s) * 8, 1);
        asm volatile("fence.mbarrier_init.release.cluster;" ::: "memory");
        fence_async_smem();
      }
      __syncwarp();
      bar_arrive(0, 512);
      if (elect_one()) {
#pragma unroll 1
        for (int n = 0; n < NST; n++) {
          const uint32_t st = sb + n * STAGE, fb = bars + (B_FX + n) * 8;
          KS(64 + n);
          mbar_expect_tx(fb, STAGE);
          tma_load(st, &mx, fb, n * 64, bi * 128);
          tma_load(st + 16384, &mw, fb, 1024 + bj * 128, n * 64);
          tma_load(st + 24576, &mw, fb, 2048 + bj * 128, n * 64);
        }
      }
      __syncwarp();
      bar_sync(10, 64);
    } else {
      if (warp == 9) {
        if (elect_one()) {
#pragma unroll
          for (int s = B_FY; s < B_NUM; s++) mbar_init(bars + s * 8, s < B_WPHI ? 1 : s < B_EM ? 4 : 8);
          asm volatile("fence.mbarrier_init.release.cluster;" ::: "memory");
          fence_async_smem();
        }
        __syncwarp();
        bar_arrive(10, 64);
      }
      bar_sync(0, 512);
    }
    if (!elect_one()) return;
    if (warp == 8) {
      uint32_t slot = 0, ph = 0;
#pragma unroll 1
      for (int n = NST; n < 48; n++) {
        const int t = n >> 4, k = n & 15;
        const int c0 = t == 2 ? bj * 128 : 1024 + bj * 128 + t * 64, c1 = t == 2 ? c0 + 64 : c0 + 1024;
        const uint32_t st = sb + slot * STAGE, fb = bars + (B_FX + slot) * 8;
        if (n <= NST + 3 * RSTEP && (n - NST) % RSTEP == 0) {
          const int c = (n - NST) / RSTEP;
          mbar_expect_tx(bars + (B_RX + c) * 8, c == 0 ? 8192 + 4096 : 8192);
          tma_load(sb + SM_PHI + c * 8192, &mxr, bars + (B_RX + c) * 8, c * 256, bi * 128 + bj * 16);
          if (c == 0) { bulk_load(sb + SM_V, P.w_r, 2048, bars + B_RX * 8); bulk_load(sb + SM_V + 2048, P.gate_w, 2048, bars + B_RX * 8); }
        }
        mbar_wait(bars + (B_EM + slot) * 8, ph, budget);
        KS(64 + n);
        mbar_expect_tx(fb, STAGE);
        tma_load(st, &mx, fb, k * 64, bi * 128);
        tma_load(st + 16384, &mw, fb, c0, k * 64);
        tma_load(st + 24576, &mw, fb, c1, k * 64);
        if (WOPF && t == 2 && (k & 3) == (bi & 3)) { tma_prefetch(&mwo, c0, k * 64); tma_prefetch(&mwo, c1, k * 64); }
        if (++slot == NST) { slot = 0; ph ^= 1; }
      }
#pragma unroll 1
      for (int s = 0; s < 16; s++) {
        const int p = s < 2 ? s : (s >= 9), q = s < 9 ? s - 2 : s - 9;
        const int k0 = (s < 2 ? bj : q + (q >= bj)) * 128 + p * 64;
        const uint32_t st = sb + slot * STAGE, fb = bars + (B_FX + slot) * 8;
        mbar_wait(bars + (B_EM + slot) * 8, ph, budget);
        KS(64 + 48 + s);
        mbar_expect_tx(fb, 16384);
        tma_load(st + 16384, &mwo, fb, bj * 128, k0);
        tma_load(st + 24576, &mwo, fb, bj * 128 + 64, k0);
        if (s == XS1 || s == XS0) {
#pragma unroll 1
          for (int m = s == XS1; m >= (s != XS0); m--) {
            if (m) mbar_wait(bars + (B_RD + 1) * 8, 0, budget);
            mbar_expect_tx(bars + (B_XT + m) * 8, 16384);
            tma_load(sb + (m ? SM_PHI : 0), &mx64, bars + (B_XT + m) * 8, bj * 128, bi * 128 + m * 64);
            tma_load(sb + (m ? SM_PHI + 8192 : STAGE), &mx64, bars + (B_XT + m) * 8, bj * 128 + 64, bi * 128 + m * 64);
          }
        }
        if (++slot == NST) { slot = 0; ph ^= 1; }
      }
      if (REPF) prefetch_map(&mout);
    } else if (warp == 9) {
      prefetch_map(&mo); prefetch_map(&mout);
      uint32_t old;
      asm volatile("atom.add.release.gpu.global.u32 %0, [%1], 1;" : "=r"(old) : "l"(&g_cnt[C_START]) : "memory");
      sts32(sb + SM_MISC, (old & ~255u) + 256u);
      mbar_arrive(bars + B_EPOCH * 8);
      const CUtensorMap* m = (cta & 8) ? &mu : &mg;
      const int l0 = (cta >> 4) * 14, a0 = (cta & 7) * 64, d1 = (cta >> 2) * 112 - 14 * 16, d2 = (cta & 3) * 4;
      uint32_t buf = 0, ph = 0;
#pragma unroll 1
      for (int c = 0; c < 21; c++) {
        const uint32_t dst = sb + moe_buf(buf), fb = bars + (B_MF + buf) * 8;
        mbar_wait(bars + (B_ME + buf) * 8, ph, budget);
        mbar_expect_tx(fb, 8192);
        if (c < 14) tma_load(dst, m, fb, a0 + ((l0 + c) >> 4) * 512, ((l0 + c) & 15) * 64); else tma_load3(dst, &md, fb, d1 + c * 16, d2);
        if (c == 16) {
#pragma unroll 1
          for (int f = 17; f < 21; f++) { __nanosleep(MGAP); tma_prefetch3(&md, d1 + f * 16, d2); }
        }
        if (c < 2) __nanosleep(MGAP);
        if (c == 17) mbar_arrive(bars + B_M2 * 8);
        if (++buf >= (c >= 14 ? 2 : 3)) { buf = 0; ph ^= 1; }
      }
      mbar_wait(bars + (B_PUB + 1) * 8, 0, budget);
      tma_store(&mo, sb + 4 * STAGE, bj * 128 + 64, bi * 128);
      mbar_wait(bars + (B_PUB + 3) * 8, 0, budget);
      {
        tma_store(&mo, sb + 4 * STAGE + 8192, bj * 128 + 64, bi * 128 + 64);
        asm volatile("cp.async.bulk.commit_group;" ::: "memory");
        asm volatile("cp.async.bulk.wait_group 0;" ::: "memory");
        mbar_arrive(bars + B_PS * 8);
      }
      signal_add(&g_cnt[(C_O + bi * 4 + 1) * 32], 32u);
      TS(57);
      wait_count<POLLF>(&g_cnt[(C_O + bi * 4 + 1) * 32], (old & ~255u) + 256u, budget);
      mbar_arrive(bars + B_P1 * 8);
      TS(3);
    } else {
      const int u = warp - 10, hp = bj * 2 + u;
      mbar_wait(bars + B_EPOCH * 8, 0, budget);
      const uint32_t target = lds32(sb + SM_MISC);
      mbar_wait(bars + B_INFO * 8, 0, budget);
      wait_count<200>(&g_cnt[C_START], target, budget);
      fence_async_global();
#pragma unroll 1
      for (int e = 0; e < 2; e++) {
        uint32_t* cnt = &g_cnt[(e ? C_O + bi * 4 + u * 2 : C_KV + hp) * 32];
        mbar_wait(bars + (e ? B_PUB + u * 2 : B_RH + u) * 8, 0, budget);
        if (e == 0) {
          static_assert(SM_PHI == SM_Z + 4096, "staging is contiguous");
#pragma unroll 1
          for (uint32_t c = 0; c < 10; c++) {
            if (c == 4) {
              asm volatile("cp.async.bulk.commit_group;" ::: "memory");
              asm volatile("cp.async.bulk.wait_group.read 0;" ::: "memory");
              mbar_wait(bars + (B_RED + u) * 8, 0, budget);
              if (u) mbar_arrive(bars + B_AF * 8);
            }
            bulk_reduce(&g_kvr[hp * 2560 + c * 256], sb + SM_Z + c * 1024, 1024);
            if (c < 9) __nanosleep(u && c >= 3 ? RED_GAP1 : RED_GAP0);
          }
          asm volatile("cp.async.bulk.commit_group;" ::: "memory");
          asm volatile("cp.async.bulk.wait_group 0;" ::: "memory");
          TS(21 + u * 16);
          mbar_arrive(bars + (B_RD + u) * 8);
        }
        if (e) {
          tma_store(&mo, sb + 3 * STAGE + u * 8192, bj * 128, bi * 128 + u * 64);
          asm volatile("cp.async.bulk.commit_group;" ::: "memory");
          asm volatile("cp.async.bulk.wait_group 0;" ::: "memory");
        }
        signal_add(cnt, e ? 32u : 16u);
        TS(e ? 56 + u * 2 : 60 + u);
        if (REPF && !e) prefetch_map(&mo);
        if (e == 0) {
          mbar_wait(bars + (u ? B_M2 : B_AF) * 8, 0, budget);
        }
        wait_count<POLLF>(cnt, target, budget);
        fence_async_global();
        if (e == 0) {
          mbar_expect_tx(bars + (B_KV + u) * 8, 10240);
          bulk_load(sb + SM_V + u * 8192, &g_kvr[hp * 2560], 8192, bars + (B_KV + u) * 8);
          bulk_load(sb + SM_Z + u * 2048, &g_kvr[hp * 2560 + 2048], 2048, bars + (B_KV + u) * 8);
          TS(38 + u);
        }
      }
      TS(2 + u * 2);
      if (u == 0) mbar_wait2(bars + B_T3 * 8, bars + B_XR * 8, 0, budget);
      uint32_t slot = 0, ph = 1;
#pragma unroll 1
      for (int s = 2; s < 16; s++) {
        const int p = s >= 9, q = s < 9 ? s - 2 : s - 9;
        if (s == 6) mbar_wait(bars + B_PS * 8, 0, budget);
        if (s == 9) { mbar_wait(bars + B_P1 * 8, 0, budget); fence_async_global(); }
        const uint32_t fb = bars + (B_FY + u * NST + slot) * 8;
        mbar_wait(bars + (B_EM + slot) * 8, ph, budget);
        mbar_expect_tx(fb, 8192);
        tma_load(sb + slot * STAGE + u * 8192, &mo, fb, (q + (q >= bj)) * 128 + p * 64, bi * 128 + u * 64);
        if (++slot == NST) { slot = 0; ph ^= 1; }
      }
    }
  }
}

typedef CUresult (*EncodeFn)(CUtensorMap*, CUtensorMapDataType, cuuint32_t, void*, const cuuint64_t*, const cuuint64_t*, const cuuint32_t*,
                             const cuuint32_t*, CUtensorMapInterleave, CUtensorMapSwizzle, CUtensorMapL2promotion, CUtensorMapFloatOOBfill);

void make_map(EncodeFn enc, CUtensorMap* m, const void* ptr, uint64_t cols, uint64_t rows, uint32_t bc, uint32_t br, CUtensorMapSwizzle swz) {
  const cuuint64_t dims[2] = {cols, rows}, strides[1] = {cols * 2};
  const cuuint32_t box[2] = {bc, br}, es[2] = {1, 1};
  enc(m, CU_TENSOR_MAP_DATA_TYPE_BFLOAT16, 2, const_cast<void*>(ptr), dims, strides, box, es, CU_TENSOR_MAP_INTERLEAVE_NONE, swz,
      CU_TENSOR_MAP_L2_PROMOTION_L2_128B, CU_TENSOR_MAP_FLOAT_OOB_FILL_NONE);
}

}

extern "C" void kernel_launch(void* const* d_in, const int* in_sizes, int n_in, void* d_out, int out_size) {
  (void)in_sizes; (void)n_in; (void)out_size;
  void* fn = nullptr;
  cudaDriverEntryPointQueryResult qr;
  cudaGetDriverEntryPoint("cuTensorMapEncodeTiled", &fn, cudaEnableDefault, &qr);
  EncodeFn enc = (EncodeFn)fn;
  void* o_ptr = nullptr;
  cudaGetSymbolAddress(&o_ptr, g_o);
  CUtensorMap mx, mw, mwo, mo, mout, mxr, mg, mu, md, mx64;
  make_map(enc, &mx, d_in[0], kD, kS, 64, 128, CU_TENSOR_MAP_SWIZZLE_128B);
  make_map(enc, &mx64, d_in[0], kD, kS, 64, 64, CU_TENSOR_MAP_SWIZZLE_128B);
  make_map(enc, &mxr, d_in[0], kD, kS, 256, 16, CU_TENSOR_MAP_SWIZZLE_NONE);
  make_map(enc, &mw, d_in[1], 3 * kD, kD, 64, 64, CU_TENSOR_MAP_SWIZZLE_128B);
  make_map(enc, &mwo, d_in[3], kD, kD, 64, 64, CU_TENSOR_MAP_SWIZZLE_128B);
  make_map(enc, &mo, o_ptr, kD, kS, 64, 64, CU_TENSOR_MAP_SWIZZLE_128B);
  make_map(enc, &mout, d_out, kD, kS, 64, 16, CU_TENSOR_MAP_SWIZZLE_128B);
  make_map(enc, &mg, d_in[6], kF, kD, 64, 64, CU_TENSOR_MAP_SWIZZLE_128B);
  make_map(enc, &mu, d_in[7], kF, kD, 64, 64, CU_TENSOR_MAP_SWIZZLE_128B);
  {
    const cuuint64_t dims[3] = {64, kF, 16}, strides[2] = {kD * 2, 128};
    const cuuint32_t box[3] = {64, 16, 4}, es[3] = {1, 1, 1};
    enc(&md, CU_TENSOR_MAP_DATA_TYPE_BFLOAT16, 3, d_in[8], dims, strides, box, es, CU_TENSOR_MAP_INTERLEAVE_NONE, CU_TENSOR_MAP_SWIZZLE_128B,
        CU_TENSOR_MAP_L2_PROMOTION_L2_128B, CU_TENSOR_MAP_FLOAT_OOB_FILL_NONE);
  }
  Params P;
  P.x = (const __nv_bfloat16*)d_in[0];
  P.w = (const __nv_bfloat16*)d_in[1];
  P.w_phi = (const __nv_bfloat16*)d_in[2];
  P.w_r = (const __nv_bfloat16*)d_in[5];
  P.gate_w = (const __nv_bfloat16*)d_in[9];
  P.da = make_desc(sb, 16, 1024, 1);
  P.db = make_desc(sb + 16384, 8192, 1024, 1);
  P.dw = make_desc(sb + SM_WPHI, 16, 512, 2);
  P.dphi = make_desc(sb + SM_PHI, 16, 1024, 1);
  P.dv = make_desc(sb + SM_V, SM_ONE - SM_V, 512, 2);
  P.dkv = make_desc(sb + SM_V, SM_Z - SM_V, 512, 2);
  P.dband = make_desc(sb + SM_BAND, 128, 128, 0);
  P.dxs = make_desc(sb + SM_BAND, 16, 128, 0);
  int dev = 0, sms = 0;
  cudaGetDevice(&dev);
  cudaDeviceGetAttribute(&sms, cudaDevAttrMultiProcessorCount, dev);
  auto kern = sms == 132 ? fused_kernel<true> : fused_kernel<false>;
  cudaFuncSetAttribute(kern, cudaFuncAttributeMaxDynamicSharedMemorySize, SM_ALLOC);
  kern<<<132, 512, SM_ALLOC, cudaStreamPerThread>>>(P, mx, mw, mwo, mo, mout, mxr, mg, mu, md, mx64);
}
```

```cpp
#include <cuda_runtime.h>
#include <cuda_bf16.h>
#include <cuda.h>
#include <stdint.h>

namespace {

template<int TA, int TB> __device__ __forceinline__ void wgmma_m64n128k16_ss(float (&d)[64], uint64_t da, uint64_t db, int scale_d) {
  asm volatile("{\n.reg .pred p;\nsetp.ne.b32 p, %66, 0;\n"
    "wgmma.mma_async.sync.aligned.m64n128k16.f32.bf16.bf16 "
    "{%0, %1, %2, %3, %4, %5, %6, %7, %8, %9, %10, %11, %12, %13, %14, %15, "
    "%16, %17, %18, %19, %20, %21, %22, %23, %24, %25, %26, %27, %28, %29, %30, %31, "
    "%32, %33, %34, %35, %36, %37, %38, %39, %40, %41, %42, %43, %44, %45, %46, %47, "
    "%48, %49, %50, %51, %52, %53, %54, %55, %56, %57, %58, %59, %60, %61, %62, %63}, "
    "%64, %65, p, 1, 1, %67, %68;\n}\n"
    : "+f"(d[0]), "+f"(d[1]), "+f"(d[2]), "+f"(d[3]), "+f"(d[4]), "+f"(d[5]), "+f"(d[6]), "+f"(d[7]),
      "+f"(d[8]), "+f"(d[9]), "+f"(d[10]), "+f"(d[11]), "+f"(d[12]), "+f"(d[13]), "+f"(d[14]), "+f"(d[15]),
      "+f"(d[16]), "+f"(d[17]), "+f"(d[18]), "+f"(d[19]), "+f"(d[20]), "+f"(d[21]), "+f"(d[22]), "+f"(d[23]),
      "+f"(d[24]), "+f"(d[25]), "+f"(d[26]), "+f"(d[27]), "+f"(d[28]), "+f"(d[29]), "+f"(d[30]), "+f"(d[31]),
      "+f"(d[32]), "+f"(d[33]), "+f"(d[34]), "+f"(d[35]), "+f"(d[36]), "+f"(d[37]), "+f"(d[38]), "+f"(d[39]),
      "+f"(d[40]), "+f"(d[41]), "+f"(d[42]), "+f"(d[43]), "+f"(d[44]), "+f"(d[45]), "+f"(d[46]), "+f"(d[47]),
      "+f"(d[48]), "+f"(d[49]), "+f"(d[50]), "+f"(d[51]), "+f"(d[52]), "+f"(d[53]), "+f"(d[54]), "+f"(d[55]),
      "+f"(d[56]), "+f"(d[57]), "+f"(d[58]), "+f"(d[59]), "+f"(d[60]), "+f"(d[61]), "+f"(d[62]), "+f"(d[63])
    : "l"(da), "l"(db), "r"(scale_d), "n"(TA), "n"(TB));
}

template<int TB> __device__ __forceinline__ void wgmma_m64n32k16_rs(float (&d)[16], const uint32_t (&a)[4], uint64_t db, int scale_d) {
  asm volatile("{\n.reg .pred p;\nsetp.ne.b32 p, %21, 0;\n"
    "wgmma.mma_async.sync.aligned.m64n32k16.f32.bf16.bf16 "
    "{%0, %1, %2, %3, %4, %5, %6, %7, %8, %9, %10, %11, %12, %13, %14, %15}, "
    "{%16, %17, %18, %19}, %20, p, 1, 1, %22;\n}\n"
    : "+f"(d[0]), "+f"(d[1]), "+f"(d[2]), "+f"(d[3]), "+f"(d[4]), "+f"(d[5]), "+f"(d[6]), "+f"(d[7]),
      "+f"(d[8]), "+f"(d[9]), "+f"(d[10]), "+f"(d[11]), "+f"(d[12]), "+f"(d[13]), "+f"(d[14]), "+f"(d[15])
    : "r"(a[0]), "r"(a[1]), "r"(a[2]), "r"(a[3]), "l"(db), "r"(scale_d), "n"(TB));
}

template<int TA, int TB> __device__ __forceinline__ void wgmma_m64n40k16_ss(float (&d)[20], uint64_t da, uint64_t db, int scale_d) {
  asm volatile("{\n.reg .pred p;\nsetp.ne.b32 p, %22, 0;\n"
    "wgmma.mma_async.sync.aligned.m64n40k16.f32.bf16.bf16 "
    "{%0, %1, %2, %3, %4, %5, %6, %7, %8, %9, %10, %11, %12, %13, %14, %15, "
    "%16, %17, %18, %19}, "
    "%20, %21, p, 1, 1, %23, %24;\n}\n"
    : "+f"(d[0]), "+f"(d[1]), "+f"(d[2]), "+f"(d[3]), "+f"(d[4]), "+f"(d[5]), "+f"(d[6]), "+f"(d[7]),
      "+f"(d[8]), "+f"(d[9]), "+f"(d[10]), "+f"(d[11]), "+f"(d[12]), "+f"(d[13]), "+f"(d[14]), "+f"(d[15]),
      "+f"(d[16]), "+f"(d[17]), "+f"(d[18]), "+f"(d[19])
    : "l"(da), "l"(db), "r"(scale_d), "n"(TA), "n"(TB));
}

template<int TB> __device__ __forceinline__ void wgmma_m64n40k16_rs(float (&d)[20], const uint32_t (&a)[4], uint64_t db, int scale_d) {
  asm volatile("{\n.reg .pred p;\nsetp.ne.b32 p, %25, 0;\n"
    "wgmma.mma_async.sync.aligned.m64n40k16.f32.bf16.bf16 "
    "{%0, %1, %2, %3, %4, %5, %6, %7, %8, %9, %10, %11, %12, %13, %14, %15, "
    "%16, %17, %18, %19}, "
    "{%20, %21, %22, %23}, %24, p, 1, 1, %26;\n}\n"
    : "+f"(d[0]), "+f"(d[1]), "+f"(d[2]), "+f"(d[3]), "+f"(d[4]), "+f"(d[5]), "+f"(d[6]), "+f"(d[7]),
      "+f"(d[8]), "+f"(d[9]), "+f"(d[10]), "+f"(d[11]), "+f"(d[12]), "+f"(d[13]), "+f"(d[14]), "+f"(d[15]),
      "+f"(d[16]), "+f"(d[17]), "+f"(d[18]), "+f"(d[19])
    : "r"(a[0]), "r"(a[1]), "r"(a[2]), "r"(a[3]), "l"(db), "r"(scale_d), "n"(TB));
}

template<int TA, int TB> __device__ __forceinline__ void wgmma_m64n8k16_ss(float (&d)[4], uint64_t da, uint64_t db, int scale_d) {
  asm volatile("{\n.reg .pred p;\nsetp.ne.b32 p, %6, 0;\n"
    "wgmma.mma_async.sync.aligned.m64n8k16.f32.bf16.bf16 "
    "{%0, %1, %2, %3}, "
    "%4, %5, p, 1, 1, %7, %8;\n}\n"
    : "+f"(d[0]), "+f"(d[1]), "+f"(d[2]), "+f"(d[3])
    : "l"(da), "l"(db), "r"(scale_d), "n"(TA), "n"(TB));
}

constexpr int kS = 2048, kD = 1024, kF = 3584;
constexpr int NST = 5, STAGE = 32768;
constexpr uint32_t sb = 1024;
constexpr int SM_V    = NST * STAGE;
constexpr int SM_Z    = SM_V + 16384;
constexpr int SM_PHI  = SM_Z + 4096;
constexpr int SM_MOE  = SM_PHI + 16384;
constexpr int SM_WPHI = SM_MOE + 16384;
constexpr int SM_ONE  = SM_WPHI + 8192;
constexpr int SM_BAND = SM_ONE + 1024;
constexpr int SM_G    = SM_BAND + 2176;
constexpr int SM_BAR  = SM_G + 512;
constexpr int SM_MISC = SM_BAR + 512;
constexpr int SM_TOTAL = SM_MISC + 64;
static_assert(SM_TOTAL <= 232448, "smem");
constexpr uint32_t bars = sb + SM_BAR;
constexpr int B_FX = 0  , B_FY = 5  , B_EPOCH = 16, B_RX = 17  , B_MF = 21  , B_RD = 24  , B_KV = 26  , B_M2 = 28, B_P1 = 29, B_PS = 15, B_XT = 30  , B_AF = 32;
constexpr int B_WPHI = 33, B_INFO = 34, B_QS = 35, B_XP = 36, B_RED = 37  , B_PUB = 39  , B_ME = 43  , B_MD = 46, B_T3 = 47, B_RH = 48  , B_XR = 50;
constexpr int B_EM = 51  , B_DUMMY = 56, B_NUM = 57;
constexpr int C_START = 0, C_O = 1, C_KV = C_O + 64;

__device__ uint2 g_gate[kS];
__device__ uint2 g_key[128];
__device__ uint2 g_pre[4 * kF];
__device__ uint2 g_yp[32 * kD];
__device__ __align__(128) uint32_t g_kvr[16 * 2560];
__device__ __align__(128) uint32_t g_cnt[(C_KV + 32) * 32];
__device__ __align__(1024) __nv_bfloat16 g_o[kS * kD];
#define KS(id)
#define RG(id)
#define TS(id)
#define TSG(id)
constexpr int SM_ALLOC = SM_TOTAL;

#define POLL0 500
#define POLL1 150
#define RSTEP 1
#define POLLR 400
#define EARLY_N 2
#define EARLY_GAP 200
#define POLLF 50
#define RED_GAP0 250
#define RED_GAP1 0
#define YIELD_EXP 1
#define XS0 1
#define XS1 3
#define REPF 1
#define P0_FIRST 1
#define MGAP 300

struct Params {
  const __nv_bfloat16 *x, *w, *w_phi, *w_r, *gate_w;
  uint64_t da, db, dw, dphi, dv, dkv, dband, dxs;
};

__device__ __forceinline__ uint32_t smem_u32(const void* p) { return (uint32_t)__cvta_generic_to_shared(p); }
__device__ __forceinline__ void mbar_init(uint32_t bar, uint32_t cnt) { asm volatile("mbarrier.init.shared::cta.b64 [%0], %1;" :: "r"(bar), "r"(cnt) : "memory"); }
__device__ __forceinline__ void mbar_expect_tx(uint32_t bar, uint32_t bytes) { asm volatile("mbarrier.arrive.expect_tx.shared::cta.b64 _, [%0], %1;" :: "r"(bar), "r"(bytes) : "memory"); }
__device__ __forceinline__ void mbar_arrive(uint32_t bar) { asm volatile("mbarrier.arrive.shared::cta.b64 _, [%0];" :: "r"(bar) : "memory"); }
__device__ __forceinline__ void mbar_arrive_n(uint32_t bar, uint32_t n) { asm volatile("mbarrier.arrive.shared::cta.b64 _, [%0], %1;" :: "r"(bar), "r"(n) : "memory"); }
constexpr int BUDGET = 1 << 20;
__device__ __forceinline__ void mbar_wait(uint32_t bar, uint32_t parity, int& budget) {
  asm volatile("{\n.reg .pred p;\n"
               "WAIT_L:\nmbarrier.try_wait.parity.shared::cta.b64 p, [%1], %2;\n@p bra WAIT_D;\n"
               "add.s32 %0, %0, -1;\nsetp.gt.s32 p, %0, 0;\n@p bra WAIT_L;\nWAIT_D:\n}"
               : "+r"(budget) : "r"(bar), "r"(parity) : "memory");
}
__device__ __forceinline__ void mbar_wait2(uint32_t bar0, uint32_t bar1, uint32_t parity, int& budget) {
  asm volatile("{\n.reg .pred p, q;\n"
               "WAIT_L:\nmbarrier.try_wait.parity.shared::cta.b64 p, [%1], %3;\nmbarrier.try_wait.parity.shared::cta.b64 q, [%2], %3;\n"
               "and.pred p, p, q;\n@p bra WAIT_D;\n"
               "add.s32 %0, %0, -1;\nsetp.gt.s32 p, %0, 0;\n@p bra WAIT_L;\nWAIT_D:\n}"
               : "+r"(budget) : "r"(bar0), "r"(bar1), "r"(parity) : "memory");
}
template <int SLEEP>
__device__ __forceinline__ void wait_count(const uint32_t* p, uint32_t target, int& budget) {
  asm volatile("{\n.reg .pred p;\n.reg .s32 v;\n"
               "WAIT_L:\nld.acquire.gpu.global.s32 v, [%1];\nsub.s32 v, v, %2;\nsetp.ge.s32 p, v, 0;\n@p bra WAIT_D;\n"
               "nanosleep.u32 %3;\nadd.s32 %0, %0, -4;\nsetp.gt.s32 p, %0, 0;\n@p bra WAIT_L;\nWAIT_D:\n}"
               : "+r"(budget) : "l"(p), "r"(target), "n"(SLEEP) : "memory");
}
__device__ __forceinline__ void tma_load(uint32_t dst, const CUtensorMap* m, uint32_t bar, int c0, int c1) {
  asm volatile("cp.async.bulk.tensor.2d.shared::cluster.global.mbarrier::complete_tx::bytes [%0], [%1, {%3, %4}], [%2];"
    :: "r"(dst), "l"(m), "r"(bar), "r"(c0), "r"(c1) : "memory");
}
__device__ __forceinline__ void tma_load3(uint32_t dst, const CUtensorMap* m, uint32_t bar, int c1, int c2) {
  asm volatile("cp.async.bulk.tensor.3d.shared::cluster.global.mbarrier::complete_tx::bytes [%0], [%1, {%5, %3, %4}], [%2];"
    :: "r"(dst), "l"(m), "r"(bar), "r"(c1), "r"(c2), "r"(0) : "memory");
}
__device__ __forceinline__ void tma_prefetch3(const CUtensorMap* m, int c1, int c2) {
  asm volatile("cp.async.bulk.prefetch.tensor.3d.L2.global [%0, {%3, %1, %2}];" :: "l"(m), "r"(c1), "r"(c2), "r"(0) : "memory");
}
__device__ __forceinline__ void tma_store(const CUtensorMap* m, uint32_t src, int c0, int c1) {
  asm volatile("cp.async.bulk.tensor.2d.global.shared::cta.bulk_group [%0, {%2, %3}], [%1];" :: "l"(m), "r"(src), "r"(c0), "r"(c1) : "memory");
}
__device__ __forceinline__ void bulk_load(uint32_t dst, const void* src, uint32_t bytes, uint32_t bar) {
  asm volatile("cp.async.bulk.shared::cluster.global.mbarrier::complete_tx::bytes [%0], [%1], %2, [%3];" :: "r"(dst), "l"(src), "r"(bytes), "r"(bar) : "memory");
}
__device__ __forceinline__ void bulk_reduce(void* dst, uint32_t src, uint32_t bytes) {
  asm volatile("cp.reduce.async.bulk.global.shared::cta.bulk_group.add.noftz.bf16 [%0], [%1], %2;" :: "l"(dst), "r"(src), "r"(bytes) : "memory");
}
__device__ __forceinline__ void prefetch_map(const CUtensorMap* m) { asm volatile("prefetch.tensormap [%0];" :: "l"(m) : "memory"); }
__device__ __forceinline__ bool elect_one() {
  uint32_t p;
  asm volatile("{\n.reg .pred P;\nelect.sync _|P, 0xffffffff;\nselp.u32 %0, 1, 0, P;\n}" : "=r"(p));
  return p;
}
__device__ __forceinline__ void wg_fence() { asm volatile("wgmma.fence.sync.aligned;" ::: "memory"); }
__device__ __forceinline__ void wg_commit() { asm volatile("wgmma.commit_group.sync.aligned;" ::: "memory"); }
template <int N> __device__ __forceinline__ void wg_wait() { asm volatile("wgmma.wait_group.sync.aligned %0;" :: "n"(N) : "memory"); }
template <int N> __device__ __forceinline__ void zero(float (&r)[N]) {
#pragma unroll
  for (int i = 0; i < N; i++) r[i] = 0.f;
}
template <int N> __device__ __forceinline__ void pin(float (&r)[N]) {
#pragma unroll
  for (int i = 0; i < N; i++) asm volatile("" : "+f"(r[i]) :: "memory");
}
template <int N> __device__ __forceinline__ void pinr(uint32_t (&r)[N][4]) {
#pragma unroll
  for (int i = 0; i < N; i++) asm volatile("" : "+r"(r[i][0]), "+r"(r[i][1]), "+r"(r[i][2]), "+r"(r[i][3]) :: "memory");
}
__device__ __forceinline__ void fence_async_smem() { asm volatile("fence.proxy.async.shared::cta;" ::: "memory"); }
__device__ __forceinline__ void fence_async_global() { asm volatile("fence.proxy.async.global;" ::: "memory"); }
__device__ __forceinline__ void bar_sync(int id, int n) { asm volatile("bar.sync %0, %1;" :: "r"(id), "r"(n) : "memory"); }
__device__ __forceinline__ void bar_arrive(int id, int n) { asm volatile("bar.arrive %0, %1;" :: "r"(id), "r"(n) : "memory"); }
__device__ __forceinline__ void arrive_one(uint32_t bar) {
  asm volatile("{\n.reg .pred p;\nelect.sync _|p, 0xffffffff;\n@p mbarrier.arrive.shared::cta.b64 _, [%0];\n}" :: "r"(bar) : "memory");
}
__device__ __forceinline__ void warp_arrive(uint32_t bar, int lane) { __syncwarp(); if (lane == 0) mbar_arrive(bar); }
__host__ __device__ constexpr uint64_t make_desc(uint32_t addr, uint32_t lbo, uint32_t sbo, uint32_t swz) {
  return (uint64_t)((addr & 0x3FFFF) >> 4) | ((uint64_t)((lbo & 0x3FFFF) >> 4) << 16) | ((uint64_t)(sbo >> 4) << 32) | ((uint64_t)swz << 62);
}
__device__ __forceinline__ uint32_t pack2(float lo, float hi) {
  uint32_t r; asm("cvt.rn.bf16x2.f32 %0, %1, %2;" : "=r"(r) : "f"(hi), "f"(lo)); return r;
}
__device__ __forceinline__ float bf_lo(uint32_t v) { return __uint_as_float(v << 16); }
__device__ __forceinline__ float bf_hi(uint32_t v) { return __uint_as_float(v & 0xffff0000u); }
__device__ __forceinline__ float ex2(float x) { float r; asm("ex2.approx.ftz.f32 %0, %1;" : "=f"(r) : "f"(x)); return r; }
__device__ __forceinline__ float rcp(float x) { float r; asm("rcp.approx.ftz.f32 %0, %1;" : "=f"(r) : "f"(x)); return r; }
constexpr float LOG2E = 1.4426950408889634f;
__device__ __forceinline__ float sigmoidf(float x) { return rcp(1.0f + ex2(-LOG2E * x)); }
__device__ __forceinline__ void sts128(uint32_t a, uint32_t x, uint32_t y, uint32_t z, uint32_t w) {
  asm volatile("st.shared.v4.u32 [%0], {%1,%2,%3,%4};" :: "r"(a), "r"(x), "r"(y), "r"(z), "r"(w) : "memory");
}
__device__ __forceinline__ void lds128(uint32_t a, uint32_t (&r)[4]) {
  asm volatile("ld.shared.v4.u32 {%0,%1,%2,%3}, [%4];" : "=r"(r[0]), "=r"(r[1]), "=r"(r[2]), "=r"(r[3]) : "r"(a) : "memory");
}
__device__ __forceinline__ void sts32(uint32_t a, uint32_t v) { asm volatile("st.shared.u32 [%0], %1;" :: "r"(a), "r"(v) : "memory"); }
__device__ __forceinline__ uint32_t lds32(uint32_t a) { uint32_t v; asm volatile("ld.shared.u32 %0, [%1];" : "=r"(v) : "r"(a) : "memory"); return v; }
__device__ __forceinline__ float ldsf(uint32_t a) { return __uint_as_float(lds32(a)); }
__device__ __forceinline__ void stmatrix4(uint32_t a, uint32_t r0, uint32_t r1, uint32_t r2, uint32_t r3) {
  asm volatile("stmatrix.sync.aligned.m8n8.x4.shared.b16 [%0], {%1,%2,%3,%4};" :: "r"(a), "r"(r0), "r"(r1), "r"(r2), "r"(r3) : "memory");
}
__device__ __forceinline__ void ldmatrix4(uint32_t a, uint32_t (&r)[4]) {
  asm volatile("ldmatrix.sync.aligned.m8n8.x4.shared.b16 {%0,%1,%2,%3}, [%4];" : "=r"(r[0]), "=r"(r[1]), "=r"(r[2]), "=r"(r[3]) : "r"(a) : "memory");
}
__device__ __forceinline__ uint4 ldg_nc(const void* p) {
  uint4 v; asm volatile("ld.global.nc.L1::no_allocate.v4.u32 {%0,%1,%2,%3}, [%4];" : "=r"(v.x), "=r"(v.y), "=r"(v.z), "=r"(v.w) : "l"(p)); return v;
}
__device__ __forceinline__ void st_tagged(uint2* p, uint32_t v, uint32_t tag) {
  asm volatile("{\n.reg .b64 x;\nmov.b64 x, {%1, %2};\nst.relaxed.gpu.global.b64 [%0], x;\n}" :: "l"(p), "r"(v), "r"(tag) : "memory");
}
__device__ __forceinline__ uint2 ld_tagged(const uint2* p) {
  uint2 v; asm volatile("{\n.reg .b64 x;\nld.relaxed.gpu.global.b64 x, [%2];\nmov.b64 {%0, %1}, x;\n}" : "=r"(v.x), "=r"(v.y) : "l"(p) : "memory"); return v;
}
__device__ __forceinline__ void probe(const uint2* p, uint32_t tag, int& budget) {
  do { __nanosleep(POLL0); budget -= 16; } while (!__all_sync(0xffffffffu, ld_tagged(p).y == tag) && budget > 0);
}
template <int STRIDE, int N>
__device__ __forceinline__ void gather(const uint2* p, uint32_t tag, float& s0, float& s1, int& budget) {
  uint32_t pause = 0;
  bool again;
#pragma unroll 1
  do {
    __nanosleep(pause);
    pause = POLL0;
    uint32_t bad = 0;
    s0 = s1 = 0.f;
#pragma unroll
    for (int i = 0; i < N; i++) {
      const uint2 w = ld_tagged(p + i * STRIDE);
      bad |= w.y ^ tag;
      if (i < N / 2) s0 += __uint_as_float(w.x); else s1 += __uint_as_float(w.x);
    }
    budget -= 16;
    again = __any_sync(0xffffffffu, bad != 0) && budget > 0;
  } while (again);
}
__device__ __forceinline__ void sts16(uint32_t a, uint32_t v) { asm volatile("st.shared.u16 [%0], %1;" :: "r"(a), "h"((uint16_t)v) : "memory"); }
__device__ __forceinline__ void signal_add(uint32_t* p, uint32_t v) { asm volatile("red.release.gpu.global.add.u32 [%0], %1;" :: "l"(p), "r"(v) : "memory"); }
__device__ __forceinline__ float qmax(float v) { v = fmaxf(v, __shfl_xor_sync(0xffffffffu, v, 1)); return fmaxf(v, __shfl_xor_sync(0xffffffffu, v, 2)); }
__device__ __forceinline__ float qsum(float v) { v += __shfl_xor_sync(0xffffffffu, v, 1); return v + __shfl_xor_sync(0xffffffffu, v, 2); }
__device__ __forceinline__ float fold(float a, float b, bool hi, int m) { return (hi ? b : a) + __shfl_xor_sync(0xffffffffu, hi ? a : b, m); }

__device__ __forceinline__ void yield_slot() { asm volatile("pmevent 0;" ::: "memory"); }
__device__ __forceinline__ float fma_v(float a, float b, float c) { float r; asm volatile("fma.rn.f32 %0, %1, %2, %3;" : "=f"(r) : "f"(a), "f"(b), "f"(c)); return r; }
constexpr uint32_t EXP_TOP = 0x58805880u;
__device__ __forceinline__ void exp_plain(const float (&p)[16], float (&ep)[16], float (&em)[16]) {
#pragma unroll
  for (int i = 0; i < 16; i++) { ep[i] = ex2(p[i]); em[i] = ex2(-p[i]); }
}
__device__ __forceinline__ void exp_shifted(const float (&p)[16], float sgn, float (&e)[16]) {
#pragma unroll
  for (int i = 0; i < 16; i++) e[i] = sgn * p[i];
#pragma unroll
  for (int o = 0; o < 4; o += 2) {
    const float mx = qmax(fmaxf(fmaxf(fmaxf(e[o], e[o + 1]), fmaxf(e[o + 4], e[o + 5])), fmaxf(fmaxf(e[o + 8], e[o + 9]), fmaxf(e[o + 12], e[o + 13]))));
#pragma unroll
    for (int c = 0; c < 4; c++) { e[4 * c + o] = ex2(e[4 * c + o] - mx); e[4 * c + o + 1] = ex2(e[4 * c + o + 1] - mx); }
  }
}
__device__ __forceinline__ void pack_sums(const float (&e)[16], uint32_t (&pk)[2][4], float (&s)[2]) {
#pragma unroll
  for (int i = 0; i < 8; i++) pk[i >> 2][i & 3] = pack2(e[2 * i], e[2 * i + 1]);
#pragma unroll
  for (int o = 0; o < 4; o += 2) s[o >> 1] = ((e[o] + e[o + 1]) + (e[o + 4] + e[o + 5])) + ((e[o + 8] + e[o + 9]) + (e[o + 12] + e[o + 13]));
}
__device__ __forceinline__ uint32_t rcp2(float s) { const float r = rcp(s); return pack2(r, r); }
__device__ __forceinline__ uint32_t add2(uint32_t a, uint32_t b) { uint32_t r; asm("add.rn.bf16x2 %0, %1, %2;" : "=r"(r) : "r"(a), "r"(b)); return r; }
__device__ __forceinline__ uint32_t mul2(uint32_t a, uint32_t b) { uint32_t r; asm("mul.rn.bf16x2 %0, %1, %2;" : "=r"(r) : "r"(a), "r"(b)); return r; }
__device__ __forceinline__ void store_phi(uint32_t a, const uint32_t (&pk)[2][4], uint32_t r0, uint32_t r1) {
#pragma unroll
  for (int h = 0; h < 2; h++) stmatrix4(a ^ (h * 32), mul2(pk[h][0], r0), mul2(pk[h][1], r1), mul2(pk[h][2], r0), mul2(pk[h][3], r1));
}
__device__ __forceinline__ uint32_t exp_frags(const float (&p)[16], uint32_t (&ef)[4][4], uint32_t top) {
  float ep[16], em[16];
  exp_plain(p, ep, em);
#pragma unroll
  for (int s = 0; s < 2; s++)
#pragma unroll
    for (int r = 0; r < 4; r++) {
      ef[s][r] = pack2(ep[8 * s + 2 * r], ep[8 * s + 2 * r + 1]);
      ef[2 + s][r] = pack2(em[8 * s + 2 * r], em[8 * s + 2 * r + 1]);
    }
#pragma unroll
  for (int s = 0; s < 4; s++) top = __vimax3_u16x2(__vimax3_u16x2(top, ef[s][0], ef[s][1]), ef[s][2], ef[s][3]);
  return top;
}
__device__ __forceinline__ void pair_frags(float (&p0)[16], const float (&p1)[16], uint32_t (&ef)[2][4][4]) {
  const uint32_t top = exp_frags(p1, ef[1], exp_frags(p0, ef[0], EXP_TOP));
  if (__builtin_expect(__any_sync(0xffffffffu, top != EXP_TOP), 0)) {
#pragma unroll 1
    for (int u = 0; u < 4; u++) {
      float e[16];
      exp_shifted(p0, (u & 1) ? -1.f : 1.f, e);
#pragma unroll
      for (int r = 0; r < 4; r++) {
#pragma unroll
        for (int s = 0; s < 6; s++) ef[s >> 2][s & 3][r] = ef[(s + 2) >> 2][(s + 2) & 3][r];
        ef[1][2][r] = pack2(e[2 * r], e[2 * r + 1]);
        ef[1][3][r] = pack2(e[8 + 2 * r], e[8 + 2 * r + 1]);
      }
      if (u & 1) {
#pragma unroll
        for (int c = 0; c < 16; c++) p0[c] = p1[c];
      }
    }
  }
}
__device__ __forceinline__ void issue_pq(float (&p)[4][16], const uint32_t (&qf)[4][2][4], uint64_t dw, int accumulate) {
  wg_fence();
#pragma unroll
  for (int h = 0; h < 4; h++) {
    wgmma_m64n32k16_rs<1>(p[h], qf[h][0], dw + h * 128, accumulate);
    wgmma_m64n32k16_rs<1>(p[h], qf[h][1], dw + h * 128 + 64, 1);
  }
  wg_commit();
}

#define SPLIT_BATCH 2
__device__ __forceinline__ void mainloop128(float (&acc)[2][64], uint64_t da0, uint64_t db0, uint32_t slot, uint32_t ph, int steps, bool lane0, int& budget, int cta, int n0) {
  uint32_t prev = 0;
#pragma unroll 1
  for (int k = 0; k < steps; k++) {
    mbar_wait(bars + B_FX * 8 + slot * 8, ph, budget);
    const uint64_t da = da0 + slot * (STAGE >> 4), db = db0 + slot * (STAGE >> 4);
#pragma unroll
    for (int kk = 0; kk < 4; kk++) {
      if (SPLIT_BATCH == 2 || !(kk & 1)) {
        wg_wait<1>();
        if (kk == 3 - SPLIT_BATCH && k > 0 && lane0) mbar_arrive_n(bars + B_EM * 8 + prev * 8, 2);
        wg_fence();
      }
      wgmma_m64n128k16_ss<0, 1>(acc[0], da + kk * 2, db + kk * 128, kk ? 1 : k);
      wgmma_m64n128k16_ss<0, 1>(acc[1], da + 512 + kk * 2, db + kk * 128, kk ? 1 : k);
      if (SPLIT_BATCH == 2 || (kk & 1)) wg_commit();
    }
    prev = slot;
    if (++slot == NST) { slot = 0; ph ^= 1; }
  }
}
__device__ __forceinline__ void kstep64(float (&acc)[64], uint64_t da, uint64_t db, int accumulate) {
  wg_fence();
#pragma unroll
  for (int kk = 0; kk < 4; kk++) wgmma_m64n128k16_ss<0, 1>(acc, da + kk * 2, db + kk * 128, kk ? 1 : accumulate);
  wg_commit();
}
__device__ __forceinline__ void issue_kv(float (&kv)[20], uint64_t dphi, uint64_t dv, int accumulate) {
  wg_fence();
#pragma unroll
  for (int ks = 0; ks < 4; ks++)
    wgmma_m64n40k16_ss<1, 1>(kv, dphi + ks * 128, dv - (uint64_t)ks * ((64ull << 16) - 64ull), ks ? 1 : accumulate);
  wg_commit();
}
template <int HALF>
__device__ __forceinline__ void load_x(uint32_t sx, uint32_t (&xf)[8][4]) {
#pragma unroll
  for (int u = 0; u < 8; u++) ldmatrix4((sx ^ ((u & 3) * 32)) + (u >> 2) * HALF, xf[u]);
}
__device__ __forceinline__ uint32_t moe_buf(uint32_t b) { return b == 2 ? SM_V + 8192 : SM_MOE + b * 8192; }
template <bool DOWN>
__device__ __forceinline__ void moe_chunks(float (&a)[4], int n, uint32_t& buf, uint32_t& ph, uint64_t da0, uint64_t db, bool lane0) {
  int budget = BUDGET;
  zero(a);
#pragma unroll 1
  for (int c = 0; c < n; c++) {
    mbar_wait(bars + B_MF * 8 + buf * 8, ph, budget);
    const uint64_t da = da0 + (moe_buf(buf) >> 4);
    wg_fence();
#pragma unroll
    for (int j = 0; j < 4; j++) wgmma_m64n8k16_ss<1, 0>(a, da + j * 128, DOWN ? db - j : db + j * 2, 1);
    wg_commit();
    wg_wait<0>();
    if (lane0) mbar_arrive(bars + B_ME * 8 + buf * 8);
    db += DOWN ? 16 : 8;
    if (++buf >= (DOWN ? 2 : 3)) { buf = 0; ph ^= 1; }
  }
  pin(a);
}
constexpr uint64_t DV_TILE = 4 * ((64ull << 16) - 64ull);

template <bool BY_SM>
__global__ void __launch_bounds__(512, 1)
fused_kernel(const Params P, const __grid_constant__ CUtensorMap mx, const __grid_constant__ CUtensorMap mw, const __grid_constant__ CUtensorMap mwo,
             const __grid_constant__ CUtensorMap mo, const __grid_constant__ CUtensorMap mout, const __grid_constant__ CUtensorMap mxr,
             const __grid_constant__ CUtensorMap mg, const __grid_constant__ CUtensorMap mu, const __grid_constant__ CUtensorMap md,
             const __grid_constant__ CUtensorMap mx64) {
  extern __shared__ __align__(1024) uint8_t smem_raw[];
  const int tid = threadIdx.x, lane = tid & 31;
  if (tid == 256) TS(1);
  const int warp = __shfl_sync(0xffffffffu, tid >> 5, 0), wg = warp >> 2;
  int budget = BUDGET;
  if (warp == 10 && elect_one()) { prefetch_map(&mx); prefetch_map(&mw); }
  int cta;
  {
    uint32_t smid;
    asm volatile("mov.u32 %0, %%smid;" : "=r"(smid));
    const uint32_t t = smid >> 1, d = ((t - 32) * 37) >> 8;
    const uint32_t p0 = (t & 7) * 8 + (t >> 3), p1 = (t - 31 - d * 7) * 8 + 4 + d, p2 = t < 62 ? t + 4 : t - 58;
    cta = BY_SM ? (t < 32 ? p0 : t < 60 ? p1 : p2) * 2 + (smid & 1) : blockIdx.x;
  }
  if (cta >= 128 || smem_u32(smem_raw) != sb) {
    if (tid == 0) {
      const uint32_t old = atomicAdd(&g_cnt[C_START], 32u);
      wait_count<500>(&g_cnt[C_START], (old & ~255u) + 256u, budget);
    }
    return;
  }
  const int bi = (cta >> 5) * 4 + ((cta >> 2) & 3);
  const int bj = ((cta >> 4) & 1) * 4 + (cta & 3);

  auto load_first = [&](int n) {
    const uint32_t st = sb + n * STAGE, fb = bars + (B_FX + n) * 8;
    KS(64 + n);
    mbar_expect_tx(fb, STAGE);
    tma_load(st, &mx, fb, n * 64, bi * 128);
    tma_load(st + 16384, &mw, fb, 1024 + bj * 128, n * 64);
    tma_load(st + 24576, &mw, fb, 2048 + bj * 128, n * 64);
  };
  if (warp == 8 && elect_one()) {
    TS(7);
#pragma unroll
    for (int s = 0; s < NST; s++) mbar_init(bars + (B_FX + s) * 8, 1);
    asm volatile("fence.mbarrier_init.release.cluster;" ::: "memory");
    fence_async_smem();
#pragma unroll
    for (int n = 0; n < P0_FIRST; n++) load_first(n);
  }
  if (wg < 2 && (warp & 3) < EARLY_N && lane < (wg ? 8 : 16)) {
    const int n = warp & 3;
    const __nv_bfloat16* p = wg ? P.w + (size_t)(n * 64 + bi + (lane >> 1) * 16) * (3 * kD) + 1024 + (lane & 1) * 1024 + bj * 128
                                : P.x + (size_t)(bi * 128 + bj * 16 + lane) * kD + n * 64;
    if (n) __nanosleep(n * EARLY_GAP);
    asm volatile("prefetch.global.L2 [%0];" :: "l"(p));
  }
  __syncwarp();

  if (wg == 3) {
    asm volatile("setmaxnreg.dec.sync.aligned.u32 64;");
    const int t3 = tid - 384, w3 = warp - 12;
    if (t3 == 0) TSG(0);
    if (t3 < 80) *reinterpret_cast<uint4*>(&g_kvr[cta * 320 + t3 * 4]) = make_uint4(0, 0, 0, 0);
    if (t3 < 17) st_tagged(t3 < 16 ? &g_gate[bi * 128 + bj * 16 + t3] : &g_key[cta], 0, 1);
    bar_sync(0, 512);
#pragma unroll 1
    for (int u = 0; u < 4; u++) {
      const uint4 v = ldg_nc(P.w_phi + bj * 4096 + (u * 128 + t3) * 8);
      sts128(sb + SM_WPHI + u * 2048 + (t3 >> 2) * 64 + (((t3 & 3) ^ ((t3 >> 3) & 3)) << 4),
             pack2(LOG2E * bf_lo(v.x), LOG2E * bf_hi(v.x)), pack2(LOG2E * bf_lo(v.y), LOG2E * bf_hi(v.y)),
             pack2(LOG2E * bf_lo(v.z), LOG2E * bf_hi(v.z)), pack2(LOG2E * bf_lo(v.w), LOG2E * bf_hi(v.w)));
    }
    fence_async_smem();
    warp_arrive(bars + B_WPHI * 8, lane);
    bar_sync(6, 256);
    const uint32_t target = lds32(sb + SM_MISC);
    uint32_t key;
    {
      uint32_t kk[4];
      lds128(sb + SM_MISC + 16, kk);
      if (t3 == 0) st_tagged(&g_key[cta], max(max(kk[0], kk[1]), max(kk[2], kk[3])), target);
      uint2 k, gv;
      __nanosleep(POLLR);
      do {
        __nanosleep(POLL1);
        k = ld_tagged(&g_key[t3]);
        gv = ld_tagged(&g_gate[bi * 128 + t3]);
        budget -= 4;
      } while (!__all_sync(0xffffffffu, k.y == target && gv.y == target) && budget > 0);
      key = __reduce_max_sync(0xffffffffu, k.x);
      if (lane == 0) sts32(sb + SM_MISC + 32 + w3 * 4, key);
      sts32(sb + SM_G + t3 * 4, gv.x);
      bar_sync(5, 128);
      lds128(sb + SM_MISC + 32, kk);
      key = max(max(kk[0], kk[1]), max(kk[2], kk[3]));
    }
    const int idx = (0xFFFF - (key & 0xFFFF)) & (kS - 1);
    if (t3 == 0) { sts32(sb + SM_MISC + 4, idx); TS(8); }
    warp_arrive(bars + B_INFO * 8, lane);
    {
      const uint4 v = ldg_nc(P.x + (size_t)idx * kD + t3 * 8);
      sts128(sb + SM_BAND + t3 * 16, v.x, v.y, v.z, v.w);
    }
    const int t2 = (lane & 3) * 2, row = w3 * 16 + (lane >> 2);
    float a[4];
    uint32_t buf = 0, ph = 0;
    fence_async_smem();
    bar_sync(5, 128);
    {
      const int r = cta >> 4;
#pragma unroll 1
      for (int part = 0; part < 2; part++) {
        const int n = part ? 14 - 2 * r : 2 * r;
        moe_chunks<false>(a, n, buf, ph, P.da, P.dxs + (part ? 0 : (16 - n) * 8), lane == 0);
        uint2* dst = &g_pre[(((cta >> 2) & 2) + 1 - part) * kF + ((r - 1 + part) * 8 + (cta & 7)) * 64 + row];
        if (t2 == 0 && n) { st_tagged(dst, __float_as_uint(a[0]), target); st_tagged(dst + 8, __float_as_uint(a[2]), target); }
      }
    }
    if (t3 == 0) TS(9);
    bar_sync(5, 128);
    sts128(sb + SM_BAND + t3 * 16, 0, 0, 0, 0);
    {
      __nanosleep(POLL0);
      float gs, us;
      gather<kF, 4>(&g_pre[(cta >> 2) * 112 + min(t3, 111)], target, gs, us, budget);
      bar_sync(5, 128);
      if (t3 < 112) sts16(sb + SM_BAND + 112 + (t3 >> 3) * 128 + (t3 & 7) * 2, pack2(gs * sigmoidf(gs) * us, 0.f));
    }
    fence_async_smem();
    bar_sync(5, 128);
    if (t3 == 0) TS(12);
    moe_chunks<true>(a, 7, buf, ph, P.da, P.dband + 7, lane == 0);
    if (t3 == 0) TS(10);
    if (t2 < 4) {
      uint2* dst = &g_yp[(cta >> 2) * kD + (cta & 3) * 256 + t2 * 64 + row];
      st_tagged(dst, __float_as_uint(a[0]), target); st_tagged(dst + 8, __float_as_uint(a[2]), target);
      st_tagged(dst + 64, __float_as_uint(a[1]), target); st_tagged(dst + 72, __float_as_uint(a[3]), target);
    }
    if (lane == 0) mbar_arrive(bars + B_MD * 8);
    if ((idx >> 7) == bi) {
      mbar_wait(bars + (B_PUB + 3) * 8, 0, budget);
      if (w3 == 0) probe(&g_yp[lane * kD + bj * 128], target, budget);
      bar_sync(5, 128);
      float y = 0.f;
#pragma unroll 1
      for (int hf = 0; hf < 2; hf++) {
        float y0, y1;
        gather<kD, 16>(&g_yp[hf * 16 * kD + bj * 128 + t3], target, y0, y1, budget);
        y += y0 + y1;
      }
      const uint32_t ob = key >> 16;
      const float upd = y * sigmoidf(__uint_as_float(((ob & 0x8000u) ? (ob ^ 0x8000u) : (~ob & 0xFFFFu)) << 16));
      const float xv = __bfloat162float(P.x[(size_t)idx * kD + bj * 128 + t3]);
      mbar_wait(bars + (B_XT + 1) * 8, 0, budget);
      sts16(sb + ((idx & 64) ? SM_PHI : SM_MOE) + (t3 >> 6) * 8192 + (idx & 63) * 128 + ((((t3 >> 3) & 7) ^ (idx & 7)) << 4) + (t3 & 7) * 2, pack2(xv + upd, 0.f));
      warp_arrive(bars + B_XP * 8, lane);
      if (t3 == 0) TS(11);
    }
  } else if (wg < 2) {
    asm volatile("setmaxnreg.inc.sync.aligned.u32 208;");
    const int tw = tid & 127, w = warp & 3, g = lane >> 2, t = lane & 3;
    const bool lane0 = lane == 0;
    if (wg == 0) sts128(sb + SM_ONE + (tw & 63) * 16, 0x3f803f80u, 0x3f803f80u, 0x3f803f80u, 0x3f803f80u);
    bar_sync(0, 512);
    if (wg == 1) {
      float sr[4], sg[4];
      zero(sr); zero(sg);
#pragma unroll 1
      for (int c = 0; c < 4; c++) {
        mbar_wait(bars + (B_RX + c) * 8, 0, budget);
        uint32_t rs[4], gs[4], xs[4][4];
        lds128(sb + SM_V + c * 512 + lane * 16, rs);
        lds128(sb + SM_V + 2048 + c * 512 + lane * 16, gs);
#pragma unroll
        for (int r = 0; r < 4; r++) lds128(sb + SM_PHI + c * 8192 + (w * 4 + r) * 512 + lane * 16, xs[r]);
#pragma unroll
        for (int e = 0; e < 4; e++) {
          const float r0 = bf_lo(rs[e]), r1 = bf_hi(rs[e]), g0 = bf_lo(gs[e]), g1 = bf_hi(gs[e]);
#pragma unroll
          for (int r = 0; r < 4; r++) {
            const float x0 = bf_lo(xs[r][e]), x1 = bf_hi(xs[r][e]);
            sr[r] = fma_v(x0, r0, sr[r]); sg[r] = fma_v(x0, g0, sg[r]);
            sr[r] = fma_v(x1, r1, sr[r]); sg[r] = fma_v(x1, g1, sg[r]);
            if (r != 1) yield_slot();
          }
        }
      }
      fence_async_smem();
      __syncwarp();
      if (lane < 3) mbar_arrive(bars + (B_ME + lane) * 8);
      const bool b4 = lane & 16, b3 = lane & 8, b2 = lane & 4;
      const float v = qsum(fold(fold(fold(sr[0], sg[0], b4, 16), fold(sr[2], sg[2], b4, 16), b3, 8),
                                fold(fold(sr[1], sg[1], b4, 16), fold(sr[3], sg[3], b4, 16), b3, 8), b2, 4));
      const int row = bi * 128 + bj * 16 + w * 4 + (g & 3);
      const uint32_t rb = pack2(v + 0.f, 0.f);
      const uint32_t ob = (rb & 0x8000u) ? (~rb & 0xFFFFu) : (rb | 0x8000u);
      const uint32_t best = __reduce_max_sync(0xffffffffu, b4 ? 0u : (ob << 16) | (0xFFFFu - row));
      mbar_wait(bars + B_EPOCH * 8, 0, budget);
      const uint32_t tag = lds32(sb + SM_MISC);
      if (lane0) sts32(sb + SM_MISC + 16 + w * 4, best);
      if (b4 && t == 0) st_tagged(&g_gate[row], __float_as_uint(sigmoidf(v)), tag);
      if (tw == 0) TS(14);
      bar_arrive(6, 256);
      bar_sync(1, 256);
    }

    {
      float acc[2][64];
      if (tw == 0) TS(16 + wg * 16);
      mainloop128(acc, P.da, P.db, wg, wg, 16, lane0, budget, cta, wg * 16);
      bar_sync(1 + wg, 256);
      wg_wait<0>();
      pin(acc[0]); pin(acc[1]);
      if (lane0) mbar_arrive_n(bars + (B_EM + wg) * 8, 2);
      if (tw == 0) TS(17 + wg * 16);
      float p[4][16];
      uint32_t vp[8][4];
      const uint32_t av = sb + SM_V + (w * 16 + g) * 64 + ((t ^ (g >> 1)) << 4);
      {
        uint32_t kf[4][2][4];
#pragma unroll
        for (int u = 0; u < 4; u++)
#pragma unroll
          for (int s = 0; s < 2; s++)
#pragma unroll
            for (int r = 0; r < 4; r++) kf[u][s][r] = pack2(acc[u & 1][16 * (u >> 1) + 8 * s + 2 * r], acc[u & 1][16 * (u >> 1) + 8 * s + 2 * r + 1]);
        mbar_wait(bars + B_WPHI * 8, 0, budget);
        const uint64_t dw = P.dw + wg * 256;
        wg_fence();
#pragma unroll
        for (int u = 0; u < 4; u++) {
          wgmma_m64n32k16_rs<1>(p[u], kf[u][0], dw + (u >> 1) * 128, 0);
          wgmma_m64n32k16_rs<1>(p[u], kf[u][1], dw + (u >> 1) * 128 + 64, 1);
        }
        wg_commit();
#pragma unroll
        for (int u = 0; u < 8; u++) {
          const float* a = &acc[(u >> 1) & 1][32 + 16 * (u >> 2) + 2 * (u & 1)];
          vp[u][0] = pack2(a[0], a[1]); vp[u][1] = pack2(a[4], a[5]); vp[u][2] = pack2(a[8], a[9]); vp[u][3] = pack2(a[12], a[13]);
          if (u < 4) sts128(av + (u >> 1) * 4096 + (u & 1) * 512, vp[u][0], vp[u][1], vp[u][2], vp[u][3]);
        }
        pinr(vp);
        wg_wait<0>();
#pragma unroll
        for (int u = 0; u < 4; u++) pin(p[u]);
      }
      if (tw == 0) TS(18 + wg * 16);
      float kv[2][20];
      {
        const uint32_t sphi = sb + SM_PHI + (w * 16 + (lane & 15)) * 128 + (((lane >> 4) ^ (lane & 7)) << 4);
        uint32_t top = EXP_TOP;
        uint32_t pk[4][2][4];
        float ps[2];
        uint32_t sh[1][4];
        uint32_t redo = 0, redo0 = 0;
        const uint32_t astage = sb + (w * 16 + (lane & 15)) * 64 + (((lane >> 4) ^ ((lane >> 1) & 3)) << 4);
        auto stage_kv = [&](int hh) {
#pragma unroll
          for (int q = 0; q < 2; q++) {
            const float* a = &kv[hh][8 * q];
            stmatrix4((astage ^ (q * 32)) + (hh ? SM_PHI : SM_Z), pack2(a[0], a[1]), pack2(a[2], a[3]), pack2(a[4], a[5]), pack2(a[6], a[7]));
          }
        };
#pragma unroll
        for (int i = 0; i < 11; i++) {
          if (i >= 3) {
            const int j = i - 3;
            const uint32_t s2 = add2(sh[0][2], sh[0][3]);
            top = __vmaxu2(top, s2);
            store_phi((sphi ^ ((j & 1) * 64)) + (j & 2) * 4096, pk[j & 3], rcp2(bf_lo(s2)), rcp2(bf_hi(s2)));
          }
          if (i >= 2 && i <= 9) { sh[0][2] = add2(sh[0][0], sh[0][1]); sh[0][3] = __shfl_xor_sync(0xffffffffu, sh[0][2], 2); }
          if (i >= 1 && i <= 8) { sh[0][0] = pack2(ps[0], ps[1]); sh[0][1] = __shfl_xor_sync(0xffffffffu, sh[0][0], 1); }
          if (i == 1) sh[0][2] = sh[0][3] = 0;
          if (i < 8) {
            pin(p[i >> 1]);
            float e[16];
#pragma unroll
            for (int c = 0; c < 16; c++) e[c] = ex2((i & 1) ? -p[i >> 1][c] : p[i >> 1][c]);
            pack_sums(e, pk[i & 3], ps);
            pinr(pk[i & 3]); pin(ps);
          }
          if (i < 10) yield_slot();
          if (i >= 1 && i <= 9) pinr(sh);
          if (i == 7) { wg_wait<0>(); pin(kv[0]); stage_kv(0); }
          if (i == 2 && wg) mbar_wait(bars + B_RD * 8, 0, budget);
          if (i >= 4 && !(i & 1)) {
            const int u = (i - 4) >> 1;
            fence_async_smem();
            wg_wait<0>();
            if (!(u & 1)) bar_sync(7 + wg, 128);
            else asm volatile("{\n.reg .pred p, q;\nsetp.ne.b32 p, %2, %3;\nbar.red.or.pred q, %1, 128, p;\nselp.u32 %0, 1, 0, q;\n}"
                              : "=r"(redo) : "r"(7 + wg), "r"(top), "n"(EXP_TOP) : "memory");
            if (u == 1) redo0 = redo;
            if (u == 2 && lane0 && !redo0) mbar_arrive(bars + (B_RH + wg) * 8);
            issue_kv(kv[u >> 1], P.dphi + (u & 1) * 512, P.dv - (u & 1) * DV_TILE, u & 1);
            if (u == 1 || u == 2) {
#pragma unroll
              for (int r = 0; r < 2; r++) sts128(av + ((u + 1) & 1) * 4096 + r * 512, vp[2 * u + 2 + r][0], vp[2 * u + 2 + r][1], vp[2 * u + 2 + r][2], vp[2 * u + 2 + r][3]);
            }
            if (u < 3) yield_slot();
          }
        }
        if (tw == 0) TS(19 + wg * 16);
        wg_wait<0>();
        pin(kv[0]); pin(kv[1]);
        if (__builtin_expect(__any_sync(0xffffffffu, redo), 0)) {
#pragma unroll 1
          for (int u = 0; u < 4; u++) {
            bar_sync(7 + wg, 128);
#pragma unroll 1
            for (int sg = 0; sg < 2; sg++) {
              float e[16];
              exp_shifted(p[0], sg ? -1.f : 1.f, e);
              pack_sums(e, pk[0], ps);
              store_phi(sphi ^ (sg * 64), pk[0], rcp2(qsum(ps[0])), rcp2(qsum(ps[1])));
            }
            sts128(av, vp[0][0], vp[0][1], vp[0][2], vp[0][3]);
            sts128(av + 512, vp[1][0], vp[1][1], vp[1][2], vp[1][3]);
            fence_async_smem();
            bar_sync(7 + wg, 128);
            issue_kv(kv[1], P.dphi, P.dv, u & 1);
            wg_wait<0>();
            pin(kv[1]);
#pragma unroll
            for (int c = 0; c < 16; c++) { p[0][c] = p[1][c]; p[1][c] = p[2][c]; p[2][c] = p[3][c]; }
#pragma unroll
            for (int c = 0; c < 24; c++) vp[c >> 2][c & 3] = vp[(c >> 2) + 2][c & 3];
            if (u == 1) {
#pragma unroll
              for (int c = 0; c < 20; c++) kv[0][c] = kv[1][c];
            }
          }
          if (__any_sync(0xffffffffu, redo0)) {
            stage_kv(0);
            fence_async_smem();
            warp_arrive(bars + (B_RH + wg) * 8, lane);
          }
        }
        if (tw == 0) TS(20 + wg * 16);
        bar_sync(7 + wg, 128);
        stage_kv(1);
      }
      {
        const uint32_t z = pack2(t == 0 ? kv[0][16] : t == 1 ? kv[1][16] : t == 2 ? kv[0][18] : kv[1][18], 0.0625f);
        sts128(sb + SM_PHI + 4096 + ((w & 1) * 16 + (t >> 1) * 8 + g) * 64 + ((((w & 2) + (t & 1)) ^ (g >> 1)) << 4), z, z, z, z);
      }
      fence_async_smem();
      warp_arrive(bars + (B_RED + wg) * 8, lane);
      if (tw == 0) TS(51 + wg * 4);
    }

    uint32_t stash = sb + 3 * STAGE + w * 4096 + lane * 16;
    const int rowl = wg * 64 + w * 16 + g;
    mbar_wait(bars + B_INFO * 8, 0, budget);
    const float gA = ldsf(sb + SM_G + rowl * 4), gB = ldsf(sb + SM_G + rowl * 4 + 32);
    uint32_t own = sb + 3 * STAGE + rowl * 128 + ((t ^ g) << 4);
    uint32_t sx = sb + (wg ? SM_PHI : SM_MOE) + (w * 16 + (lane & 15)) * 128 + (((lane >> 4) ^ (lane & 7)) << 4);
    uint32_t routed = lds32(sb + SM_MISC + 4) - (bi * 128 + rowl);
    asm volatile("" : "+r"(own), "+r"(stash), "+r"(sx), "+r"(routed));
    {
      float p[4][16];
      uint32_t ef[2][4][4];
      uint32_t qf[4][2][4];
      auto pack_q = [&](const float (&a)[64]) {
#pragma unroll
        for (int i = 0; i < 32; i++) qf[i >> 3][(i >> 2) & 1][i & 3] = pack2(a[2 * i], a[2 * i + 1]);
      };
      if (wg == 0) {
        float acc[2][64];
        bar_sync(2, 256);
        if (tw == 0) TS(22);
        mainloop128(acc, P.da, P.db, 32 % NST, (32 / NST) & 1, 12, lane0, budget, cta, 32);
#pragma unroll
        for (int n = 44; n < 48; n++) {
          mbar_wait(bars + (B_FX + n % NST) * 8, (n / NST) & 1, budget);
          kstep64(acc[0], P.da + (n % NST) * (STAGE >> 4), P.db + (n % NST) * (STAGE >> 4), 1);
          if (n == 47) break;
          wg_wait<1>();
          if (n == 44) {
            if (lane0) mbar_arrive_n(bars + (B_EM + 43 % NST) * 8, 2);
            pin(acc[1]);
            bar_sync(7, 128);
          }
          if (n <= 45) {
#pragma unroll
            for (int u = (n - 44) * 4; u < (n - 43) * 4; u++) {
              const float* a = &acc[1][8 * u];
              sts128(stash + u * 512, pack2(a[0], a[1]), pack2(a[2], a[3]), pack2(a[4], a[5]), pack2(a[6], a[7]));
            }
          }
          if (n == 45) warp_arrive(bars + B_QS * 8, lane);
        }
        bar_sync(13, 256);
        wg_wait<0>();
        pin(acc[0]);
        if (tw == 0) TS(15);
        pack_q(acc[0]);
        issue_pq(p, qf, P.dw, 0);
        bar_arrive(14, 256);
        wg_wait<0>();
      } else {
        float acc[64];
        mbar_wait(bars + B_QS * 8, 0, budget);
#pragma unroll
        for (int u = 0; u < 8; u++) lds128(stash + u * 512, qf[u >> 1][u & 1]);
        pinr(qf[3]);
        bar_sync(13, 256);
#pragma unroll
        for (int n = 44; n < 48; n++) {
#pragma unroll
          for (int hf = 0; hf < 2; hf++) {
            const uint64_t da = P.da + 512 + (n % NST) * (STAGE >> 4) + hf * 4, db = P.db + (n % NST) * (STAGE >> 4) + hf * 256;
            wg_wait<1>();
            if (hf && n > 44 && lane0) mbar_arrive_n(bars + (B_EM + (n - 1) % NST) * 8, 2);
            wg_fence();
            wgmma_m64n128k16_ss<0, 1>(acc, da, db, n > 44 || hf);
            wgmma_m64n128k16_ss<0, 1>(acc, da + 2, db + 128, 1);
            wg_commit();
          }
          if (n == 44) bar_sync(14, 256);
          if (n == 46) issue_pq(p, qf, P.dw, 0);
        }
        wg_wait<0>();
        pin(acc);
        if (lane0) { mbar_arrive_n(bars + (B_EM + 47 % NST) * 8, 2); mbar_arrive(bars + B_T3 * 8); }
        if (tw == 0) TS(23);
        pack_q(acc);
        issue_pq(p, qf, P.dw, 1);
        wg_wait<0>();
      }
#pragma unroll
      for (int h = 0; h < 4; h++) pin(p[h]);
      if (tw == 0) TS(24 + wg * 16);

      RG(1);
      pair_frags(p[0], p[1], ef);
      if (YIELD_EXP && wg) bar_arrive(11, 256);
#pragma unroll 1
      for (int pr = 0; pr < 2; pr++) {
        float np[2][20], nm[2][20];
        RG(2 + pr * 8);
        mbar_wait(bars + (B_KV + pr) * 8, 0, budget);
        RG(3 + pr * 8);
        wg_fence();
#pragma unroll
        for (int hh = 0; hh < 2; hh++) {
          const uint64_t dk = P.dkv - (uint64_t)pr * ((384ull << 16) - 512ull) - hh * ((255ull << 16) - 256ull);
          wgmma_m64n40k16_rs<1>(np[hh], ef[hh][0], dk, 0);
          wgmma_m64n40k16_rs<1>(np[hh], ef[hh][1], dk + 64, 1);
          wgmma_m64n40k16_rs<1>(nm[hh], ef[hh][2], dk + 128 - (126ull << 16), 0);
          wgmma_m64n40k16_rs<1>(nm[hh], ef[hh][3], dk + 192 - (126ull << 16), 1);
          wg_commit();
        }
        uint32_t o[4][4];
#pragma unroll
        for (int hh = 0; hh < 2; hh++) {
          if (hh == 0) wg_wait<1>(); else wg_wait<0>();
          pin(np[hh]); pin(nm[hh]);
          RG(4 + hh + pr * 8);
#pragma unroll
          for (int r = 0; r < 2; r++) {
            const float dp = np[hh][16 + 2 * r], sp = np[hh][17 + 2 * r], dm = nm[hh][16 + 2 * r], sm = nm[hh][17 + 2 * r];
            const float inv = (r == 0 ? gA : gB) * rcp(fmaf(dp, sm, fmaf(1e-6f, sm, dm) * sp));
            const float cp = sm * inv, cm = sp * inv;
#pragma unroll
            for (int c = 0; c < 4; c++)
              o[hh * 2 + r][c] = pack2(fmaf(np[hh][4 * c + 2 * r], cp, nm[hh][4 * c + 2 * r] * cm), fmaf(np[hh][4 * c + 2 * r + 1], cp, nm[hh][4 * c + 2 * r + 1] * cm));
          }
        }
        pinr(o);
        yield_slot();
#pragma unroll
        for (int i = 0; i < 4; i++) sts128((own ^ ((i >> 1) * 64)) + (i & 1) * 1024, o[i][0], o[i][1], o[i][2], o[i][3]);
        fence_async_smem();
        RG(6 + pr * 8);
        warp_arrive(bars + (B_PUB + wg * 2 + pr) * 8, lane);
        RG(7 + pr * 8);
        if (tw == 0) TS(25 + pr + wg * 16);
        if (pr) break;
        own += STAGE;
        if (YIELD_EXP && !wg) bar_sync(11, 256);
        RG(9);
        pin(p[2]); pin(p[3]);
        pair_frags(p[2], p[3], ef);
      }
    }
    uint32_t xf[8][4];
    if (!wg) {
      mbar_wait(bars + B_XT * 8, 0, budget);
      load_x<STAGE>(sx - SM_MOE, xf);
      pinr(xf);
      fence_async_smem();
      warp_arrive(bars + B_XR * 8, lane);
      mbar_wait(bars + (B_PUB + 3) * 8, 0, budget);
    } else {
#pragma unroll
      for (int i = 0; i < 32; i++) xf[i >> 2][i & 3] = 0;
    }
    bar_sync(7 + wg, 128);

    RG(18);
    float oacc[64];
    {
      const uint64_t dam = P.da + wg * 512;
      mbar_wait2(bars + (B_FX + 3) * 8, bars + (B_FX + 4) * 8, 1, budget);
      kstep64(oacc, dam + 3 * (STAGE >> 4), P.db + 3 * (STAGE >> 4), 0);
      if (tw == 0) TS(27 + wg * 16);
      kstep64(oacc, dam + 4 * (STAGE >> 4), P.db + 4 * (STAGE >> 4), 1);
      wg_wait<1>();
      if (lane0) mbar_arrive(bars + (B_EM + 3) * 8);
      if (wg) {
        wg_wait<0>();
        if (lane0) mbar_arrive(bars + (B_EM + 4) * 8);
        mbar_wait(bars + (B_XT + 1) * 8, 0, budget);
        load_x<8192>(sx, xf);
      }
      const uint32_t fy = (B_FY + wg * NST - B_FX) * 8;
      uint32_t rel = bars + (wg ? B_DUMMY : B_EM + 4) * 8;
#pragma unroll 1
      for (uint32_t ph = 0; ph < 2; ph++) {
#pragma unroll 1
        for (uint32_t slot = 0; slot < NST; slot++) {
          const uint32_t fx = bars + B_FX * 8 + slot * 8;
          mbar_wait2(fx, fx + fy, ph, budget);
          kstep64(oacc, dam + slot * (STAGE >> 4), P.db + slot * (STAGE >> 4), 1);
          wg_wait<1>();
          arrive_one(rel);
          rel = fx + (B_EM - B_FX) * 8;
        }
      }
      if (wg) {
#pragma unroll 1
        for (uint32_t slot = 0; slot < 4; slot++) mbar_wait(bars + (B_FY + NST + slot) * 8, 0, budget);
        bar_sync(12, 256);
      }
#pragma unroll 1
      for (uint32_t slot = 0; slot < 4; slot++) {
        if (!wg) mbar_wait2(bars + (B_FX + slot) * 8, bars + (B_FY + slot) * 8, 0, budget);
        wg_wait<1>();
        kstep64(oacc, dam + slot * (STAGE >> 4), P.db + slot * (STAGE >> 4), 1);
      }
      if (!wg) bar_arrive(12, 256);
    }
    if (!wg) mbar_wait(bars + B_MD * 8, 0, budget);
    if (__any_sync(0xffffffffu, (routed & ~8u) == 0)) {
      uint32_t xu[8][4];
      mbar_wait(bars + B_XP * 8, 0, budget);
      load_x<8192>(sx, xu);
#pragma unroll
      for (int i = 0; i < 32; i++) if (routed == (i & 1) * 8u) xf[i >> 2][i & 3] = xu[i >> 2][i & 3];
    }
    const float hA = 1.0f - gA, hB = 1.0f - gB;
    float xv[64];
#pragma unroll
    for (int i = 0; i < 32; i++) { xv[2 * i] = bf_lo(xf[i >> 2][i & 3]); xv[2 * i + 1] = bf_hi(xf[i >> 2][i & 3]); }
    pin(xv);
    yield_slot();
    wg_wait<0>();
    pin(oacc);
    if (tw == 0) TS(29 + wg * 16);
#pragma unroll
    for (int hf = 0; hf < 2; hf++) {
#pragma unroll
      for (int u = hf * 4; u < hf * 4 + 4; u++) {
        const float* a = &oacc[8 * u];
        const float* b = &xv[8 * u];
        stmatrix4((sx ^ ((u & 3) * 32)) + hf * 8192,
                  pack2(fmaf(hA, b[0], a[0]), fmaf(hA, b[1], a[1])), pack2(fmaf(hB, b[2], a[2]), fmaf(hB, b[3], a[3])),
                  pack2(fmaf(hA, b[4], a[4]), fmaf(hA, b[5], a[5])), pack2(fmaf(hB, b[6], a[6]), fmaf(hB, b[7], a[7])));
      }
      fence_async_smem();
      __syncwarp();
      if (elect_one()) tma_store(&mout, sb + (wg ? SM_PHI : SM_MOE) + hf * 8192 + w * 2048, bj * 128 + hf * 64, bi * 128 + warp * 16);
    }
    if (elect_one()) {
      asm volatile("cp.async.bulk.commit_group;" ::: "memory");
      asm volatile("cp.async.bulk.wait_group.read 0;" ::: "memory");
    }
  } else {
    asm volatile("setmaxnreg.dec.sync.aligned.u32 32;");
    if (warp == 8) {
      bar_arrive(0, 512);
      if (elect_one()) {
#pragma unroll 1
        for (int n = P0_FIRST; n < NST; n++) load_first(n);
      }
      __syncwarp();
      bar_sync(10, 64);
    } else {
      if (warp == 9) {
        if (elect_one()) {
#pragma unroll
          for (int s = B_FY; s < B_NUM; s++) mbar_init(bars + s * 8, s < B_WPHI ? 1 : s < B_EM ? 4 : 8);
          asm volatile("fence.mbarrier_init.release.cluster;" ::: "memory");
          fence_async_smem();
        }
        __syncwarp();
        bar_arrive(10, 64);
      }
      bar_sync(0, 512);
    }
    if (!elect_one()) return;
    if (warp == 8) {
      uint32_t slot = 0, ph = 0;
#pragma unroll 1
      for (int n = NST; n < 48; n++) {
        const int t = n >> 4, k = n & 15;
        const int c0 = t == 2 ? bj * 128 : 1024 + bj * 128 + t * 64, c1 = t == 2 ? c0 + 64 : c0 + 1024;
        const uint32_t st = sb + slot * STAGE, fb = bars + (B_FX + slot) * 8;
        if (n <= NST + 3 * RSTEP && (n - NST) % RSTEP == 0) {
          const int c = (n - NST) / RSTEP;
          mbar_expect_tx(bars + (B_RX + c) * 8, c == 0 ? 8192 + 4096 : 8192);
          tma_load(sb + SM_PHI + c * 8192, &mxr, bars + (B_RX + c) * 8, c * 256, bi * 128 + bj * 16);
          if (c == 0) { bulk_load(sb + SM_V, P.w_r, 2048, bars + B_RX * 8); bulk_load(sb + SM_V + 2048, P.gate_w, 2048, bars + B_RX * 8); }
        }
        mbar_wait(bars + (B_EM + slot) * 8, ph, budget);
        KS(64 + n);
        mbar_expect_tx(fb, STAGE);
        tma_load(st, &mx, fb, k * 64, bi * 128);
        tma_load(st + 16384, &mw, fb, c0, k * 64);
        tma_load(st + 24576, &mw, fb, c1, k * 64);
        if (++slot == NST) { slot = 0; ph ^= 1; }
      }
#pragma unroll 1
      for (int s = 0; s < 16; s++) {
        const int p = s < 2 ? s : (s >= 9), q = s < 9 ? s - 2 : s - 9;
        const int k0 = (s < 2 ? bj : q + (q >= bj)) * 128 + p * 64;
        const uint32_t st = sb + slot * STAGE, fb = bars + (B_FX + slot) * 8;
        mbar_wait(bars + (B_EM + slot) * 8, ph, budget);
        KS(64 + 48 + s);
        mbar_expect_tx(fb, 16384);
        tma_load(st + 16384, &mwo, fb, bj * 128, k0);
        tma_load(st + 24576, &mwo, fb, bj * 128 + 64, k0);
        if (s == XS1 || s == XS0) {
#pragma unroll 1
          for (int m = s == XS1; m >= (s != XS0); m--) {
            if (m) mbar_wait(bars + (B_RD + 1) * 8, 0, budget);
            mbar_expect_tx(bars + (B_XT + m) * 8, 16384);
            tma_load(sb + (m ? SM_PHI : 0), &mx64, bars + (B_XT + m) * 8, bj * 128, bi * 128 + m * 64);
            tma_load(sb + (m ? SM_PHI + 8192 : STAGE), &mx64, bars + (B_XT + m) * 8, bj * 128 + 64, bi * 128 + m * 64);
          }
        }
        if (++slot == NST) { slot = 0; ph ^= 1; }
      }
      if (REPF) prefetch_map(&mout);
    } else if (warp == 9) {
      prefetch_map(&mo); prefetch_map(&mout);
      uint32_t old;
      asm volatile("atom.add.release.gpu.global.u32 %0, [%1], 1;" : "=r"(old) : "l"(&g_cnt[C_START]) : "memory");
      sts32(sb + SM_MISC, (old & ~255u) + 256u);
      mbar_arrive(bars + B_EPOCH * 8);
      const CUtensorMap* m = (cta & 8) ? &mu : &mg;
      const int l0 = (cta >> 4) * 14, a0 = (cta & 7) * 64, d1 = (cta >> 2) * 112 - 14 * 16, d2 = (cta & 3) * 4;
      uint32_t buf = 0, ph = 0;
#pragma unroll 1
      for (int c = 0; c < 21; c++) {
        const uint32_t dst = sb + moe_buf(buf), fb = bars + (B_MF + buf) * 8;
        mbar_wait(bars + (B_ME + buf) * 8, ph, budget);
        mbar_expect_tx(fb, 8192);
        if (c < 14) tma_load(dst, m, fb, a0 + ((l0 + c) >> 4) * 512, ((l0 + c) & 15) * 64); else tma_load3(dst, &md, fb, d1 + c * 16, d2);
        if (c == 16) {
#pragma unroll 1
          for (int f = 17; f < 21; f++) { __nanosleep(MGAP); tma_prefetch3(&md, d1 + f * 16, d2); }
        }
        if (c < 2) __nanosleep(MGAP);
        if (c == 17) mbar_arrive(bars + B_M2 * 8);
        if (++buf >= (c >= 14 ? 2 : 3)) { buf = 0; ph ^= 1; }
      }
      mbar_wait(bars + (B_PUB + 1) * 8, 0, budget);
      tma_store(&mo, sb + 4 * STAGE, bj * 128 + 64, bi * 128);
      mbar_wait(bars + (B_PUB + 3) * 8, 0, budget);
      {
        tma_store(&mo, sb + 4 * STAGE + 8192, bj * 128 + 64, bi * 128 + 64);
        asm volatile("cp.async.bulk.commit_group;" ::: "memory");
        asm volatile("cp.async.bulk.wait_group 0;" ::: "memory");
        mbar_arrive(bars + B_PS * 8);
      }
      signal_add(&g_cnt[(C_O + bi * 4 + 1) * 32], 32u);
      TS(57);
      wait_count<POLLF>(&g_cnt[(C_O + bi * 4 + 1) * 32], (old & ~255u) + 256u, budget);
      mbar_arrive(bars + B_P1 * 8);
      TS(3);
    } else {
      const int u = warp - 10, hp = bj * 2 + u;
      mbar_wait(bars + B_EPOCH * 8, 0, budget);
      const uint32_t target = lds32(sb + SM_MISC);
      mbar_wait(bars + B_INFO * 8, 0, budget);
      wait_count<200>(&g_cnt[C_START], target, budget);
      fence_async_global();
#pragma unroll 1
      for (int e = 0; e < 2; e++) {
        uint32_t* cnt = &g_cnt[(e ? C_O + bi * 4 + u * 2 : C_KV + hp) * 32];
        mbar_wait(bars + (e ? B_PUB + u * 2 : B_RH + u) * 8, 0, budget);
        if (e == 0) {
          static_assert(SM_PHI == SM_Z + 4096, "staging is contiguous");
#pragma unroll 1
          for (uint32_t c = 0; c < 10; c++) {
            if (c == 4) {
              asm volatile("cp.async.bulk.commit_group;" ::: "memory");
              asm volatile("cp.async.bulk.wait_group.read 0;" ::: "memory");
              mbar_wait(bars + (B_RED + u) * 8, 0, budget);
              if (u) mbar_arrive(bars + B_AF * 8);
            }
            bulk_reduce(&g_kvr[hp * 2560 + c * 256], sb + SM_Z + c * 1024, 1024);
            if (c < 9) __nanosleep(u && c >= 3 ? RED_GAP1 : RED_GAP0);
          }
          asm volatile("cp.async.bulk.commit_group;" ::: "memory");
          asm volatile("cp.async.bulk.wait_group 0;" ::: "memory");
          TS(21 + u * 16);
          mbar_arrive(bars + (B_RD + u) * 8);
        }
        if (e) {
          tma_store(&mo, sb + 3 * STAGE + u * 8192, bj * 128, bi * 128 + u * 64);
          asm volatile("cp.async.bulk.commit_group;" ::: "memory");
          asm volatile("cp.async.bulk.wait_group 0;" ::: "memory");
        }
        signal_add(cnt, e ? 32u : 16u);
        TS(e ? 56 + u * 2 : 60 + u);
        if (REPF && !e) prefetch_map(&mo);
        if (e == 0) {
          mbar_wait(bars + (u ? B_M2 : B_AF) * 8, 0, budget);
        }
        wait_count<POLLF>(cnt, target, budget);
        fence_async_global();
        if (e == 0) {
          mbar_expect_tx(bars + (B_KV + u) * 8, 10240);
          bulk_load(sb + SM_V + u * 8192, &g_kvr[hp * 2560], 8192, bars + (B_KV + u) * 8);
          bulk_load(sb + SM_Z + u * 2048, &g_kvr[hp * 2560 + 2048], 2048, bars + (B_KV + u) * 8);
          TS(38 + u);
        }
      }
      TS(2 + u * 2);
      if (u == 0) mbar_wait2(bars + B_T3 * 8, bars + B_XR * 8, 0, budget);
      uint32_t slot = 0, ph = 1;
#pragma unroll 1
      for (int s = 2; s < 16; s++) {
        const int p = s >= 9, q = s < 9 ? s - 2 : s - 9;
        if (s == 6) mbar_wait(bars + B_PS * 8, 0, budget);
        if (s == 9) { mbar_wait(bars + B_P1 * 8, 0, budget); fence_async_global(); }
        const uint32_t fb = bars + (B_FY + u * NST + slot) * 8;
        mbar_wait(bars + (B_EM + slot) * 8, ph, budget);
        mbar_expect_tx(fb, 8192);
        tma_load(sb + slot * STAGE + u * 8192, &mo, fb, (q + (q >= bj)) * 128 + p * 64, bi * 128 + u * 64);
        if (++slot == NST) { slot = 0; ph ^= 1; }
      }
    }
  }
}

typedef CUresult (*EncodeFn)(CUtensorMap*, CUtensorMapDataType, cuuint32_t, void*, const cuuint64_t*, const cuuint64_t*, const cuuint32_t*,
                             const cuuint32_t*, CUtensorMapInterleave, CUtensorMapSwizzle, CUtensorMapL2promotion, CUtensorMapFloatOOBfill);

void make_map(EncodeFn enc, CUtensorMap* m, const void* ptr, uint64_t cols, uint64_t rows, uint32_t bc, uint32_t br, CUtensorMapSwizzle swz) {
  const cuuint64_t dims[2] = {cols, rows}, strides[1] = {cols * 2};
  const cuuint32_t box[2] = {bc, br}, es[2] = {1, 1};
  enc(m, CU_TENSOR_MAP_DATA_TYPE_BFLOAT16, 2, const_cast<void*>(ptr), dims, strides, box, es, CU_TENSOR_MAP_INTERLEAVE_NONE, swz,
      CU_TENSOR_MAP_L2_PROMOTION_L2_128B, CU_TENSOR_MAP_FLOAT_OOB_FILL_NONE);
}

}

extern "C" void kernel_launch(void* const* d_in, const int* in_sizes, int n_in, void* d_out, int out_size) {
  (void)in_sizes; (void)n_in; (void)out_size;
  void* fn = nullptr;
  cudaDriverEntryPointQueryResult qr;
  cudaGetDriverEntryPoint("cuTensorMapEncodeTiled", &fn, cudaEnableDefault, &qr);
  EncodeFn enc = (EncodeFn)fn;
  void* o_ptr = nullptr;
  cudaGetSymbolAddress(&o_ptr, g_o);
  CUtensorMap mx, mw, mwo, mo, mout, mxr, mg, mu, md, mx64;
  make_map(enc, &mx, d_in[0], kD, kS, 64, 128, CU_TENSOR_MAP_SWIZZLE_128B);
  make_map(enc, &mx64, d_in[0], kD, kS, 64, 64, CU_TENSOR_MAP_SWIZZLE_128B);
  make_map(enc, &mxr, d_in[0], kD, kS, 256, 16, CU_TENSOR_MAP_SWIZZLE_NONE);
  make_map(enc, &mw, d_in[1], 3 * kD, kD, 64, 64, CU_TENSOR_MAP_SWIZZLE_128B);
  make_map(enc, &mwo, d_in[3], kD, kD, 64, 64, CU_TENSOR_MAP_SWIZZLE_128B);
  make_map(enc, &mo, o_ptr, kD, kS, 64, 64, CU_TENSOR_MAP_SWIZZLE_128B);
  make_map(enc, &mout, d_out, kD, kS, 64, 16, CU_TENSOR_MAP_SWIZZLE_128B);
  make_map(enc, &mg, d_in[6], kF, kD, 64, 64, CU_TENSOR_MAP_SWIZZLE_128B);
  make_map(enc, &mu, d_in[7], kF, kD, 64, 64, CU_TENSOR_MAP_SWIZZLE_128B);
  {
    const cuuint64_t dims[3] = {64, kF, 16}, strides[2] = {kD * 2, 128};
    const cuuint32_t box[3] = {64, 16, 4}, es[3] = {1, 1, 1};
    enc(&md, CU_TENSOR_MAP_DATA_TYPE_BFLOAT16, 3, d_in[8], dims, strides, box, es, CU_TENSOR_MAP_INTERLEAVE_NONE, CU_TENSOR_MAP_SWIZZLE_128B,
        CU_TENSOR_MAP_L2_PROMOTION_L2_128B, CU_TENSOR_MAP_FLOAT_OOB_FILL_NONE);
  }
  Params P;
  P.x = (const __nv_bfloat16*)d_in[0];
  P.w = (const __nv_bfloat16*)d_in[1];
  P.w_phi = (const __nv_bfloat16*)d_in[2];
  P.w_r = (const __nv_bfloat16*)d_in[5];
  P.gate_w = (const __nv_bfloat16*)d_in[9];
  P.da = make_desc(sb, 16, 1024, 1);
  P.db = make_desc(sb + 16384, 8192, 1024, 1);
  P.dw = make_desc(sb + SM_WPHI, 16, 512, 2);
  P.dphi = make_desc(sb + SM_PHI, 16, 1024, 1);
  P.dv = make_desc(sb + SM_V, SM_ONE - SM_V, 512, 2);
  P.dkv = make_desc(sb + SM_V, SM_Z - SM_V, 512, 2);
  P.dband = make_desc(sb + SM_BAND, 128, 128, 0);
  P.dxs = make_desc(sb + SM_BAND, 16, 128, 0);
  int dev = 0, sms = 0;
  cudaGetDevice(&dev);
  cudaDeviceGetAttribute(&sms, cudaDevAttrMultiProcessorCount, dev);
  auto kern = sms == 132 ? fused_kernel<true> : fused_kernel<false>;
  cudaFuncSetAttribute(kern, cudaFuncAttributeMaxDynamicSharedMemorySize, SM_ALLOC);
  kern<<<132, 512, SM_ALLOC, cudaStreamPerThread>>>(P, mx, mw, mwo, mo, mout, mxr, mg, mu, md, mx64);
}
```

```cpp
#include <cuda_runtime.h>
#include <cuda_bf16.h>
#include <cuda.h>
#include <stdint.h>

namespace {

template<int TA, int TB> __device__ __forceinline__ void wgmma_m64n128k16_ss(float (&d)[64], uint64_t da, uint64_t db, int scale_d) {
  asm volatile("{\n.reg .pred p;\nsetp.ne.b32 p, %66, 0;\n"
    "wgmma.mma_async.sync.aligned.m64n128k16.f32.bf16.bf16 "
    "{%0, %1, %2, %3, %4, %5, %6, %7, %8, %9, %10, %11, %12, %13, %14, %15, "
    "%16, %17, %18, %19, %20, %21, %22, %23, %24, %25, %26, %27, %28, %29, %30, %31, "
    "%32, %33, %34, %35, %36, %37, %38, %39, %40, %41, %42, %43, %44, %45, %46, %47, "
    "%48, %49, %50, %51, %52, %53, %54, %55, %56, %57, %58, %59, %60, %61, %62, %63}, "
    "%64, %65, p, 1, 1, %67, %68;\n}\n"
    : "+f"(d[0]), "+f"(d[1]), "+f"(d[2]), "+f"(d[3]), "+f"(d[4]), "+f"(d[5]), "+f"(d[6]), "+f"(d[7]),
      "+f"(d[8]), "+f"(d[9]), "+f"(d[10]), "+f"(d[11]), "+f"(d[12]), "+f"(d[13]), "+f"(d[14]), "+f"(d[15]),
      "+f"(d[16]), "+f"(d[17]), "+f"(d[18]), "+f"(d[19]), "+f"(d[20]), "+f"(d[21]), "+f"(d[22]), "+f"(d[23]),
      "+f"(d[24]), "+f"(d[25]), "+f"(d[26]), "+f"(d[27]), "+f"(d[28]), "+f"(d[29]), "+f"(d[30]), "+f"(d[31]),
      "+f"(d[32]), "+f"(d[33]), "+f"(d[34]), "+f"(d[35]), "+f"(d[36]), "+f"(d[37]), "+f"(d[38]), "+f"(d[39]),
      "+f"(d[40]), "+f"(d[41]), "+f"(d[42]), "+f"(d[43]), "+f"(d[44]), "+f"(d[45]), "+f"(d[46]), "+f"(d[47]),
      "+f"(d[48]), "+f"(d[49]), "+f"(d[50]), "+f"(d[51]), "+f"(d[52]), "+f"(d[53]), "+f"(d[54]), "+f"(d[55]),
      "+f"(d[56]), "+f"(d[57]), "+f"(d[58]), "+f"(d[59]), "+f"(d[60]), "+f"(d[61]), "+f"(d[62]), "+f"(d[63])
    : "l"(da), "l"(db), "r"(scale_d), "n"(TA), "n"(TB));
}

template<int TB> __device__ __forceinline__ void wgmma_m64n32k16_rs(float (&d)[16], const uint32_t (&a)[4], uint64_t db, int scale_d) {
  asm volatile("{\n.reg .pred p;\nsetp.ne.b32 p, %21, 0;\n"
    "wgmma.mma_async.sync.aligned.m64n32k16.f32.bf16.bf16 "
    "{%0, %1, %2, %3, %4, %5, %6, %7, %8, %9, %10, %11, %12, %13, %14, %15}, "
    "{%16, %17, %18, %19}, %20, p, 1, 1, %22;\n}\n"
    : "+f"(d[0]), "+f"(d[1]), "+f"(d[2]), "+f"(d[3]), "+f"(d[4]), "+f"(d[5]), "+f"(d[6]), "+f"(d[7]),
      "+f"(d[8]), "+f"(d[9]), "+f"(d[10]), "+f"(d[11]), "+f"(d[12]), "+f"(d[13]), "+f"(d[14]), "+f"(d[15])
    : "r"(a[0]), "r"(a[1]), "r"(a[2]), "r"(a[3]), "l"(db), "r"(scale_d), "n"(TB));
}

template<int TA, int TB> __device__ __forceinline__ void wgmma_m64n40k16_ss(float (&d)[20], uint64_t da, uint64_t db, int scale_d) {
  asm volatile("{\n.reg .pred p;\nsetp.ne.b32 p, %22, 0;\n"
    "wgmma.mma_async.sync.aligned.m64n40k16.f32.bf16.bf16 "
    "{%0, %1, %2, %3, %4, %5, %6, %7, %8, %9, %10, %11, %12, %13, %14, %15, "
    "%16, %17, %18, %19}, "
    "%20, %21, p, 1, 1, %23, %24;\n}\n"
    : "+f"(d[0]), "+f"(d[1]), "+f"(d[2]), "+f"(d[3]), "+f"(d[4]), "+f"(d[5]), "+f"(d[6]), "+f"(d[7]),
      "+f"(d[8]), "+f"(d[9]), "+f"(d[10]), "+f"(d[11]), "+f"(d[12]), "+f"(d[13]), "+f"(d[14]), "+f"(d[15]),
      "+f"(d[16]), "+f"(d[17]), "+f"(d[18]), "+f"(d[19])
    : "l"(da), "l"(db), "r"(scale_d), "n"(TA), "n"(TB));
}

template<int TB> __device__ __forceinline__ void wgmma_m64n40k16_rs(float (&d)[20], const uint32_t (&a)[4], uint64_t db, int scale_d) {
  asm volatile("{\n.reg .pred p;\nsetp.ne.b32 p, %25, 0;\n"
    "wgmma.mma_async.sync.aligned.m64n40k16.f32.bf16.bf16 "
    "{%0, %1, %2, %3, %4, %5, %6, %7, %8, %9, %10, %11, %12, %13, %14, %15, "
    "%16, %17, %18, %19}, "
    "{%20, %21, %22, %23}, %24, p, 1, 1, %26;\n}\n"
    : "+f"(d[0]), "+f"(d[1]), "+f"(d[2]), "+f"(d[3]), "+f"(d[4]), "+f"(d[5]), "+f"(d[6]), "+f"(d[7]),
      "+f"(d[8]), "+f"(d[9]), "+f"(d[10]), "+f"(d[11]), "+f"(d[12]), "+f"(d[13]), "+f"(d[14]), "+f"(d[15]),
      "+f"(d[16]), "+f"(d[17]), "+f"(d[18]), "+f"(d[19])
    : "r"(a[0]), "r"(a[1]), "r"(a[2]), "r"(a[3]), "l"(db), "r"(scale_d), "n"(TB));
}

template<int TA, int TB> __device__ __forceinline__ void wgmma_m64n8k16_ss(float (&d)[4], uint64_t da, uint64_t db, int scale_d) {
  asm volatile("{\n.reg .pred p;\nsetp.ne.b32 p, %6, 0;\n"
    "wgmma.mma_async.sync.aligned.m64n8k16.f32.bf16.bf16 "
    "{%0, %1, %2, %3}, "
    "%4, %5, p, 1, 1, %7, %8;\n}\n"
    : "+f"(d[0]), "+f"(d[1]), "+f"(d[2]), "+f"(d[3])
    : "l"(da), "l"(db), "r"(scale_d), "n"(TA), "n"(TB));
}

constexpr int kS = 2048, kD = 1024, kF = 3584;
constexpr int NST = 5, STAGE = 32768;
constexpr uint32_t sb = 1024;
constexpr int SM_V    = NST * STAGE;
constexpr int SM_Z    = SM_V + 16384;
constexpr int SM_PHI  = SM_Z + 4096;
constexpr int SM_MOE  = SM_PHI + 16384;
constexpr int SM_WPHI = SM_MOE + 16384;
constexpr int SM_ONE  = SM_WPHI + 8192;
constexpr int SM_BAND = SM_ONE + 1024;
constexpr int SM_G    = SM_BAND + 2176;
constexpr int SM_BAR  = SM_G + 512;
constexpr int SM_MISC = SM_BAR + 512;
constexpr int SM_TOTAL = SM_MISC + 64;
static_assert(SM_TOTAL <= 232448, "smem");
constexpr uint32_t bars = sb + SM_BAR;
constexpr int B_FX = 0  , B_FY = 5  , B_EPOCH = 16, B_RX = 17  , B_MF = 21  , B_RD = 24  , B_KV = 26  , B_AF = 28, B_P1 = 29, B_PS = 15, B_XT = 30  ;
constexpr int B_WPHI = 32, B_INFO = 33, B_QS = 34, B_XP = 35, B_RED = 36  , B_PUB = 38  , B_ME = 42  , B_MD = 45, B_T3 = 46, B_RH = 47  , B_XR = 49;
constexpr int B_EM = 50  , B_DUMMY = 55, B_NUM = 56;
constexpr int C_START = 0, C_O = 1, C_KV = C_O + 64;

__device__ uint2 g_gate[kS];
__device__ uint2 g_key[128];
__device__ uint2 g_pre[4 * kF];
__device__ uint2 g_yp[32 * kD];
__device__ __align__(128) uint32_t g_kvr[16 * 2560];
__device__ __align__(128) uint32_t g_cnt[(C_KV + 32) * 32];
__device__ __align__(1024) __nv_bfloat16 g_o[kS * kD];
#define KS(id)
#define RG(id)
#define TS(id)
#define TSG(id)
constexpr int SM_ALLOC = SM_TOTAL;

#define POLL0 500
#define POLL1 150
#define RSTEP 1
#define POLLR 400
#define EARLY_N 2
#define EARLY_GAP 200
#define POLLF 50
#define RED_GAP0 250
#define RED_GAP1 0
#define YIELD_EXP 1
#define XS0 1
#define XS1 3
#define REPF 1
#define LATE_D 3
#define DPF 1
#define P0_FIRST 1
#define MGAP 300

struct Params {
  const __nv_bfloat16 *x, *w, *w_phi, *w_r, *gate_w;
  uint64_t da, db, dw, dphi, dv, dkv, dband, dxs;
};

__device__ __forceinline__ uint32_t smem_u32(const void* p) { return (uint32_t)__cvta_generic_to_shared(p); }
__device__ __forceinline__ void mbar_init(uint32_t bar, uint32_t cnt) { asm volatile("mbarrier.init.shared::cta.b64 [%0], %1;" :: "r"(bar), "r"(cnt) : "memory"); }
__device__ __forceinline__ void mbar_expect_tx(uint32_t bar, uint32_t bytes) { asm volatile("mbarrier.arrive.expect_tx.shared::cta.b64 _, [%0], %1;" :: "r"(bar), "r"(bytes) : "memory"); }
__device__ __forceinline__ void mbar_arrive(uint32_t bar) { asm volatile("mbarrier.arrive.shared::cta.b64 _, [%0];" :: "r"(bar) : "memory"); }
__device__ __forceinline__ void mbar_arrive_n(uint32_t bar, uint32_t n) { asm volatile("mbarrier.arrive.shared::cta.b64 _, [%0], %1;" :: "r"(bar), "r"(n) : "memory"); }
constexpr int BUDGET = 1 << 20;
__device__ __forceinline__ void mbar_wait(uint32_t bar, uint32_t parity, int& budget) {
  asm volatile("{\n.reg .pred p;\n"
               "WAIT_L:\nmbarrier.try_wait.parity.shared::cta.b64 p, [%1], %2;\n@p bra WAIT_D;\n"
               "add.s32 %0, %0, -1;\nsetp.gt.s32 p, %0, 0;\n@p bra WAIT_L;\nWAIT_D:\n}"
               : "+r"(budget) : "r"(bar), "r"(parity) : "memory");
}
__device__ __forceinline__ void mbar_wait2(uint32_t bar0, uint32_t bar1, uint32_t parity, int& budget) {
  asm volatile("{\n.reg .pred p, q;\n"
               "WAIT_L:\nmbarrier.try_wait.parity.shared::cta.b64 p, [%1], %3;\nmbarrier.try_wait.parity.shared::cta.b64 q, [%2], %3;\n"
               "and.pred p, p, q;\n@p bra WAIT_D;\n"
               "add.s32 %0, %0, -1;\nsetp.gt.s32 p, %0, 0;\n@p bra WAIT_L;\nWAIT_D:\n}"
               : "+r"(budget) : "r"(bar0), "r"(bar1), "r"(parity) : "memory");
}
template <int SLEEP>
__device__ __forceinline__ void wait_count(const uint32_t* p, uint32_t target, int& budget) {
  asm volatile("{\n.reg .pred p;\n.reg .s32 v;\n"
               "WAIT_L:\nld.acquire.gpu.global.s32 v, [%1];\nsub.s32 v, v, %2;\nsetp.ge.s32 p, v, 0;\n@p bra WAIT_D;\n"
               "nanosleep.u32 %3;\nadd.s32 %0, %0, -4;\nsetp.gt.s32 p, %0, 0;\n@p bra WAIT_L;\nWAIT_D:\n}"
               : "+r"(budget) : "l"(p), "r"(target), "n"(SLEEP) : "memory");
}
__device__ __forceinline__ void tma_load(uint32_t dst, const CUtensorMap* m, uint32_t bar, int c0, int c1) {
  asm volatile("cp.async.bulk.tensor.2d.shared::cluster.global.mbarrier::complete_tx::bytes [%0], [%1, {%3, %4}], [%2];"
    :: "r"(dst), "l"(m), "r"(bar), "r"(c0), "r"(c1) : "memory");
}
__device__ __forceinline__ void tma_load3(uint32_t dst, const CUtensorMap* m, uint32_t bar, int c1, int c2) {
  asm volatile("cp.async.bulk.tensor.3d.shared::cluster.global.mbarrier::complete_tx::bytes [%0], [%1, {%5, %3, %4}], [%2];"
    :: "r"(dst), "l"(m), "r"(bar), "r"(c1), "r"(c2), "r"(0) : "memory");
}
__device__ __forceinline__ void tma_prefetch3(const CUtensorMap* m, int c1, int c2) {
  asm volatile("cp.async.bulk.prefetch.tensor.3d.L2.global [%0, {%3, %1, %2}];" :: "l"(m), "r"(c1), "r"(c2), "r"(0) : "memory");
}
__device__ __forceinline__ void tma_store(const CUtensorMap* m, uint32_t src, int c0, int c1) {
  asm volatile("cp.async.bulk.tensor.2d.global.shared::cta.bulk_group [%0, {%2, %3}], [%1];" :: "l"(m), "r"(src), "r"(c0), "r"(c1) : "memory");
}
__device__ __forceinline__ void bulk_load(uint32_t dst, const void* src, uint32_t bytes, uint32_t bar) {
  asm volatile("cp.async.bulk.shared::cluster.global.mbarrier::complete_tx::bytes [%0], [%1], %2, [%3];" :: "r"(dst), "l"(src), "r"(bytes), "r"(bar) : "memory");
}
__device__ __forceinline__ void bulk_reduce(void* dst, uint32_t src, uint32_t bytes) {
  asm volatile("cp.reduce.async.bulk.global.shared::cta.bulk_group.add.noftz.bf16 [%0], [%1], %2;" :: "l"(dst), "r"(src), "r"(bytes) : "memory");
}
__device__ __forceinline__ void prefetch_map(const CUtensorMap* m) { asm volatile("prefetch.tensormap [%0];" :: "l"(m) : "memory"); }
__device__ __forceinline__ bool elect_one() {
  uint32_t p;
  asm volatile("{\n.reg .pred P;\nelect.sync _|P, 0xffffffff;\nselp.u32 %0, 1, 0, P;\n}" : "=r"(p));
  return p;
}
__device__ __forceinline__ void wg_fence() { asm volatile("wgmma.fence.sync.aligned;" ::: "memory"); }
__device__ __forceinline__ void wg_commit() { asm volatile("wgmma.commit_group.sync.aligned;" ::: "memory"); }
template <int N> __device__ __forceinline__ void wg_wait() { asm volatile("wgmma.wait_group.sync.aligned %0;" :: "n"(N) : "memory"); }
template <int N> __device__ __forceinline__ void zero(float (&r)[N]) {
#pragma unroll
  for (int i = 0; i < N; i++) r[i] = 0.f;
}
template <int N> __device__ __forceinline__ void pin(float (&r)[N]) {
#pragma unroll
  for (int i = 0; i < N; i++) asm volatile("" : "+f"(r[i]) :: "memory");
}
template <int N> __device__ __forceinline__ void pinr(uint32_t (&r)[N][4]) {
#pragma unroll
  for (int i = 0; i < N; i++) asm volatile("" : "+r"(r[i][0]), "+r"(r[i][1]), "+r"(r[i][2]), "+r"(r[i][3]) :: "memory");
}
__device__ __forceinline__ void fence_async_smem() { asm volatile("fence.proxy.async.shared::cta;" ::: "memory"); }
__device__ __forceinline__ void fence_async_global() { asm volatile("fence.proxy.async.global;" ::: "memory"); }
__device__ __forceinline__ void bar_sync(int id, int n) { asm volatile("bar.sync %0, %1;" :: "r"(id), "r"(n) : "memory"); }
__device__ __forceinline__ void bar_arrive(int id, int n) { asm volatile("bar.arrive %0, %1;" :: "r"(id), "r"(n) : "memory"); }
__device__ __forceinline__ void arrive_one(uint32_t bar) {
  asm volatile("{\n.reg .pred p;\nelect.sync _|p, 0xffffffff;\n@p mbarrier.arrive.shared::cta.b64 _, [%0];\n}" :: "r"(bar) : "memory");
}
__device__ __forceinline__ void warp_arrive(uint32_t bar, int lane) { __syncwarp(); if (lane == 0) mbar_arrive(bar); }
__host__ __device__ constexpr uint64_t make_desc(uint32_t addr, uint32_t lbo, uint32_t sbo, uint32_t swz) {
  return (uint64_t)((addr & 0x3FFFF) >> 4) | ((uint64_t)((lbo & 0x3FFFF) >> 4) << 16) | ((uint64_t)(sbo >> 4) << 32) | ((uint64_t)swz << 62);
}
__device__ __forceinline__ uint32_t pack2(float lo, float hi) {
  uint32_t r; asm("cvt.rn.bf16x2.f32 %0, %1, %2;" : "=r"(r) : "f"(hi), "f"(lo)); return r;
}
__device__ __forceinline__ float bf_lo(uint32_t v) { return __uint_as_float(v << 16); }
__device__ __forceinline__ float bf_hi(uint32_t v) { return __uint_as_float(v & 0xffff0000u); }
__device__ __forceinline__ float ex2(float x) { float r; asm("ex2.approx.ftz.f32 %0, %1;" : "=f"(r) : "f"(x)); return r; }
__device__ __forceinline__ float rcp(float x) { float r; asm("rcp.approx.ftz.f32 %0, %1;" : "=f"(r) : "f"(x)); return r; }
constexpr float LOG2E = 1.4426950408889634f;
__device__ __forceinline__ float sigmoidf(float x) { return rcp(1.0f + ex2(-LOG2E * x)); }
__device__ __forceinline__ void sts128(uint32_t a, uint32_t x, uint32_t y, uint32_t z, uint32_t w) {
  asm volatile("st.shared.v4.u32 [%0], {%1,%2,%3,%4};" :: "r"(a), "r"(x), "r"(y), "r"(z), "r"(w) : "memory");
}
__device__ __forceinline__ void lds128(uint32_t a, uint32_t (&r)[4]) {
  asm volatile("ld.shared.v4.u32 {%0,%1,%2,%3}, [%4];" : "=r"(r[0]), "=r"(r[1]), "=r"(r[2]), "=r"(r[3]) : "r"(a) : "memory");
}
__device__ __forceinline__ void sts32(uint32_t a, uint32_t v) { asm volatile("st.shared.u32 [%0], %1;" :: "r"(a), "r"(v) : "memory"); }
__device__ __forceinline__ uint32_t lds32(uint32_t a) { uint32_t v; asm volatile("ld.shared.u32 %0, [%1];" : "=r"(v) : "r"(a) : "memory"); return v; }
__device__ __forceinline__ float ldsf(uint32_t a) { return __uint_as_float(lds32(a)); }
__device__ __forceinline__ void stmatrix4(uint32_t a, uint32_t r0, uint32_t r1, uint32_t r2, uint32_t r3) {
  asm volatile("stmatrix.sync.aligned.m8n8.x4.shared.b16 [%0], {%1,%2,%3,%4};" :: "r"(a), "r"(r0), "r"(r1), "r"(r2), "r"(r3) : "memory");
}
__device__ __forceinline__ void ldmatrix4(uint32_t a, uint32_t (&r)[4]) {
  asm volatile("ldmatrix.sync.aligned.m8n8.x4.shared.b16 {%0,%1,%2,%3}, [%4];" : "=r"(r[0]), "=r"(r[1]), "=r"(r[2]), "=r"(r[3]) : "r"(a) : "memory");
}
__device__ __forceinline__ uint4 ldg_nc(const void* p) {
  uint4 v; asm volatile("ld.global.nc.L1::no_allocate.v4.u32 {%0,%1,%2,%3}, [%4];" : "=r"(v.x), "=r"(v.y), "=r"(v.z), "=r"(v.w) : "l"(p)); return v;
}
__device__ __forceinline__ void st_tagged(uint2* p, uint32_t v, uint32_t tag) {
  asm volatile("{\n.reg .b64 x;\nmov.b64 x, {%1, %2};\nst.relaxed.gpu.global.b64 [%0], x;\n}" :: "l"(p), "r"(v), "r"(tag) : "memory");
}
__device__ __forceinline__ uint2 ld_tagged(const uint2* p) {
  uint2 v; asm volatile("{\n.reg .b64 x;\nld.relaxed.gpu.global.b64 x, [%2];\nmov.b64 {%0, %1}, x;\n}" : "=r"(v.x), "=r"(v.y) : "l"(p) : "memory"); return v;
}
__device__ __forceinline__ void probe(const uint2* p, uint32_t tag, int& budget) {
  do { __nanosleep(POLL0); budget -= 16; } while (!__all_sync(0xffffffffu, ld_tagged(p).y == tag) && budget > 0);
}
template <int STRIDE, int N>
__device__ __forceinline__ void gather(const uint2* p, uint32_t tag, float& s0, float& s1, int& budget) {
  uint32_t pause = 0;
  bool again;
#pragma unroll 1
  do {
    __nanosleep(pause);
    pause = POLL0;
    uint32_t bad = 0;
    s0 = s1 = 0.f;
#pragma unroll
    for (int i = 0; i < N; i++) {
      const uint2 w = ld_tagged(p + i * STRIDE);
      bad |= w.y ^ tag;
      if (i < N / 2) s0 += __uint_as_float(w.x); else s1 += __uint_as_float(w.x);
    }
    budget -= 16;
    again = __any_sync(0xffffffffu, bad != 0) && budget > 0;
  } while (again);
}
__device__ __forceinline__ void sts16(uint32_t a, uint32_t v) { asm volatile("st.shared.u16 [%0], %1;" :: "r"(a), "h"((uint16_t)v) : "memory"); }
__device__ __forceinline__ void signal_add(uint32_t* p, uint32_t v) { asm volatile("red.release.gpu.global.add.u32 [%0], %1;" :: "l"(p), "r"(v) : "memory"); }
__device__ __forceinline__ float qmax(float v) { v = fmaxf(v, __shfl_xor_sync(0xffffffffu, v, 1)); return fmaxf(v, __shfl_xor_sync(0xffffffffu, v, 2)); }
__device__ __forceinline__ float qsum(float v) { v += __shfl_xor_sync(0xffffffffu, v, 1); return v + __shfl_xor_sync(0xffffffffu, v, 2); }
__device__ __forceinline__ float fold(float a, float b, bool hi, int m) { return (hi ? b : a) + __shfl_xor_sync(0xffffffffu, hi ? a : b, m); }

__device__ __forceinline__ void yield_slot() { asm volatile("pmevent 0;" ::: "memory"); }
__device__ __forceinline__ float fma_v(float a, float b, float c) { float r; asm volatile("fma.rn.f32 %0, %1, %2, %3;" : "=f"(r) : "f"(a), "f"(b), "f"(c)); return r; }
constexpr uint32_t EXP_TOP = 0x58805880u;
__device__ __forceinline__ void exp_plain(const float (&p)[16], float (&ep)[16], float (&em)[16]) {
#pragma unroll
  for (int i = 0; i < 16; i++) { ep[i] = ex2(p[i]); em[i] = ex2(-p[i]); }
}
__device__ __forceinline__ void exp_shifted(const float (&p)[16], float sgn, float (&e)[16]) {
#pragma unroll
  for (int i = 0; i < 16; i++) e[i] = sgn * p[i];
#pragma unroll
  for (int o = 0; o < 4; o += 2) {
    const float mx = qmax(fmaxf(fmaxf(fmaxf(e[o], e[o + 1]), fmaxf(e[o + 4], e[o + 5])), fmaxf(fmaxf(e[o + 8], e[o + 9]), fmaxf(e[o + 12], e[o + 13]))));
#pragma unroll
    for (int c = 0; c < 4; c++) { e[4 * c + o] = ex2(e[4 * c + o] - mx); e[4 * c + o + 1] = ex2(e[4 * c + o + 1] - mx); }
  }
}
__device__ __forceinline__ void pack_sums(const float (&e)[16], uint32_t (&pk)[2][4], float (&s)[2]) {
#pragma unroll
  for (int i = 0; i < 8; i++) pk[i >> 2][i & 3] = pack2(e[2 * i], e[2 * i + 1]);
#pragma unroll
  for (int o = 0; o < 4; o += 2) s[o >> 1] = ((e[o] + e[o + 1]) + (e[o + 4] + e[o + 5])) + ((e[o + 8] + e[o + 9]) + (e[o + 12] + e[o + 13]));
}
__device__ __forceinline__ uint32_t rcp2(float s) { const float r = rcp(s); return pack2(r, r); }
__device__ __forceinline__ uint32_t add2(uint32_t a, uint32_t b) { uint32_t r; asm("add.rn.bf16x2 %0, %1, %2;" : "=r"(r) : "r"(a), "r"(b)); return r; }
__device__ __forceinline__ uint32_t mul2(uint32_t a, uint32_t b) { uint32_t r; asm("mul.rn.bf16x2 %0, %1, %2;" : "=r"(r) : "r"(a), "r"(b)); return r; }
__device__ __forceinline__ void store_phi(uint32_t a, const uint32_t (&pk)[2][4], uint32_t r0, uint32_t r1) {
#pragma unroll
  for (int h = 0; h < 2; h++) stmatrix4(a ^ (h * 32), mul2(pk[h][0], r0), mul2(pk[h][1], r1), mul2(pk[h][2], r0), mul2(pk[h][3], r1));
}
__device__ __forceinline__ uint32_t exp_frags(const float (&p)[16], uint32_t (&ef)[4][4], uint32_t top) {
  float ep[16], em[16];
  exp_plain(p, ep, em);
#pragma unroll
  for (int s = 0; s < 2; s++)
#pragma unroll
    for (int r = 0; r < 4; r++) {
      ef[s][r] = pack2(ep[8 * s + 2 * r], ep[8 * s + 2 * r + 1]);
      ef[2 + s][r] = pack2(em[8 * s + 2 * r], em[8 * s + 2 * r + 1]);
    }
#pragma unroll
  for (int s = 0; s < 4; s++) top = __vimax3_u16x2(__vimax3_u16x2(top, ef[s][0], ef[s][1]), ef[s][2], ef[s][3]);
  return top;
}
__device__ __forceinline__ void pair_frags(float (&p0)[16], const float (&p1)[16], uint32_t (&ef)[2][4][4]) {
  const uint32_t top = exp_frags(p1, ef[1], exp_frags(p0, ef[0], EXP_TOP));
  if (__builtin_expect(__any_sync(0xffffffffu, top != EXP_TOP), 0)) {
#pragma unroll 1
    for (int u = 0; u < 4; u++) {
      float e[16];
      exp_shifted(p0, (u & 1) ? -1.f : 1.f, e);
#pragma unroll
      for (int r = 0; r < 4; r++) {
#pragma unroll
        for (int s = 0; s < 6; s++) ef[s >> 2][s & 3][r] = ef[(s + 2) >> 2][(s + 2) & 3][r];
        ef[1][2][r] = pack2(e[2 * r], e[2 * r + 1]);
        ef[1][3][r] = pack2(e[8 + 2 * r], e[8 + 2 * r + 1]);
      }
      if (u & 1) {
#pragma unroll
        for (int c = 0; c < 16; c++) p0[c] = p1[c];
      }
    }
  }
}
__device__ __forceinline__ void issue_pq(float (&p)[4][16], const uint32_t (&qf)[4][2][4], uint64_t dw, int accumulate) {
  wg_fence();
#pragma unroll
  for (int h = 0; h < 4; h++) {
    wgmma_m64n32k16_rs<1>(p[h], qf[h][0], dw + h * 128, accumulate);
    wgmma_m64n32k16_rs<1>(p[h], qf[h][1], dw + h * 128 + 64, 1);
  }
  wg_commit();
}

#define QD1 2
#define QD2 2
#define QD3 1
template <int W>
__device__ __forceinline__ void mainloop128(float (&acc)[2][64], uint64_t da0, uint64_t db0, uint32_t slot, uint32_t ph, int steps, bool lane0, int& budget, int cta, int n0) {
  uint32_t prev = 0;
#pragma unroll 1
  for (int k = 0; k < steps; k++) {
    mbar_wait(bars + B_FX * 8 + slot * 8, ph, budget);
    const uint64_t da = da0 + slot * (STAGE >> 4), db = db0 + slot * (STAGE >> 4);
#pragma unroll
    for (int kk = 0; kk < 4; kk++) {
      wg_wait<W>();
      if (kk == W && k > 0 && lane0) mbar_arrive_n(bars + B_EM * 8 + prev * 8, 2);
      wg_fence();
      wgmma_m64n128k16_ss<0, 1>(acc[0], da + kk * 2, db + kk * 128, kk ? 1 : k);
      wgmma_m64n128k16_ss<0, 1>(acc[1], da + 512 + kk * 2, db + kk * 128, kk ? 1 : k);
      wg_commit();
    }
    prev = slot;
    if (++slot == NST) { slot = 0; ph ^= 1; }
  }
}
__device__ __forceinline__ void kstep64(float (&acc)[64], uint64_t da, uint64_t db, int accumulate) {
  wg_fence();
#pragma unroll
  for (int kk = 0; kk < 4; kk++) wgmma_m64n128k16_ss<0, 1>(acc, da + kk * 2, db + kk * 128, kk ? 1 : accumulate);
  wg_commit();
}
__device__ __forceinline__ void issue_kv(float (&kv)[20], uint64_t dphi, uint64_t dv, int accumulate) {
  wg_fence();
#pragma unroll
  for (int ks = 0; ks < 4; ks++)
    wgmma_m64n40k16_ss<1, 1>(kv, dphi + ks * 128, dv - (uint64_t)ks * ((64ull << 16) - 64ull), ks ? 1 : accumulate);
  wg_commit();
}
template <int HALF>
__device__ __forceinline__ void load_x(uint32_t sx, uint32_t (&xf)[8][4]) {
#pragma unroll
  for (int u = 0; u < 8; u++) ldmatrix4((sx ^ ((u & 3) * 32)) + (u >> 2) * HALF, xf[u]);
}
__device__ __forceinline__ uint32_t moe_buf(uint32_t b) { return b == 2 ? SM_V + 8192 : SM_MOE + b * 8192; }
template <bool DOWN>
__device__ __forceinline__ void moe_chunks(float (&a)[4], int n, uint32_t& buf, uint32_t& ph, uint64_t da0, uint64_t db, bool lane0) {
  int budget = BUDGET;
  zero(a);
#pragma unroll 1
  for (int c = 0; c < n; c++) {
    if (DOWN && c == 7 - LATE_D) mbar_wait(bars + B_T3 * 8, 0, budget);
    mbar_wait(bars + B_MF * 8 + buf * 8, ph, budget);
    const uint64_t da = da0 + (moe_buf(buf) >> 4);
    wg_fence();
#pragma unroll
    for (int j = 0; j < 4; j++) wgmma_m64n8k16_ss<1, 0>(a, da + j * 128, DOWN ? db - j : db + j * 2, 1);
    wg_commit();
    wg_wait<0>();
    if (lane0) mbar_arrive(bars + B_ME * 8 + buf * 8);
    db += DOWN ? 16 : 8;
    if (++buf == 3) { buf = 0; ph ^= 1; }
  }
  pin(a);
}
constexpr uint64_t DV_TILE = 4 * ((64ull << 16) - 64ull);

template <bool BY_SM>
__global__ void __launch_bounds__(512, 1)
fused_kernel(const Params P, const __grid_constant__ CUtensorMap mx, const __grid_constant__ CUtensorMap mw, const __grid_constant__ CUtensorMap mwo,
             const __grid_constant__ CUtensorMap mo, const __grid_constant__ CUtensorMap mout, const __grid_constant__ CUtensorMap mxr,
             const __grid_constant__ CUtensorMap mg, const __grid_constant__ CUtensorMap mu, const __grid_constant__ CUtensorMap md,
             const __grid_constant__ CUtensorMap mx64) {
  extern __shared__ __align__(1024) uint8_t smem_raw[];
  const int tid = threadIdx.x, lane = tid & 31;
  if (tid == 256) TS(1);
  const int warp = __shfl_sync(0xffffffffu, tid >> 5, 0), wg = warp >> 2;
  int budget = BUDGET;
  if (warp == 10 && elect_one()) { prefetch_map(&mx); prefetch_map(&mw); }
  int cta;
  {
    uint32_t smid;
    asm volatile("mov.u32 %0, %%smid;" : "=r"(smid));
    const uint32_t t = smid >> 1, d = ((t - 32) * 37) >> 8;
    const uint32_t p0 = (t & 7) * 8 + (t >> 3), p1 = (t - 31 - d * 7) * 8 + 4 + d, p2 = t < 62 ? t + 4 : t - 58;
    cta = BY_SM ? (t < 32 ? p0 : t < 60 ? p1 : p2) * 2 + (smid & 1) : blockIdx.x;
  }
  if (cta >= 128 || smem_u32(smem_raw) != sb) {
    if (tid == 0) {
      const uint32_t old = atomicAdd(&g_cnt[C_START], 32u);
      wait_count<500>(&g_cnt[C_START], (old & ~255u) + 256u, budget);
    }
    return;
  }
  const int bi = (cta >> 5) * 4 + ((cta >> 2) & 3);
  const int bj = ((cta >> 4) & 1) * 4 + (cta & 3);

  auto load_first = [&](int n) {
    const uint32_t st = sb + n * STAGE, fb = bars + (B_FX + n) * 8;
    KS(64 + n);
    mbar_expect_tx(fb, STAGE);
    tma_load(st, &mx, fb, n * 64, bi * 128);
    tma_load(st + 16384, &mw, fb, 1024 + bj * 128, n * 64);
    tma_load(st + 24576, &mw, fb, 2048 + bj * 128, n * 64);
  };
  if (warp == 8 && elect_one()) {
    TS(7);
#pragma unroll
    for (int s = 0; s < NST; s++) mbar_init(bars + (B_FX + s) * 8, 1);
    asm volatile("fence.mbarrier_init.release.cluster;" ::: "memory");
    fence_async_smem();
#pragma unroll
    for (int n = 0; n < P0_FIRST; n++) load_first(n);
  }
  if (wg < 2 && (warp & 3) < EARLY_N && lane < (wg ? 8 : 16)) {
    const int n = warp & 3;
    const __nv_bfloat16* p = wg ? P.w + (size_t)(n * 64 + bi + (lane >> 1) * 16) * (3 * kD) + 1024 + (lane & 1) * 1024 + bj * 128
                                : P.x + (size_t)(bi * 128 + bj * 16 + lane) * kD + n * 64;
    if (n) __nanosleep(n * EARLY_GAP);
    asm volatile("prefetch.global.L2 [%0];" :: "l"(p));
  }
  __syncwarp();

  if (wg == 3) {
    asm volatile("setmaxnreg.dec.sync.aligned.u32 64;");
    const int t3 = tid - 384, w3 = warp - 12;
    if (t3 == 0) TSG(0);
    if (t3 < 80) *reinterpret_cast<uint4*>(&g_kvr[cta * 320 + t3 * 4]) = make_uint4(0, 0, 0, 0);
    if (t3 < 17) st_tagged(t3 < 16 ? &g_gate[bi * 128 + bj * 16 + t3] : &g_key[cta], 0, 1);
    bar_sync(0, 512);
#pragma unroll 1
    for (int u = 0; u < 4; u++) {
      const uint4 v = ldg_nc(P.w_phi + bj * 4096 + (u * 128 + t3) * 8);
      sts128(sb + SM_WPHI + u * 2048 + (t3 >> 2) * 64 + (((t3 & 3) ^ ((t3 >> 3) & 3)) << 4),
             pack2(LOG2E * bf_lo(v.x), LOG2E * bf_hi(v.x)), pack2(LOG2E * bf_lo(v.y), LOG2E * bf_hi(v.y)),
             pack2(LOG2E * bf_lo(v.z), LOG2E * bf_hi(v.z)), pack2(LOG2E * bf_lo(v.w), LOG2E * bf_hi(v.w)));
    }
    fence_async_smem();
    warp_arrive(bars + B_WPHI * 8, lane);
    bar_sync(6, 256);
    const uint32_t target = lds32(sb + SM_MISC);
    uint32_t key;
    {
      uint32_t kk[4];
      lds128(sb + SM_MISC + 16, kk);
      if (t3 == 0) st_tagged(&g_key[cta], max(max(kk[0], kk[1]), max(kk[2], kk[3])), target);
      uint2 k, gv;
      __nanosleep(POLLR);
      do {
        __nanosleep(POLL1);
        k = ld_tagged(&g_key[t3]);
        gv = ld_tagged(&g_gate[bi * 128 + t3]);
        budget -= 4;
      } while (!__all_sync(0xffffffffu, k.y == target && gv.y == target) && budget > 0);
      key = __reduce_max_sync(0xffffffffu, k.x);
      if (lane == 0) sts32(sb + SM_MISC + 32 + w3 * 4, key);
      sts32(sb + SM_G + t3 * 4, gv.x);
      bar_sync(5, 128);
      lds128(sb + SM_MISC + 32, kk);
      key = max(max(kk[0], kk[1]), max(kk[2], kk[3]));
    }
    const int idx = (0xFFFF - (key & 0xFFFF)) & (kS - 1);
    if (t3 == 0) { sts32(sb + SM_MISC + 4, idx); TS(8); }
    warp_arrive(bars + B_INFO * 8, lane);
    {
      const uint4 v = ldg_nc(P.x + (size_t)idx * kD + t3 * 8);
      sts128(sb + SM_BAND + t3 * 16, v.x, v.y, v.z, v.w);
    }
    const int t2 = (lane & 3) * 2, row = w3 * 16 + (lane >> 2);
    float a[4];
    uint32_t buf = 0, ph = 0;
    fence_async_smem();
    bar_sync(5, 128);
    {
      const int r = cta >> 4;
#pragma unroll 1
      for (int part = 0; part < 2; part++) {
        const int n = part ? 14 - 2 * r : 2 * r;
        moe_chunks<false>(a, n, buf, ph, P.da, P.dxs + (part ? 0 : (16 - n) * 8), lane == 0);
        uint2* dst = &g_pre[(((cta >> 2) & 2) + 1 - part) * kF + ((r - 1 + part) * 8 + (cta & 7)) * 64 + row];
        if (t2 == 0 && n) { st_tagged(dst, __float_as_uint(a[0]), target); st_tagged(dst + 8, __float_as_uint(a[2]), target); }
      }
    }
    if (t3 == 0) TS(9);
    bar_sync(5, 128);
    sts128(sb + SM_BAND + t3 * 16, 0, 0, 0, 0);
    {
      __nanosleep(POLL0);
      float gs, us;
      gather<kF, 4>(&g_pre[(cta >> 2) * 112 + min(t3, 111)], target, gs, us, budget);
      bar_sync(5, 128);
      if (t3 < 112) sts16(sb + SM_BAND + 112 + (t3 >> 3) * 128 + (t3 & 7) * 2, pack2(gs * sigmoidf(gs) * us, 0.f));
    }
    fence_async_smem();
    bar_sync(5, 128);
    if (t3 == 0) TS(12);
    moe_chunks<true>(a, 7, buf, ph, P.da, P.dband + 7, lane == 0);
    if (lane == 0) mbar_arrive(bars + B_MD * 8);
    if (t3 == 0) TS(10);
    if (t2 < 4) {
      uint2* dst = &g_yp[(cta >> 2) * kD + (cta & 3) * 256 + t2 * 64 + row];
      st_tagged(dst, __float_as_uint(a[0]), target); st_tagged(dst + 8, __float_as_uint(a[2]), target);
      st_tagged(dst + 64, __float_as_uint(a[1]), target); st_tagged(dst + 72, __float_as_uint(a[3]), target);
    }
    if ((idx >> 7) == bi) {
      mbar_wait(bars + (B_PUB + 3) * 8, 0, budget);
      if (w3 == 0) probe(&g_yp[lane * kD + bj * 128], target, budget);
      bar_sync(5, 128);
      float y = 0.f;
#pragma unroll 1
      for (int hf = 0; hf < 2; hf++) {
        float y0, y1;
        gather<kD, 16>(&g_yp[hf * 16 * kD + bj * 128 + t3], target, y0, y1, budget);
        y += y0 + y1;
      }
      const uint32_t ob = key >> 16;
      const float upd = y * sigmoidf(__uint_as_float(((ob & 0x8000u) ? (ob ^ 0x8000u) : (~ob & 0xFFFFu)) << 16));
      const float xv = __bfloat162float(P.x[(size_t)idx * kD + bj * 128 + t3]);
      mbar_wait(bars + (B_XT + 1) * 8, 0, budget);
      sts16(sb + ((idx & 64) ? SM_PHI : SM_MOE) + (t3 >> 6) * 8192 + (idx & 63) * 128 + ((((t3 >> 3) & 7) ^ (idx & 7)) << 4) + (t3 & 7) * 2, pack2(xv + upd, 0.f));
      warp_arrive(bars + B_XP * 8, lane);
      if (t3 == 0) TS(11);
    }
  } else if (wg < 2) {
    asm volatile("setmaxnreg.inc.sync.aligned.u32 208;");
    const int tw = tid & 127, w = warp & 3, g = lane >> 2, t = lane & 3;
    const bool lane0 = lane == 0;
    if (wg == 0) sts128(sb + SM_ONE + (tw & 63) * 16, 0x3f803f80u, 0x3f803f80u, 0x3f803f80u, 0x3f803f80u);
    bar_sync(0, 512);
    if (wg == 1) {
      float sr[4], sg[4];
      zero(sr); zero(sg);
#pragma unroll 1
      for (int c = 0; c < 4; c++) {
        mbar_wait(bars + (B_RX + c) * 8, 0, budget);
        uint32_t rs[4], gs[4], xs[4][4];
        lds128(sb + SM_V + c * 512 + lane * 16, rs);
        lds128(sb + SM_V + 2048 + c * 512 + lane * 16, gs);
#pragma unroll
        for (int r = 0; r < 4; r++) lds128(sb + SM_PHI + c * 8192 + (w * 4 + r) * 512 + lane * 16, xs[r]);
#pragma unroll
        for (int e = 0; e < 4; e++) {
          const float r0 = bf_lo(rs[e]), r1 = bf_hi(rs[e]), g0 = bf_lo(gs[e]), g1 = bf_hi(gs[e]);
#pragma unroll
          for (int r = 0; r < 4; r++) {
            const float x0 = bf_lo(xs[r][e]), x1 = bf_hi(xs[r][e]);
            sr[r] = fma_v(x0, r0, sr[r]); sg[r] = fma_v(x0, g0, sg[r]);
            sr[r] = fma_v(x1, r1, sr[r]); sg[r] = fma_v(x1, g1, sg[r]);
            if (r != 1) yield_slot();
          }
        }
      }
      fence_async_smem();
      __syncwarp();
      if (lane < 3) mbar_arrive(bars + (B_ME + lane) * 8);
      const bool b4 = lane & 16, b3 = lane & 8, b2 = lane & 4;
      const float v = qsum(fold(fold(fold(sr[0], sg[0], b4, 16), fold(sr[2], sg[2], b4, 16), b3, 8),
                                fold(fold(sr[1], sg[1], b4, 16), fold(sr[3], sg[3], b4, 16), b3, 8), b2, 4));
      const int row = bi * 128 + bj * 16 + w * 4 + (g & 3);
      const uint32_t rb = pack2(v + 0.f, 0.f);
      const uint32_t ob = (rb & 0x8000u) ? (~rb & 0xFFFFu) : (rb | 0x8000u);
      const uint32_t best = __reduce_max_sync(0xffffffffu, b4 ? 0u : (ob << 16) | (0xFFFFu - row));
      mbar_wait(bars + B_EPOCH * 8, 0, budget);
      const uint32_t tag = lds32(sb + SM_MISC);
      if (lane0) sts32(sb + SM_MISC + 16 + w * 4, best);
      if (b4 && t == 0) st_tagged(&g_gate[row], __float_as_uint(sigmoidf(v)), tag);
      if (tw == 0) TS(14);
      bar_arrive(6, 256);
      bar_sync(1, 256);
    }

    {
      float acc[2][64];
      if (tw == 0) TS(16 + wg * 16);
      if (QD1 != QD2 && wg == 0) mainloop128<QD1>(acc, P.da, P.db, 0, 0, 16, lane0, budget, cta, 0);
      else mainloop128<QD2>(acc, P.da, P.db, wg, wg, 16, lane0, budget, cta, wg * 16);
      bar_sync(1 + wg, 256);
      wg_wait<0>();
      pin(acc[0]); pin(acc[1]);
      if (lane0) mbar_arrive_n(bars + (B_EM + wg) * 8, 2);
      if (tw == 0) TS(17 + wg * 16);
      float p[4][16];
      uint32_t vp[8][4];
      const uint32_t av = sb + SM_V + (w * 16 + g) * 64 + ((t ^ (g >> 1)) << 4);
      {
        uint32_t kf[4][2][4];
#pragma unroll
        for (int u = 0; u < 4; u++)
#pragma unroll
          for (int s = 0; s < 2; s++)
#pragma unroll
            for (int r = 0; r < 4; r++) kf[u][s][r] = pack2(acc[u & 1][16 * (u >> 1) + 8 * s + 2 * r], acc[u & 1][16 * (u >> 1) + 8 * s + 2 * r + 1]);
        mbar_wait(bars + B_WPHI * 8, 0, budget);
        const uint64_t dw = P.dw + wg * 256;
        wg_fence();
#pragma unroll
        for (int u = 0; u < 4; u++) {
          wgmma_m64n32k16_rs<1>(p[u], kf[u][0], dw + (u >> 1) * 128, 0);
          wgmma_m64n32k16_rs<1>(p[u], kf[u][1], dw + (u >> 1) * 128 + 64, 1);
        }
        wg_commit();
#pragma unroll
        for (int u = 0; u < 8; u++) {
          const float* a = &acc[(u >> 1) & 1][32 + 16 * (u >> 2) + 2 * (u & 1)];
          vp[u][0] = pack2(a[0], a[1]); vp[u][1] = pack2(a[4], a[5]); vp[u][2] = pack2(a[8], a[9]); vp[u][3] = pack2(a[12], a[13]);
          if (u < 4) sts128(av + (u >> 1) * 4096 + (u & 1) * 512, vp[u][0], vp[u][1], vp[u][2], vp[u][3]);
        }
        pinr(vp);
        wg_wait<0>();
#pragma unroll
        for (int u = 0; u < 4; u++) pin(p[u]);
      }
      if (tw == 0) TS(18 + wg * 16);
      float kv[2][20];
      {
        const uint32_t sphi = sb + SM_PHI + (w * 16 + (lane & 15)) * 128 + (((lane >> 4) ^ (lane & 7)) << 4);
        uint32_t top = EXP_TOP;
        uint32_t pk[4][2][4];
        float ps[2];
        uint32_t sh[1][4];
        uint32_t redo = 0, redo0 = 0;
        const uint32_t astage = sb + (w * 16 + (lane & 15)) * 64 + (((lane >> 4) ^ ((lane >> 1) & 3)) << 4);
        auto stage_kv = [&](int hh) {
#pragma unroll
          for (int q = 0; q < 2; q++) {
            const float* a = &kv[hh][8 * q];
            stmatrix4((astage ^ (q * 32)) + (hh ? SM_PHI : SM_Z), pack2(a[0], a[1]), pack2(a[2], a[3]), pack2(a[4], a[5]), pack2(a[6], a[7]));
          }
        };
#pragma unroll
        for (int i = 0; i < 11; i++) {
          if (i >= 3) {
            const int j = i - 3;
            const uint32_t s2 = add2(sh[0][2], sh[0][3]);
            top = __vmaxu2(top, s2);
            store_phi((sphi ^ ((j & 1) * 64)) + (j & 2) * 4096, pk[j & 3], rcp2(bf_lo(s2)), rcp2(bf_hi(s2)));
          }
          if (i >= 2 && i <= 9) { sh[0][2] = add2(sh[0][0], sh[0][1]); sh[0][3] = __shfl_xor_sync(0xffffffffu, sh[0][2], 2); }
          if (i >= 1 && i <= 8) { sh[0][0] = pack2(ps[0], ps[1]); sh[0][1] = __shfl_xor_sync(0xffffffffu, sh[0][0], 1); }
          if (i == 1) sh[0][2] = sh[0][3] = 0;
          if (i < 8) {
            pin(p[i >> 1]);
            float e[16];
#pragma unroll
            for (int c = 0; c < 16; c++) e[c] = ex2((i & 1) ? -p[i >> 1][c] : p[i >> 1][c]);
            pack_sums(e, pk[i & 3], ps);
            pinr(pk[i & 3]); pin(ps);
          }
          if (i < 10) yield_slot();
          if (i >= 1 && i <= 9) pinr(sh);
          if (i == 7) { wg_wait<0>(); pin(kv[0]); stage_kv(0); }
          if (i == 2 && wg) mbar_wait(bars + B_RD * 8, 0, budget);
          if (i >= 4 && !(i & 1)) {
            const int u = (i - 4) >> 1;
            fence_async_smem();
            wg_wait<0>();
            if (!(u & 1)) bar_sync(7 + wg, 128);
            else asm volatile("{\n.reg .pred p, q;\nsetp.ne.b32 p, %2, %3;\nbar.red.or.pred q, %1, 128, p;\nselp.u32 %0, 1, 0, q;\n}"
                              : "=r"(redo) : "r"(7 + wg), "r"(top), "n"(EXP_TOP) : "memory");
            if (u == 1) redo0 = redo;
            if (u == 2 && lane0 && !redo0) mbar_arrive(bars + (B_RH + wg) * 8);
            issue_kv(kv[u >> 1], P.dphi + (u & 1) * 512, P.dv - (u & 1) * DV_TILE, u & 1);
            if (u == 1 || u == 2) {
#pragma unroll
              for (int r = 0; r < 2; r++) sts128(av + ((u + 1) & 1) * 4096 + r * 512, vp[2 * u + 2 + r][0], vp[2 * u + 2 + r][1], vp[2 * u + 2 + r][2], vp[2 * u + 2 + r][3]);
            }
            if (u < 3) yield_slot();
          }
        }
        if (tw == 0) TS(19 + wg * 16);
        wg_wait<0>();
        pin(kv[0]); pin(kv[1]);
        if (__builtin_expect(__any_sync(0xffffffffu, redo), 0)) {
#pragma unroll 1
          for (int u = 0; u < 4; u++) {
            bar_sync(7 + wg, 128);
#pragma unroll 1
            for (int sg = 0; sg < 2; sg++) {
              float e[16];
              exp_shifted(p[0], sg ? -1.f : 1.f, e);
              pack_sums(e, pk[0], ps);
              store_phi(sphi ^ (sg * 64), pk[0], rcp2(qsum(ps[0])), rcp2(qsum(ps[1])));
            }
            sts128(av, vp[0][0], vp[0][1], vp[0][2], vp[0][3]);
            sts128(av + 512, vp[1][0], vp[1][1], vp[1][2], vp[1][3]);
            fence_async_smem();
            bar_sync(7 + wg, 128);
            issue_kv(kv[1], P.dphi, P.dv, u & 1);
            wg_wait<0>();
            pin(kv[1]);
#pragma unroll
            for (int c = 0; c < 16; c++) { p[0][c] = p[1][c]; p[1][c] = p[2][c]; p[2][c] = p[3][c]; }
#pragma unroll
            for (int c = 0; c < 24; c++) vp[c >> 2][c & 3] = vp[(c >> 2) + 2][c & 3];
            if (u == 1) {
#pragma unroll
              for (int c = 0; c < 20; c++) kv[0][c] = kv[1][c];
            }
          }
          if (__any_sync(0xffffffffu, redo0)) {
            stage_kv(0);
            fence_async_smem();
            warp_arrive(bars + (B_RH + wg) * 8, lane);
          }
        }
        if (tw == 0) TS(20 + wg * 16);
        bar_sync(7 + wg, 128);
        stage_kv(1);
      }
      {
        const uint32_t z = pack2(t == 0 ? kv[0][16] : t == 1 ? kv[1][16] : t == 2 ? kv[0][18] : kv[1][18], 0.0625f);
        sts128(sb + SM_PHI + 4096 + ((w & 1) * 16 + (t >> 1) * 8 + g) * 64 + ((((w & 2) + (t & 1)) ^ (g >> 1)) << 4), z, z, z, z);
      }
      fence_async_smem();
      warp_arrive(bars + (B_RED + wg) * 8, lane);
      if (tw == 0) TS(51 + wg * 4);
    }

    uint32_t stash = sb + 3 * STAGE + w * 4096 + lane * 16;
    const int rowl = wg * 64 + w * 16 + g;
    mbar_wait(bars + B_INFO * 8, 0, budget);
    const float gA = ldsf(sb + SM_G + rowl * 4), gB = ldsf(sb + SM_G + rowl * 4 + 32);
    uint32_t own = sb + 3 * STAGE + rowl * 128 + ((t ^ g) << 4);
    uint32_t sx = sb + (wg ? SM_PHI : SM_MOE) + (w * 16 + (lane & 15)) * 128 + (((lane >> 4) ^ (lane & 7)) << 4);
    uint32_t routed = lds32(sb + SM_MISC + 4) - (bi * 128 + rowl);
    asm volatile("" : "+r"(own), "+r"(stash), "+r"(sx), "+r"(routed));
    {
      float p[4][16];
      uint32_t ef[2][4][4];
      uint32_t qf[4][2][4];
      auto pack_q = [&](const float (&a)[64]) {
#pragma unroll
        for (int i = 0; i < 32; i++) qf[i >> 3][(i >> 2) & 1][i & 3] = pack2(a[2 * i], a[2 * i + 1]);
      };
      if (wg == 0) {
        float acc[2][64];
        bar_sync(2, 256);
        if (tw == 0) TS(22);
        mainloop128<QD3>(acc, P.da, P.db, 32 % NST, (32 / NST) & 1, 12, lane0, budget, cta, 32);
#pragma unroll
        for (int n = 44; n < 48; n++) {
          mbar_wait(bars + (B_FX + n % NST) * 8, (n / NST) & 1, budget);
          kstep64(acc[0], P.da + (n % NST) * (STAGE >> 4), P.db + (n % NST) * (STAGE >> 4), 1);
          if (n == 47) break;
          wg_wait<1>();
          if (n == 44) {
            if (lane0) mbar_arrive_n(bars + (B_EM + 43 % NST) * 8, 2);
            pin(acc[1]);
            bar_sync(7, 128);
          }
          if (n <= 45) {
#pragma unroll
            for (int u = (n - 44) * 4; u < (n - 43) * 4; u++) {
              const float* a = &acc[1][8 * u];
              sts128(stash + u * 512, pack2(a[0], a[1]), pack2(a[2], a[3]), pack2(a[4], a[5]), pack2(a[6], a[7]));
            }
          }
          if (n == 45) warp_arrive(bars + B_QS * 8, lane);
        }
        bar_sync(13, 256);
        wg_wait<0>();
        pin(acc[0]);
        if (tw == 0) TS(15);
        pack_q(acc[0]);
        issue_pq(p, qf, P.dw, 0);
        bar_arrive(14, 256);
        wg_wait<0>();
      } else {
        float acc[64];
        mbar_wait(bars + B_QS * 8, 0, budget);
#pragma unroll
        for (int u = 0; u < 8; u++) lds128(stash + u * 512, qf[u >> 1][u & 1]);
        pinr(qf[3]);
        bar_sync(13, 256);
#pragma unroll
        for (int n = 44; n < 48; n++) {
#pragma unroll
          for (int hf = 0; hf < 2; hf++) {
            const uint64_t da = P.da + 512 + (n % NST) * (STAGE >> 4) + hf * 4, db = P.db + (n % NST) * (STAGE >> 4) + hf * 256;
            wg_wait<1>();
            if (hf && n > 44 && lane0) mbar_arrive_n(bars + (B_EM + (n - 1) % NST) * 8, 2);
            wg_fence();
            wgmma_m64n128k16_ss<0, 1>(acc, da, db, n > 44 || hf);
            wgmma_m64n128k16_ss<0, 1>(acc, da + 2, db + 128, 1);
            wg_commit();
          }
          if (n == 44) bar_sync(14, 256);
          if (n == 46) issue_pq(p, qf, P.dw, 0);
        }
        wg_wait<0>();
        pin(acc);
        if (lane0) { mbar_arrive_n(bars + (B_EM + 47 % NST) * 8, 2); mbar_arrive(bars + B_T3 * 8); }
        if (tw == 0) TS(23);
        pack_q(acc);
        issue_pq(p, qf, P.dw, 1);
        wg_wait<0>();
      }
#pragma unroll
      for (int h = 0; h < 4; h++) pin(p[h]);
      if (tw == 0) TS(24 + wg * 16);

      RG(1);
      pair_frags(p[0], p[1], ef);
      if (YIELD_EXP && wg) bar_arrive(11, 256);
#pragma unroll 1
      for (int pr = 0; pr < 2; pr++) {
        float np[2][20], nm[2][20];
        RG(2 + pr * 8);
        mbar_wait(bars + (B_KV + pr) * 8, 0, budget);
        RG(3 + pr * 8);
        wg_fence();
#pragma unroll
        for (int hh = 0; hh < 2; hh++) {
          const uint64_t dk = P.dkv - (uint64_t)pr * ((384ull << 16) - 512ull) - hh * ((255ull << 16) - 256ull);
          wgmma_m64n40k16_rs<1>(np[hh], ef[hh][0], dk, 0);
          wgmma_m64n40k16_rs<1>(np[hh], ef[hh][1], dk + 64, 1);
          wgmma_m64n40k16_rs<1>(nm[hh], ef[hh][2], dk + 128 - (126ull << 16), 0);
          wgmma_m64n40k16_rs<1>(nm[hh], ef[hh][3], dk + 192 - (126ull << 16), 1);
          wg_commit();
        }
        uint32_t o[4][4];
#pragma unroll
        for (int hh = 0; hh < 2; hh++) {
          if (hh == 0) wg_wait<1>(); else wg_wait<0>();
          pin(np[hh]); pin(nm[hh]);
          RG(4 + hh + pr * 8);
#pragma unroll
          for (int r = 0; r < 2; r++) {
            const float dp = np[hh][16 + 2 * r], sp = np[hh][17 + 2 * r], dm = nm[hh][16 + 2 * r], sm = nm[hh][17 + 2 * r];
            const float inv = (r == 0 ? gA : gB) * rcp(fmaf(dp, sm, fmaf(1e-6f, sm, dm) * sp));
            const float cp = sm * inv, cm = sp * inv;
#pragma unroll
            for (int c = 0; c < 4; c++)
              o[hh * 2 + r][c] = pack2(fmaf(np[hh][4 * c + 2 * r], cp, nm[hh][4 * c + 2 * r] * cm), fmaf(np[hh][4 * c + 2 * r + 1], cp, nm[hh][4 * c + 2 * r + 1] * cm));
          }
        }
        pinr(o);
        yield_slot();
#pragma unroll
        for (int i = 0; i < 4; i++) sts128((own ^ ((i >> 1) * 64)) + (i & 1) * 1024, o[i][0], o[i][1], o[i][2], o[i][3]);
        fence_async_smem();
        RG(6 + pr * 8);
        warp_arrive(bars + (B_PUB + wg * 2 + pr) * 8, lane);
        RG(7 + pr * 8);
        if (tw == 0) TS(25 + pr + wg * 16);
        if (pr) break;
        own += STAGE;
        if (YIELD_EXP && !wg) bar_sync(11, 256);
        RG(9);
        pin(p[2]); pin(p[3]);
        pair_frags(p[2], p[3], ef);
      }
    }
    uint32_t xf[8][4];
    if (!wg) {
      mbar_wait(bars + B_XT * 8, 0, budget);
      load_x<STAGE>(sx - SM_MOE, xf);
      pinr(xf);
      fence_async_smem();
      warp_arrive(bars + B_XR * 8, lane);
      mbar_wait(bars + (B_PUB + 3) * 8, 0, budget);
    } else {
#pragma unroll
      for (int i = 0; i < 32; i++) xf[i >> 2][i & 3] = 0;
    }
    bar_sync(7 + wg, 128);

    RG(18);
    float oacc[64];
    {
      const uint64_t dam = P.da + wg * 512;
      mbar_wait2(bars + (B_FX + 3) * 8, bars + (B_FX + 4) * 8, 1, budget);
      kstep64(oacc, dam + 3 * (STAGE >> 4), P.db + 3 * (STAGE >> 4), 0);
      if (tw == 0) TS(27 + wg * 16);
      kstep64(oacc, dam + 4 * (STAGE >> 4), P.db + 4 * (STAGE >> 4), 1);
      wg_wait<1>();
      if (lane0) mbar_arrive(bars + (B_EM + 3) * 8);
      if (wg) {
        wg_wait<0>();
        if (lane0) mbar_arrive(bars + (B_EM + 4) * 8);
        mbar_wait(bars + (B_XT + 1) * 8, 0, budget);
        load_x<8192>(sx, xf);
      }
      const uint32_t fy = (B_FY + wg * NST - B_FX) * 8;
      uint32_t rel = bars + (wg ? B_DUMMY : B_EM + 4) * 8;
#pragma unroll 1
      for (uint32_t ph = 0; ph < 2; ph++) {
#pragma unroll 1
        for (uint32_t slot = 0; slot < NST; slot++) {
          const uint32_t fx = bars + B_FX * 8 + slot * 8;
          mbar_wait2(fx, fx + fy, ph, budget);
          kstep64(oacc, dam + slot * (STAGE >> 4), P.db + slot * (STAGE >> 4), 1);
          wg_wait<1>();
          arrive_one(rel);
          rel = fx + (B_EM - B_FX) * 8;
        }
      }
      if (wg) {
#pragma unroll 1
        for (uint32_t slot = 0; slot < 4; slot++) mbar_wait(bars + (B_FY + NST + slot) * 8, 0, budget);
        bar_sync(12, 256);
      }
#pragma unroll 1
      for (uint32_t slot = 0; slot < 4; slot++) {
        if (!wg) mbar_wait2(bars + (B_FX + slot) * 8, bars + (B_FY + slot) * 8, 0, budget);
        wg_wait<1>();
        kstep64(oacc, dam + slot * (STAGE >> 4), P.db + slot * (STAGE >> 4), 1);
      }
      if (!wg) bar_arrive(12, 256);
    }
    if (!wg) mbar_wait(bars + B_MD * 8, 0, budget);
    if (__any_sync(0xffffffffu, (routed & ~8u) == 0)) {
      uint32_t xu[8][4];
      mbar_wait(bars + B_XP * 8, 0, budget);
      load_x<8192>(sx, xu);
#pragma unroll
      for (int i = 0; i < 32; i++) if (routed == (i & 1) * 8u) xf[i >> 2][i & 3] = xu[i >> 2][i & 3];
    }
    const float hA = 1.0f - gA, hB = 1.0f - gB;
    float xv[64];
#pragma unroll
    for (int i = 0; i < 32; i++) { xv[2 * i] = bf_lo(xf[i >> 2][i & 3]); xv[2 * i + 1] = bf_hi(xf[i >> 2][i & 3]); }
    pin(xv);
    yield_slot();
    wg_wait<0>();
    pin(oacc);
    if (tw == 0) TS(29 + wg * 16);
#pragma unroll
    for (int hf = 0; hf < 2; hf++) {
#pragma unroll
      for (int u = hf * 4; u < hf * 4 + 4; u++) {
        const float* a = &oacc[8 * u];
        const float* b = &xv[8 * u];
        stmatrix4((sx ^ ((u & 3) * 32)) + hf * 8192,
                  pack2(fmaf(hA, b[0], a[0]), fmaf(hA, b[1], a[1])), pack2(fmaf(hB, b[2], a[2]), fmaf(hB, b[3], a[3])),
                  pack2(fmaf(hA, b[4], a[4]), fmaf(hA, b[5], a[5])), pack2(fmaf(hB, b[6], a[6]), fmaf(hB, b[7], a[7])));
      }
      fence_async_smem();
      __syncwarp();
      if (elect_one()) tma_store(&mout, sb + (wg ? SM_PHI : SM_MOE) + hf * 8192 + w * 2048, bj * 128 + hf * 64, bi * 128 + warp * 16);
    }
    if (elect_one()) {
      asm volatile("cp.async.bulk.commit_group;" ::: "memory");
      asm volatile("cp.async.bulk.wait_group.read 0;" ::: "memory");
    }
  } else {
    asm volatile("setmaxnreg.dec.sync.aligned.u32 32;");
    if (warp == 8) {
      bar_arrive(0, 512);
      if (elect_one()) {
#pragma unroll 1
        for (int n = P0_FIRST; n < NST; n++) load_first(n);
      }
      __syncwarp();
      bar_sync(10, 64);
    } else {
      if (warp == 9) {
        if (elect_one()) {
#pragma unroll
          for (int s = B_FY; s < B_NUM; s++) mbar_init(bars + s * 8, s < B_WPHI ? 1 : s < B_EM ? 4 : 8);
          asm volatile("fence.mbarrier_init.release.cluster;" ::: "memory");
          fence_async_smem();
        }
        __syncwarp();
        bar_arrive(10, 64);
      }
      bar_sync(0, 512);
    }
    if (!elect_one()) return;
    if (warp == 8) {
      uint32_t slot = 0, ph = 0;
#pragma unroll 1
      for (int n = NST; n < 48; n++) {
        const int t = n >> 4, k = n & 15;
        const int c0 = t == 2 ? bj * 128 : 1024 + bj * 128 + t * 64, c1 = t == 2 ? c0 + 64 : c0 + 1024;
        const uint32_t st = sb + slot * STAGE, fb = bars + (B_FX + slot) * 8;
        if (n <= NST + 3 * RSTEP && (n - NST) % RSTEP == 0) {
          const int c = (n - NST) / RSTEP;
          mbar_expect_tx(bars + (B_RX + c) * 8, c == 0 ? 8192 + 4096 : 8192);
          tma_load(sb + SM_PHI + c * 8192, &mxr, bars + (B_RX + c) * 8, c * 256, bi * 128 + bj * 16);
          if (c == 0) { bulk_load(sb + SM_V, P.w_r, 2048, bars + B_RX * 8); bulk_load(sb + SM_V + 2048, P.gate_w, 2048, bars + B_RX * 8); }
        }
        mbar_wait(bars + (B_EM + slot) * 8, ph, budget);
        KS(64 + n);
        mbar_expect_tx(fb, STAGE);
        tma_load(st, &mx, fb, k * 64, bi * 128);
        tma_load(st + 16384, &mw, fb, c0, k * 64);
        tma_load(st + 24576, &mw, fb, c1, k * 64);
        if (++slot == NST) { slot = 0; ph ^= 1; }
      }
#pragma unroll 1
      for (int s = 0; s < 16; s++) {
        const int p = s < 2 ? s : (s >= 9), q = s < 9 ? s - 2 : s - 9;
        const int k0 = (s < 2 ? bj : q + (q >= bj)) * 128 + p * 64;
        const uint32_t st = sb + slot * STAGE, fb = bars + (B_FX + slot) * 8;
        mbar_wait(bars + (B_EM + slot) * 8, ph, budget);
        KS(64 + 48 + s);
        mbar_expect_tx(fb, 16384);
        tma_load(st + 16384, &mwo, fb, bj * 128, k0);
        tma_load(st + 24576, &mwo, fb, bj * 128 + 64, k0);
        if (s == XS1 || s == XS0) {
#pragma unroll 1
          for (int m = s == XS1; m >= (s != XS0); m--) {
            if (m) mbar_wait(bars + (B_RD + 1) * 8, 0, budget);
            mbar_expect_tx(bars + (B_XT + m) * 8, 16384);
            tma_load(sb + (m ? SM_PHI : 0), &mx64, bars + (B_XT + m) * 8, bj * 128, bi * 128 + m * 64);
            tma_load(sb + (m ? SM_PHI + 8192 : STAGE), &mx64, bars + (B_XT + m) * 8, bj * 128 + 64, bi * 128 + m * 64);
          }
        }
        if (++slot == NST) { slot = 0; ph ^= 1; }
      }
      if (REPF) prefetch_map(&mout);
    } else if (warp == 9) {
      prefetch_map(&mo); prefetch_map(&mout);
      uint32_t old;
      asm volatile("atom.add.release.gpu.global.u32 %0, [%1], 1;" : "=r"(old) : "l"(&g_cnt[C_START]) : "memory");
      sts32(sb + SM_MISC, (old & ~255u) + 256u);
      mbar_arrive(bars + B_EPOCH * 8);
      const CUtensorMap* m = (cta & 8) ? &mu : &mg;
      const int l0 = (cta >> 4) * 14, a0 = (cta & 7) * 64, d1 = (cta >> 2) * 112 - 14 * 16, d2 = (cta & 3) * 4;
      uint32_t buf = 0, ph = 0;
#pragma unroll 1
      for (int c = 0; c < 21; c++) {
        const uint32_t dst = sb + moe_buf(buf), fb = bars + (B_MF + buf) * 8;
        mbar_wait(bars + (B_ME + buf) * 8, ph, budget);
        mbar_expect_tx(fb, 8192);
        if (c < 14) tma_load(dst, m, fb, a0 + ((l0 + c) >> 4) * 512, ((l0 + c) & 15) * 64); else tma_load3(dst, &md, fb, d1 + c * 16, d2);
        if (DPF && c == 16) {
#pragma unroll 1
          for (int f = 17; f < 21; f++) { __nanosleep(MGAP); tma_prefetch3(&md, d1 + f * 16, d2); }
        }
        if (c < 2) __nanosleep(MGAP);
        if (++buf == 3) { buf = 0; ph ^= 1; }
      }
      mbar_wait(bars + (B_PUB + 1) * 8, 0, budget);
      tma_store(&mo, sb + 4 * STAGE, bj * 128 + 64, bi * 128);
      mbar_wait(bars + (B_PUB + 3) * 8, 0, budget);
      {
        tma_store(&mo, sb + 4 * STAGE + 8192, bj * 128 + 64, bi * 128 + 64);
        asm volatile("cp.async.bulk.commit_group;" ::: "memory");
        asm volatile("cp.async.bulk.wait_group 0;" ::: "memory");
        mbar_arrive(bars + B_PS * 8);
      }
      signal_add(&g_cnt[(C_O + bi * 4 + 1) * 32], 32u);
      TS(57);
      wait_count<POLLF>(&g_cnt[(C_O + bi * 4 + 1) * 32], (old & ~255u) + 256u, budget);
      mbar_arrive(bars + B_P1 * 8);
      TS(3);
    } else {
      const int u = warp - 10, hp = bj * 2 + u;
      mbar_wait(bars + B_EPOCH * 8, 0, budget);
      const uint32_t target = lds32(sb + SM_MISC);
      mbar_wait(bars + B_INFO * 8, 0, budget);
      wait_count<200>(&g_cnt[C_START], target, budget);
      fence_async_global();
#pragma unroll 1
      for (int e = 0; e < 2; e++) {
        uint32_t* cnt = &g_cnt[(e ? C_O + bi * 4 + u * 2 : C_KV + hp) * 32];
        mbar_wait(bars + (e ? B_PUB + u * 2 : B_RH + u) * 8, 0, budget);
        if (e == 0) {
          static_assert(SM_PHI == SM_Z + 4096, "staging is contiguous");
#pragma unroll 1
          for (uint32_t c = 0; c < 10; c++) {
            if (c == 4) {
              asm volatile("cp.async.bulk.commit_group;" ::: "memory");
              asm volatile("cp.async.bulk.wait_group.read 0;" ::: "memory");
              mbar_wait(bars + (B_RED + u) * 8, 0, budget);
              if (u) mbar_arrive(bars + B_AF * 8);
            }
            bulk_reduce(&g_kvr[hp * 2560 + c * 256], sb + SM_Z + c * 1024, 1024);
            if (c < 9) __nanosleep(u && c >= 3 ? RED_GAP1 : RED_GAP0);
          }
          asm volatile("cp.async.bulk.commit_group;" ::: "memory");
          asm volatile("cp.async.bulk.wait_group 0;" ::: "memory");
          TS(21 + u * 16);
          mbar_arrive(bars + (B_RD + u) * 8);
        }
        if (e) {
          tma_store(&mo, sb + 3 * STAGE + u * 8192, bj * 128, bi * 128 + u * 64);
          asm volatile("cp.async.bulk.commit_group;" ::: "memory");
          asm volatile("cp.async.bulk.wait_group 0;" ::: "memory");
        }
        signal_add(cnt, e ? 32u : 16u);
        TS(e ? 56 + u * 2 : 60 + u);
        if (REPF && !e) prefetch_map(&mo);
        if (e == 0) {
          mbar_wait(bars + (u ? B_MD : B_AF) * 8, 0, budget);
        }
        wait_count<POLLF>(cnt, target, budget);
        fence_async_global();
        if (e == 0) {
          mbar_expect_tx(bars + (B_KV + u) * 8, 10240);
          bulk_load(sb + SM_V + u * 8192, &g_kvr[hp * 2560], 8192, bars + (B_KV + u) * 8);
          bulk_load(sb + SM_Z + u * 2048, &g_kvr[hp * 2560 + 2048], 2048, bars + (B_KV + u) * 8);
          TS(38 + u);
        }
      }
      TS(2 + u * 2);
      if (u == 0) mbar_wait2(bars + B_T3 * 8, bars + B_XR * 8, 0, budget);
      uint32_t slot = 0, ph = 1;
#pragma unroll 1
      for (int s = 2; s < 16; s++) {
        const int p = s >= 9, q = s < 9 ? s - 2 : s - 9;
        if (s == 6) mbar_wait(bars + B_PS * 8, 0, budget);
        if (s == 9) { mbar_wait(bars + B_P1 * 8, 0, budget); fence_async_global(); }
        const uint32_t fb = bars + (B_FY + u * NST + slot) * 8;
        mbar_wait(bars + (B_EM + slot) * 8, ph, budget);
        mbar_expect_tx(fb, 8192);
        tma_load(sb + slot * STAGE + u * 8192, &mo, fb, (q + (q >= bj)) * 128 + p * 64, bi * 128 + u * 64);
        if (++slot == NST) { slot = 0; ph ^= 1; }
      }
    }
  }
}

typedef CUresult (*EncodeFn)(CUtensorMap*, CUtensorMapDataType, cuuint32_t, void*, const cuuint64_t*, const cuuint64_t*, const cuuint32_t*,
                             const cuuint32_t*, CUtensorMapInterleave, CUtensorMapSwizzle, CUtensorMapL2promotion, CUtensorMapFloatOOBfill);

void make_map(EncodeFn enc, CUtensorMap* m, const void* ptr, uint64_t cols, uint64_t rows, uint32_t bc, uint32_t br, CUtensorMapSwizzle swz) {
  const cuuint64_t dims[2] = {cols, rows}, strides[1] = {cols * 2};
  const cuuint32_t box[2] = {bc, br}, es[2] = {1, 1};
  enc(m, CU_TENSOR_MAP_DATA_TYPE_BFLOAT16, 2, const_cast<void*>(ptr), dims, strides, box, es, CU_TENSOR_MAP_INTERLEAVE_NONE, swz,
      CU_TENSOR_MAP_L2_PROMOTION_L2_128B, CU_TENSOR_MAP_FLOAT_OOB_FILL_NONE);
}

}

extern "C" void kernel_launch(void* const* d_in, const int* in_sizes, int n_in, void* d_out, int out_size) {
  (void)in_sizes; (void)n_in; (void)out_size;
  void* fn = nullptr;
  cudaDriverEntryPointQueryResult qr;
  cudaGetDriverEntryPoint("cuTensorMapEncodeTiled", &fn, cudaEnableDefault, &qr);
  EncodeFn enc = (EncodeFn)fn;
  void* o_ptr = nullptr;
  cudaGetSymbolAddress(&o_ptr, g_o);
  CUtensorMap mx, mw, mwo, mo, mout, mxr, mg, mu, md, mx64;
  make_map(enc, &mx, d_in[0], kD, kS, 64, 128, CU_TENSOR_MAP_SWIZZLE_128B);
  make_map(enc, &mx64, d_in[0], kD, kS, 64, 64, CU_TENSOR_MAP_SWIZZLE_128B);
  make_map(enc, &mxr, d_in[0], kD, kS, 256, 16, CU_TENSOR_MAP_SWIZZLE_NONE);
  make_map(enc, &mw, d_in[1], 3 * kD, kD, 64, 64, CU_TENSOR_MAP_SWIZZLE_128B);
  make_map(enc, &mwo, d_in[3], kD, kD, 64, 64, CU_TENSOR_MAP_SWIZZLE_128B);
  make_map(enc, &mo, o_ptr, kD, kS, 64, 64, CU_TENSOR_MAP_SWIZZLE_128B);
  make_map(enc, &mout, d_out, kD, kS, 64, 16, CU_TENSOR_MAP_SWIZZLE_128B);
  make_map(enc, &mg, d_in[6], kF, kD, 64, 64, CU_TENSOR_MAP_SWIZZLE_128B);
  make_map(enc, &mu, d_in[7], kF, kD, 64, 64, CU_TENSOR_MAP_SWIZZLE_128B);
  {
    const cuuint64_t dims[3] = {64, kF, 16}, strides[2] = {kD * 2, 128};
    const cuuint32_t box[3] = {64, 16, 4}, es[3] = {1, 1, 1};
    enc(&md, CU_TENSOR_MAP_DATA_TYPE_BFLOAT16, 3, d_in[8], dims, strides, box, es, CU_TENSOR_MAP_INTERLEAVE_NONE, CU_TENSOR_MAP_SWIZZLE_128B,
        CU_TENSOR_MAP_L2_PROMOTION_L2_128B, CU_TENSOR_MAP_FLOAT_OOB_FILL_NONE);
  }
  Params P;
  P.x = (const __nv_bfloat16*)d_in[0];
  P.w = (const __nv_bfloat16*)d_in[1];
  P.w_phi = (const __nv_bfloat16*)d_in[2];
  P.w_r = (const __nv_bfloat16*)d_in[5];
  P.gate_w = (const __nv_bfloat16*)d_in[9];
  P.da = make_desc(sb, 16, 1024, 1);
  P.db = make_desc(sb + 16384, 8192, 1024, 1);
  P.dw = make_desc(sb + SM_WPHI, 16, 512, 2);
  P.dphi = make_desc(sb + SM_PHI, 16, 1024, 1);
  P.dv = make_desc(sb + SM_V, SM_ONE - SM_V, 512, 2);
  P.dkv = make_desc(sb + SM_V, SM_Z - SM_V, 512, 2);
  P.dband = make_desc(sb + SM_BAND, 128, 128, 0);
  P.dxs = make_desc(sb + SM_BAND, 16, 128, 0);
  int dev = 0, sms = 0;
  cudaGetDevice(&dev);
  cudaDeviceGetAttribute(&sms, cudaDevAttrMultiProcessorCount, dev);
  auto kern = sms == 132 ? fused_kernel<true> : fused_kernel<false>;
  cudaFuncSetAttribute(kern, cudaFuncAttributeMaxDynamicSharedMemorySize, SM_ALLOC);
  kern<<<132, 512, SM_ALLOC, cudaStreamPerThread>>>(P, mx, mw, mwo, mo, mout, mxr, mg, mu, md, mx64);
}
```
